```python
import torch

def _softmax(x, axis=-1):
    return torch.softmax(x, dim=axis)

def _gelu(x):
    return torch.nn.functional.gelu(x, approximate='tanh')

def _silu(x):
    return torch.nn.functional.silu(x)

def _sigmoid(x):
    return torch.sigmoid(x)

def _layernorm(x, axis=-1, eps=1e-05):
    m = x.mean(dim=axis, keepdim=True)
    v = x.var(dim=axis, keepdim=True, unbiased=False)
    return (x - m) / torch.sqrt(v + eps)

def _scatter_add(tgt, idx, src, axis=0):
    return tgt.clone().index_add_(axis, idx, src)

def _segment_sum(src, seg, n):
    out = torch.zeros((n,) + src.shape[1:], dtype=src.dtype)
    return out.index_add_(0, seg, src)

def _pad(x, pw):
    flat = tuple((v for pair in reversed(pw) for v in pair))
    return torch.nn.functional.pad(x, flat)
kernel_name = 'adaLN_cond__ssm_conv_h3__glu_gated_reglu__prompt'

def setup_inputs():

    _w = lambda a: (lambda t: t.to(torch.bfloat16) if t.is_floating_point() else t)(torch.as_tensor(a))

    def _A_setup():
        B, S, D = (1, 2048, 640)
        ks = 4
        return {'q': _w((lambda *s: torch.randn(*s, dtype=torch.bfloat16) * 0.05)(B, S, D)), 'k': _w((lambda *s: torch.randn(*s, dtype=torch.bfloat16) * 0.8)(B, S, D)), 'v': _w((lambda *s: torch.randn(*s, dtype=torch.bfloat16) * 0.8)(B, S, D)), 'shift_k': _w((lambda *s: torch.randn(*s, dtype=torch.bfloat16) * 0.8)(D, ks) * 0.5), 'ssm_k': _w((lambda *s: torch.randn(*s, dtype=torch.bfloat16) * 0.8)(D, S) * (1.0 / S ** 0.5)), 'ssm_D': _w((lambda *s: torch.randn(*s, dtype=torch.bfloat16) * 0.8)(D))}
    _A_in = _A_setup()

    def _B_setup():
        B, S, D, F = (1, 2048, 640, 1536)
        return {'x': _w((lambda *s: torch.randn(*s, dtype=torch.bfloat16) * 0.05)(B, S, D)), 'W_gate': _w((lambda *s: torch.randn(*s, dtype=torch.bfloat16) * 0.8)(D, F) * (2.0 / D) ** 0.5), 'W_up': _w((lambda *s: torch.randn(*s, dtype=torch.bfloat16) * 0.8)(D, F) * (2.0 / D) ** 0.5), 'W_down': _w((lambda *s: torch.randn(*s, dtype=torch.bfloat16) * 0.8)(F, D) * (1.0 / F) ** 0.5)}
    _B_in = _B_setup()
    return {'A_q': _A_in['q'], 'A_k': _A_in['k'], 'A_v': _A_in['v'], 'A_shift_k': _A_in['shift_k'], 'A_ssm_k': _A_in['ssm_k'], 'A_ssm_D': _A_in['ssm_D'], 'B_x': _B_in['x'], 'B_W_gate': _B_in['W_gate'], 'B_W_up': _B_in['W_up'], 'B_W_down': _B_in['W_down'], 'c': _w((lambda *s: torch.randn(*s, dtype=torch.bfloat16) * 0.2)(1, 640) * 8.0), 'w_mod': _w((lambda *s: torch.randn(*s, dtype=torch.bfloat16) * 0.2)(640, 6 * 640) * 640 ** (-0.5) * 8.0)}

def reference(A_q, A_k, A_v, A_shift_k, A_ssm_k, A_ssm_D, B_x, B_W_gate, B_W_up, B_W_down, c, w_mod):

    def _A_ref(q, k, v, shift_k, ssm_k, ssm_D):
        B, S, D = q.shape
        ks = shift_k.shape[-1]
        k_pad = _pad(k, ((0, 0), (ks - 1, 0), (0, 0)))
        k_shift = torch.zeros_like(k)
        for t in range(ks):
            k_shift = k_shift + k_pad[:, t:t + S, :] * shift_k[:, ks - 1 - t][None, None, :]
        kv = k_shift * v
        L = 2 * S
        kv_pad = _pad(kv, ((0, 0), (0, S), (0, 0)))
        kf_pad = _pad(ssm_k, ((0, 0), (0, S)))
        kv_f = (lambda x, axes=(-2, -1): torch.fft.rfft2(x.float(), dim=axes))(kv_pad[:, None, :, :], axes=(1, 2))
        kf_f = (lambda x, axes=(-2, -1): torch.fft.rfft2(x.float(), dim=axes))(kf_pad[:, None, :], axes=(1, 2))
        kf_f = (lambda x, *d: x.permute(*d))(kf_f, 1, 2, 0)
        y_f = kv_f * kf_f[None, :, :, :]
        y = (lambda x, s, axes=(-2, -1): torch.fft.irfft2(x, s=s, dim=axes).to(torch.bfloat16))(y_f, (1, L), axes=(1, 2))[:, 0, :S, :]
        y = y + kv * ssm_D[None, None, :]
        return q * y

    def _B_ref(x, W_gate, W_up, W_down):
        gate = torch.einsum('bsd,df->bsf', x, W_gate)
        up = torch.einsum('bsd,df->bsf', x, W_up)
        gate = gate * (lambda x, dt: x.to(dt))(gate > 0, gate.dtype)
        h = gate * up
        return torch.einsum('bsf,fd->bsd', h, W_down)
    x = A_q
    mod = (_silu(c) @ w_mod).reshape(c.shape[0], 6, 1, -1)
    sa, ca, ga, sb, cb, gb = (mod[:, 0].clone(), mod[:, 1].clone(), mod[:, 2].clone(), mod[:, 3].clone(), mod[:, 4].clone(), mod[:, 5].clone())
    h = _layernorm(x, axis=-1) * (1 + ca) + sa
    x = x + ga * _A_ref(h, A_k, A_v, A_shift_k, A_ssm_k, A_ssm_D)
    h = _layernorm(x, axis=-1) * (1 + cb) + sb
    x = x + gb * _B_ref(h, B_W_gate, B_W_up, B_W_down)
    return x
```

```cpp
#include <cuda_runtime.h>
#include <cuda_bf16.h>
#include <cuda.h>
#include <stdint.h>
#include <stddef.h>
#include <type_traits>

namespace {

constexpr int D_ = 640;

struct Scratch {
    uint4 kvT[D_ * 256], yT[D_ * 256];
    uint4 z[16 * 10 * 1024];
    uint4 hh[16 * 24 * 1024];
    uint4 st2[2048];
    uint2 mod[1920];
    uint2 ut[5 * 3072];
    uint32_t cnt[64 * 1024];
};
__device__ __align__(1024) Scratch g_s;
#define SC(f, off) padd(P.scr, (uint32_t)offsetof(Scratch, f) + (off))
constexpr int C_KV = 0  , C_Y = 10  , C_Z = 16  , C_HH = 32  ;

constexpr uint32_t WR = 163840, MISC = 229376, SMEM_BYTES = 232448;
constexpr uint32_t ESLOT = 0x31650;
constexpr uint32_t XP = 4112, XB = 65536 + 18432, ST_SH = XB + 2 * XP;
constexpr uint32_t ST_Q = 131072, ST_H = ST_Q, ST_Y = ST_Q + 21504, ST_C = ST_Y + 9216, ST_S = ST_C + 768, UST = ST_Q;
__host__ __device__ constexpr uint32_t st_kv(int r) { return r == 2 ? ST_Y : r == 1 || r == 4 ? 65536 + 9216 : 65536; }
constexpr uint32_t PP = 4352;
constexpr uint32_t BARS = MISC, TAB1 = MISC + 656, TAB2 = TAB1 + 32 * 48, CS_TAB = TAB1  , PRF = -256;
constexpr uint32_t GBT = 0, G2B = 8192, G2A = 131072;
enum { B_H = 0, B_KV = 5, B_Q = 10, B_X = 15  , B_MD = 17  , B_AF = 20, B_AL = 30, B_WF = 40, B_G2F = 44, B_GB = 50, B_RT = 51,
       B_WE = 52, B_G2E = 56,
       B_UD = 62, B_HD = 63  , B_S0 = 66, B_HS = 67  ,
       B_RD = 70, B_UF = 75, B_EB = 76  , B_TD = 78  , B_T1 = 80, NBARS = 81 };
#define NEB 4
__host__ __device__ constexpr uint32_t bar_count(int i) {
    return i < B_WE ? 1 : i < B_UD ? 16 : i < B_RD ? 8 : i < B_EB ? 4 : i == B_EB ? 4 * NEB : i == B_EB + 1 ? 20 - 4 * NEB : i < B_T1 ? 3 : 2;
}
#define GSTAMPIF(c, i) do {} while (0)
#define STAMPIF(c, i) do {} while (0)
#define STAMP(i) do {} while (0)
#define VALIF(c, i, v) do {} while (0)
#define STAMPI STAMPIF
#define STAMPR(i) do {} while (0)
#define TWAIT(i, stmt) stmt
#define Q2 2
#define G2R 5
#define YH 0
#define NPRE 1
#define WP0 2
#define SEQ0 0x531b9
#define SEQ1 0x42dca
#define NEH 1
#define N_UT 12
#define NST 4
#define TN(i, v) v
#define ORDER hhhhhkkxkqqqkqxqxwwww
#define STR2(x) #x
#define STR(x) STR2(x)
constexpr int NORD = sizeof(STR(ORDER)) - 1;
__host__ __device__ constexpr char ord_kind(int i) { return STR(ORDER)[i]; }
__host__ __device__ constexpr int ord_index(int i) { int n = ord_kind(i) == 'k'; for (int j = 0; j < i; j++) n += ord_kind(j) == ord_kind(i); return n; }
__host__ __device__ constexpr int ord_slot(int i) { int n = 0; for (int j = 0; j < i; j++) n += ord_kind(j) == 'k' ? 2 : ord_kind(j) != 'x'; return n; }
__host__ __device__ constexpr int ord_find(char c, int n) { for (int i = 0; i < NORD; i++) if (ord_kind(i) == c && ord_index(i) == n) return i; return -1; }
__host__ __device__ constexpr int ord_count(char c) { int n = 0; for (int i = 0; i < NORD; i++) n += ord_kind(i) == c; return n; }
__host__ __device__ constexpr uint32_t ord_mask(char c) { uint32_t m = 0; for (int i = 0; i < NORD; i++) m |= (uint32_t)(ord_kind(i) == c) << i; return m; }
__host__ __device__ constexpr uint32_t ord_tasks() { uint32_t v = 1; for (int i = NORD - 1; i >= 0; i--) if (ord_kind(i) == 'k' || ord_kind(i) == 'q') v = 2 * v + (ord_kind(i) == 'k'); return 2 * v + 1; }
constexpr int NWP = ord_count('w');
static_assert(NWP % 2 == 0 && ord_kind(0) == 'h' && ord_count('x') >= 2 && ord_count('k') == 4 && ord_count('q') == 5 && ord_count('h') == 5 && ord_find('k', 4) < ord_find('q', 4) &&
              ord_find('h', NEB - 1) < ord_find('q', 0) && ord_find('h', 4) < ord_find('q', NEB), "order");
#define TV0 600
#define D_1 TN(0, TV0)
#define TV1 400
#define G_U TN(1, TV1)
#define TV2 400
#define G_ST TN(2, TV2)
#define TV4 2000
#define D_SP TN(4, TV4)
#define TV5 9000
#define D_PW TN(5, TV5)
#define TV6 1000
#define G_PW TN(6, TV6)
#define TV7 700
#define D_PK TN(7, TV7)
#define TV8 600
#define D_PY TN(8, TV8)
#define TV9 300
#define D_PZ TN(9, TV9)
#define TV10 1000
#define D_PK2 TN(10, TV10)
#define TV11 1000
#define D_UT TN(11, TV11)

__device__ __forceinline__ uint32_t smem_u32(const void* p) { return (uint32_t)__cvta_generic_to_shared(p); }
__device__ __forceinline__ void mbar_init(uint32_t bar, uint32_t cnt) { asm volatile("mbarrier.init.shared::cta.b64 [%0], %1;" :: "r"(bar), "r"(cnt) : "memory"); }
__device__ __forceinline__ void mbar_expect(uint32_t bar, uint32_t bytes) { asm volatile("mbarrier.arrive.expect_tx.shared::cta.b64 _, [%0], %1;" :: "r"(bar), "r"(bytes) : "memory"); }
__device__ __forceinline__ void mbar_arrive_if(uint32_t bar, bool p) { asm volatile("{ .reg .pred p; setp.ne.b32 p, %1, 0; @p mbarrier.arrive.shared::cta.b64 _, [%0]; }" :: "r"(bar), "r"((int)p) : "memory"); }
__device__ __forceinline__ void mbar_arrive_remote_if(uint32_t bar, bool p) { asm volatile("{ .reg .pred p; setp.ne.b32 p, %1, 0; @p mbarrier.arrive.shared::cluster.b64 _, [%0]; }" :: "r"(bar), "r"((int)p) : "memory"); }
#define WAIT_LOOP(op) "{\n .reg .pred p, q; .reg .u32 c; mov.u32 c, 0;\n LAB_WAIT:\n " op " p, [%0], %1;\n @p bra LAB_DONE;\n add.u32 c, c, 1; setp.lt.u32 q, c, 16384;\n @q bra LAB_WAIT;\n LAB_DONE:\n }"
__device__ __forceinline__ void mbar_wait(uint32_t bar, uint32_t parity) { asm volatile(WAIT_LOOP("mbarrier.try_wait.parity.shared::cta.b64") :: "r"(bar), "r"(parity) : "memory"); }
__device__ __forceinline__ bool mbar_test(uint32_t bar, uint32_t parity) {
    uint32_t ok; asm volatile("{ .reg .pred p; mbarrier.test_wait.parity.shared::cta.b64 p, [%1], %2; selp.u32 %0, 1, 0, p; }" : "=r"(ok) : "r"(bar), "r"(parity) : "memory"); return ok;
}
__device__ __forceinline__ uint32_t clock32() { uint32_t t; asm volatile("mov.u32 %0, %%clock;" : "=r"(t) :: "memory"); return t; }
__device__ __forceinline__ void wait_clock(uint32_t t0, uint32_t d) {
    asm volatile("{\n .reg .pred p; .reg .u32 t;\n LAB_CLK:\n mov.u32 t, %%clock; sub.u32 t, t, %0; setp.lt.u32 p, t, %1;\n @p bra LAB_CLK;\n }" :: "r"(t0), "r"(d) : "memory");
}
__device__ __forceinline__ bool elect() { uint32_t p; asm volatile("{ .reg .pred p; elect.sync _|p, 0xffffffff; selp.u32 %0, 1, 0, p; }" : "=r"(p)); return p; }
__device__ __forceinline__ void pf_map(const CUtensorMap* m) { asm volatile("prefetch.tensormap [%0];" :: "l"(m) : "memory"); }
__device__ __forceinline__ void bar_sync(int id, int n) { asm volatile("bar.sync %0, %1;" :: "r"(id), "r"(n) : "memory"); }
__device__ __forceinline__ bool bar_or(int id, int n, bool c) {
    uint32_t r; asm volatile("{ .reg .pred p, q; setp.ne.b32 p, %3, 0; bar.red.or.pred q, %1, %2, p; selp.u32 %0, 1, 0, q; }" : "=r"(r) : "r"(id), "r"(n), "r"((int)c) : "memory"); return r;
}
__device__ __forceinline__ void wait_until(uint32_t t1) {
    asm volatile("{\n .reg .pred p; .reg .s32 t;\n LAB_CLK:\n mov.u32 t, %%clock; sub.s32 t, t, %0; setp.lt.s32 p, t, 0;\n @p bra LAB_CLK;\n }" :: "r"(t1) : "memory");
}
__device__ __forceinline__ void pause(uint32_t d) { wait_clock(clock32(), d); }
__device__ __forceinline__ void bar_arrive(int id, int n) { asm volatile("bar.arrive %0, %1;" :: "r"(id), "r"(n) : "memory"); }
__device__ __forceinline__ void fence_async_smem() { asm volatile("fence.proxy.async.shared::cta;" ::: "memory"); }
__device__ __forceinline__ void fence_async_glob() { asm volatile("fence.proxy.async.global;" ::: "memory"); }
__device__ __forceinline__ void fence_acq() { asm volatile("fence.acquire.gpu;" ::: "memory"); }
__device__ __forceinline__ void bulk_g2s(uint32_t dst, const void* src, uint32_t bytes, uint32_t bar) {
    asm volatile("cp.async.bulk.shared::cluster.global.mbarrier::complete_tx::bytes [%0], [%1], %2, [%3];" :: "r"(dst), "l"(src), "r"(bytes), "r"(bar) : "memory");
}
__device__ __forceinline__ void pf_l2(const void* src, uint32_t bytes) { asm volatile("cp.async.bulk.prefetch.L2.global [%0], %1;" :: "l"(src), "r"(bytes) : "memory"); }
__device__ __forceinline__ void tma2d(uint32_t dst, const CUtensorMap* m, int c0, int c1, uint32_t bar) {
    asm volatile("cp.async.bulk.tensor.2d.shared::cluster.global.mbarrier::complete_tx::bytes [%0], [%1, {%3, %4}], [%2];" :: "r"(dst), "l"(m), "r"(bar), "r"(c0), "r"(c1) : "memory");
}
__device__ __forceinline__ void tma3d(uint32_t dst, const CUtensorMap* m, int c1, int c2, uint32_t bar) {
    asm volatile("cp.async.bulk.tensor.3d.shared::cluster.global.mbarrier::complete_tx::bytes [%0], [%1, {%5, %3, %4}], [%2];" :: "r"(dst), "l"(m), "r"(bar), "r"(c1), "r"(c2), "r"(0) : "memory");
}
__device__ __forceinline__ void tma4d(uint32_t dst, const CUtensorMap* m, int c0, int c2, uint32_t bar) {
    asm volatile("cp.async.bulk.tensor.4d.shared::cluster.global.mbarrier::complete_tx::bytes [%0], [%1, {%3, %5, %4, %5}], [%2];" :: "r"(dst), "l"(m), "r"(bar), "r"(c0), "r"(c2), "r"(0) : "memory");
}
__device__ __forceinline__ void tma5d_mc(uint32_t dst, const CUtensorMap* m, int c2, int c4, uint32_t bar) {
    asm volatile("cp.async.bulk.tensor.5d.shared::cluster.global.mbarrier::complete_tx::bytes.multicast::cluster [%0], [%1, {%5, %5, %3, %5, %4}], [%2], %6;"
                 :: "r"(dst), "l"(m), "r"(bar), "r"(c2), "r"(c4), "r"(0), "h"((uint16_t)3) : "memory");
}
__device__ __forceinline__ void tma3d_mc(uint32_t dst, const CUtensorMap* m, int c1, int c2, uint32_t bar) {
    asm volatile("cp.async.bulk.tensor.3d.shared::cluster.global.mbarrier::complete_tx::bytes.multicast::cluster [%0], [%1, {%5, %3, %4}], [%2], %6;"
                 :: "r"(dst), "l"(m), "r"(bar), "r"(c1), "r"(c2), "r"(0), "h"((uint16_t)3) : "memory");
}
__device__ __forceinline__ void tma2d_mc(uint32_t dst, const CUtensorMap* m, int c0, int c1, uint32_t bar) {
    asm volatile("cp.async.bulk.tensor.2d.shared::cluster.global.mbarrier::complete_tx::bytes.multicast::cluster [%0], [%1, {%3, %4}], [%2], %5;"
                 :: "r"(dst), "l"(m), "r"(bar), "r"(c0), "r"(c1), "h"((uint16_t)3) : "memory");
}
__device__ __forceinline__ void tma2d_red(const CUtensorMap* m, uint32_t src, int c0, int c1) {
    asm volatile("cp.reduce.async.bulk.tensor.2d.global.shared::cta.add.bulk_group [%0, {%2, %3}], [%1];" :: "l"(m), "r"(src), "r"(c0), "r"(c1) : "memory");
}
__device__ __forceinline__ void red_if(const void* c, uint32_t inc, bool p) { asm volatile("{ .reg .pred p; setp.ne.b32 p, %2, 0; @p red.relaxed.gpu.global.add.u32 [%0], %1; }" :: "l"(c), "r"(inc), "r"((int)p) : "memory"); }
__device__ __forceinline__ uint32_t ldg_rlx32(const void* p) { uint32_t v; asm volatile("ld.relaxed.gpu.global.u32 %0, [%1];" : "=r"(v) : "l"(p) : "memory"); return v; }
__device__ __forceinline__ uint32_t ldg_late(const char* p, int lane) { return ldg_rlx32(p + (lane & 1) * 4); }
__device__ __forceinline__ bool reached(uint32_t v, uint32_t target) { return __ballot_sync(~0u, (int)(v - target) >= 0) & 1; }
__device__ __forceinline__ uint2 ldg_rlx64(const void* p) { uint2 v; asm volatile("{ .reg .b64 x; ld.relaxed.gpu.global.b64 x, [%2]; mov.b64 {%0, %1}, x; }" : "=r"(v.x), "=r"(v.y) : "l"(p) : "memory"); return v; }
__device__ __forceinline__ void ldg_rlx128_if(uint4& v, const void* p, bool c) {
    asm volatile("{ .reg .b128 t; .reg .b64 x, y; .reg .pred p; setp.ne.b32 p, %5, 0; mov.b64 x, {%0, %1}; mov.b64 y, {%2, %3}; mov.b128 t, {x, y};\n"
                 " @p ld.relaxed.gpu.global.b128 t, [%4]; mov.b128 {x, y}, t; mov.b64 {%0, %1}, x; mov.b64 {%2, %3}, y; }"
                 : "+r"(v.x), "+r"(v.y), "+r"(v.z), "+r"(v.w) : "l"(p), "r"((int)c) : "memory");
}
__device__ __forceinline__ uint4 ldg_rlx2x64(const void* p) { uint4 v; asm volatile("{ .reg .b64 x, y; ld.relaxed.gpu.global.v2.b64 {x, y}, [%4]; mov.b64 {%0, %1}, x; mov.b64 {%2, %3}, y; }" : "=r"(v.x), "=r"(v.y), "=r"(v.z), "=r"(v.w) : "l"(p) : "memory"); return v; }
__device__ __forceinline__ void stg_rlx128(void* p, uint32_t x, uint32_t y, uint32_t z, uint32_t w) {
    asm volatile("{ .reg .b128 t; .reg .b64 a, b; mov.b64 a, {%1, %2}; mov.b64 b, {%3, %4}; mov.b128 t, {a, b}; st.relaxed.gpu.global.b128 [%0], t; }" :: "l"(p), "r"(x), "r"(y), "r"(z), "r"(w) : "memory");
}
__device__ __forceinline__ void stg_rlx128_if(void* p, const uint32_t* v, bool c) {
    asm volatile("{ .reg .pred p; .reg .b128 t; .reg .b64 a, b; setp.ne.b32 p, %5, 0; mov.b64 a, {%1, %2}; mov.b64 b, {%3, %4}; mov.b128 t, {a, b}; @p st.relaxed.gpu.global.b128 [%0], t; }" :: "l"(p), "r"(v[0]), "r"(v[1]), "r"(v[2]), "r"(v[3]), "r"((int)c) : "memory");
}
__device__ __forceinline__ void stg128(void* p, uint32_t x, uint32_t y, uint32_t z, uint32_t w) { asm volatile("st.global.v4.b32 [%0], {%1,%2,%3,%4};" :: "l"(p), "r"(x), "r"(y), "r"(z), "r"(w) : "memory"); }
__device__ __forceinline__ void stg_tag(void* p, const uint32_t* o, const uint32_t* tm, uint32_t par) {
    asm volatile("st.relaxed.gpu.global.v4.b32 [%0], {%1,%2,%3,%4};" :: "l"(p), "r"((o[0] & ~tm[0]) | (par & tm[0])), "r"((o[1] & ~tm[1]) | (par & tm[1])),
                 "r"((o[2] & ~tm[2]) | (par & tm[2])), "r"((o[3] & ~tm[3]) | (par & tm[3])) : "memory");
}
__device__ __forceinline__ void poll_cnt(const void* c, uint32_t target) {
    asm volatile("{\n .reg .pred p, q; .reg .u32 c, v; mov.u32 c, 0;\n LAB_POLL:\n ld.relaxed.gpu.global.u32 v, [%0];\n sub.u32 v, v, %1; setp.ge.s32 p, v, 0;\n @p bra LAB_PDONE;\n"
                 " add.u32 c, c, 1; setp.lt.u32 q, c, 20000;\n @q bra LAB_POLL;\n LAB_PDONE:\n }" :: "l"(c), "r"(target) : "memory");
}
template<int N, typename F> __device__ __forceinline__ void ll_wait(uint2* v, uint32_t tag, F&& addr) {
    #pragma unroll 1
    for (int it = 0; it < 20000; it++) {
        uint32_t bad = 0;
        #pragma unroll
        for (int i = 0; i < N; i++) bad |= v[i].y ^ tag;
        if (!__any_sync(~0u, bad != 0)) break;
        asm volatile("nanosleep.u32 100;");
        #pragma unroll
        for (int i = 0; i < N; i++) v[i] = ldg_rlx64(addr(i));
    }
}
__device__ __forceinline__ uint4 lds128(uint32_t a) { uint4 v; asm volatile("ld.shared.v4.b32 {%0,%1,%2,%3}, [%4];" : "=r"(v.x), "=r"(v.y), "=r"(v.z), "=r"(v.w) : "r"(a) : "memory"); return v; }
__device__ __forceinline__ uint2 lds64(uint32_t a) { uint2 v; asm volatile("ld.shared.v2.b32 {%0,%1}, [%2];" : "=r"(v.x), "=r"(v.y) : "r"(a) : "memory"); return v; }
__device__ __forceinline__ void sts128(uint32_t a, uint32_t x, uint32_t y, uint32_t z, uint32_t w) { asm volatile("st.shared.v4.b32 [%0], {%1,%2,%3,%4};" :: "r"(a), "r"(x), "r"(y), "r"(z), "r"(w) : "memory"); }
__device__ __forceinline__ void sts32(uint32_t a, uint32_t x) { asm volatile("st.shared.b32 [%0], %1;" :: "r"(a), "r"(x) : "memory"); }
__device__ __forceinline__ void ldsm4t(uint32_t* r, uint32_t a) { asm volatile("ldmatrix.sync.aligned.m8n8.x4.trans.shared.b16 {%0,%1,%2,%3}, [%4];" : "=r"(r[0]), "=r"(r[1]), "=r"(r[2]), "=r"(r[3]) : "r"(a) : "memory"); }
__device__ __forceinline__ void ldsm2t(uint32_t& r0, uint32_t& r1, uint32_t a) { asm volatile("ldmatrix.sync.aligned.m8n8.x2.trans.shared.b16 {%0,%1}, [%2];" : "=r"(r0), "=r"(r1) : "r"(a) : "memory"); }
__device__ __forceinline__ void ldsm4t_if(uint32_t* r, uint32_t a, bool c) { asm volatile("{ .reg .pred p; setp.ne.b32 p, %5, 0; @p ldmatrix.sync.aligned.m8n8.x4.trans.shared.b16 {%0,%1,%2,%3}, [%4]; }" : "+r"(r[0]), "+r"(r[1]), "+r"(r[2]), "+r"(r[3]) : "r"(a), "r"((int)c) : "memory"); }
__device__ __forceinline__ void ldsm2t_if(uint32_t* r, uint32_t a, bool c) { asm volatile("{ .reg .pred p; setp.ne.b32 p, %3, 0; @p ldmatrix.sync.aligned.m8n8.x2.trans.shared.b16 {%0,%1}, [%2]; }" : "+r"(r[0]), "+r"(r[1]) : "r"(a), "r"((int)c) : "memory"); }
__device__ __forceinline__ void lds128_if(uint4& v, uint32_t a, bool c) { asm volatile("{ .reg .pred p; setp.ne.b32 p, %5, 0; @p ld.shared.v4.b32 {%0,%1,%2,%3}, [%4]; }" : "+r"(v.x), "+r"(v.y), "+r"(v.z), "+r"(v.w) : "r"(a), "r"((int)c) : "memory"); }
__device__ __forceinline__ void cp16(uint32_t d, const void* s) { asm volatile("cp.async.cg.shared.global [%0], [%1], 16;" :: "r"(d), "l"(s) : "memory"); }
__device__ __forceinline__ char* padd(const void* p, uint32_t off) { char* r; asm("{ .reg .u64 t; cvt.u64.u32 t, %2; add.u64 %0, %1, t; }" : "=l"(r) : "l"(p), "r"(off)); return r; }
__device__ __forceinline__ uint32_t prmt(uint32_t a, uint32_t b, uint32_t s) { uint32_t r; asm("prmt.b32 %0, %1, %2, %3;" : "=r"(r) : "r"(a), "r"(b), "r"(s)); return r; }
__device__ __forceinline__ uint32_t pack2(float lo, float hi) { uint32_t r; asm("cvt.rn.bf16x2.f32 %0, %1, %2;" : "=r"(r) : "f"(hi), "f"(lo)); return r; }
__device__ __forceinline__ uint32_t pack2relu(float lo, float hi) { uint32_t r; asm("cvt.rn.relu.bf16x2.f32 %0, %1, %2;" : "=r"(r) : "f"(hi), "f"(lo)); return r; }
__device__ __forceinline__ float bflo(uint32_t w) { return __uint_as_float(w << 16); }
__device__ __forceinline__ float bfhi(uint32_t w) { return __uint_as_float(w & 0xffff0000u); }
__device__ __forceinline__ float bfround(float x) { return bflo(pack2(x, x)); }
__device__ __forceinline__ uint32_t hmul2(uint32_t a, uint32_t b) { uint32_t r; asm("mul.rn.bf16x2 %0, %1, %2;" : "=r"(r) : "r"(a), "r"(b)); return r; }
__device__ __forceinline__ uint32_t hadd2(uint32_t a, uint32_t b) { uint32_t r; asm("add.rn.bf16x2 %0, %1, %2;" : "=r"(r) : "r"(a), "r"(b)); return r; }
__device__ __forceinline__ uint32_t hfma2(uint32_t a, uint32_t b, uint32_t c) { uint32_t r; asm("fma.rn.bf16x2 %0, %1, %2, %3;" : "=r"(r) : "r"(a), "r"(b), "r"(c)); return r; }
__device__ __forceinline__ void sched_bar() { asm volatile("pmevent 1;" ::: "memory"); }
__device__ __forceinline__ void wg_fence() { asm volatile("wgmma.fence.sync.aligned;" ::: "memory"); }
__device__ __forceinline__ void wg_commit() { asm volatile("wgmma.commit_group.sync.aligned;" ::: "memory"); }
template<int N> __device__ __forceinline__ void wg_wait() { asm volatile("wgmma.wait_group.sync.aligned %0;" :: "n"(N) : "memory"); }
template<int N> __device__ __forceinline__ void pin(float* d) {
    #pragma unroll
    for (int i = 0; i < N; i++) asm volatile("" : "+f"(d[i]) :: "memory");
}
__device__ __forceinline__ uint32_t dlo(uint32_t addr, uint32_t lbo) { return ((addr & 0x3FFFF) >> 4) | ((lbo >> 4) << 16); }
__host__ __device__ constexpr uint32_t dhi(uint32_t sbo, uint32_t sw) { return (sbo >> 4) | (sw << 30); }

template<int N> struct WG;
template<> struct WG<8> { template<int TA, int TB> static __device__ __forceinline__ void ss(float* d, uint32_t alo, uint32_t ahi, uint32_t blo, uint32_t bhi, int sd) {
  asm volatile("{ .reg .pred p; .reg .b64 da, db; mov.b64 da, {%4,%5}; mov.b64 db, {%6,%7}; setp.ne.b32 p, %8, 0;\n"
    "wgmma.mma_async.sync.aligned.m64n8k16.f32.bf16.bf16 {%0,%1,%2,%3}, da, db, p, 1, 1, %9, %10; }"
    : "+f"(d[0]),"+f"(d[1]),"+f"(d[2]),"+f"(d[3])
    : "r"(alo), "r"(ahi), "r"(blo), "r"(bhi), "r"(sd), "n"(TA), "n"(TB)); }
};
template<> struct WG<16> { template<int TA, int TB> static __device__ __forceinline__ void ss(float* d, uint32_t alo, uint32_t ahi, uint32_t blo, uint32_t bhi, int sd) {
  asm volatile("{ .reg .pred p; .reg .b64 da, db; mov.b64 da, {%8,%9}; mov.b64 db, {%10,%11}; setp.ne.b32 p, %12, 0;\n"
    "wgmma.mma_async.sync.aligned.m64n16k16.f32.bf16.bf16 {%0,%1,%2,%3,%4,%5,%6,%7}, da, db, p, 1, 1, %13, %14; }"
    : "+f"(d[0]),"+f"(d[1]),"+f"(d[2]),"+f"(d[3]),"+f"(d[4]),"+f"(d[5]),"+f"(d[6]),"+f"(d[7])
    : "r"(alo), "r"(ahi), "r"(blo), "r"(bhi), "r"(sd), "n"(TA), "n"(TB)); }
};
template<> struct WG<32> { template<int TA, int TB> static __device__ __forceinline__ void ss(float* d, uint32_t alo, uint32_t ahi, uint32_t blo, uint32_t bhi, int sd) {
  asm volatile("{ .reg .pred p; .reg .b64 da, db; mov.b64 da, {%16,%17}; mov.b64 db, {%18,%19}; setp.ne.b32 p, %20, 0;\n"
    "wgmma.mma_async.sync.aligned.m64n32k16.f32.bf16.bf16 {%0,%1,%2,%3,%4,%5,%6,%7,%8,%9,%10,%11,%12,%13,%14,%15}, da, db, p, 1, 1, %21, %22; }"
    : "+f"(d[0]),"+f"(d[1]),"+f"(d[2]),"+f"(d[3]),"+f"(d[4]),"+f"(d[5]),"+f"(d[6]),"+f"(d[7]),"+f"(d[8]),"+f"(d[9]),"+f"(d[10]),"+f"(d[11]),"+f"(d[12]),"+f"(d[13]),"+f"(d[14]),"+f"(d[15])
    : "r"(alo), "r"(ahi), "r"(blo), "r"(bhi), "r"(sd), "n"(TA), "n"(TB)); }
};
template<> struct WG<48> { template<int TA, int TB> static __device__ __forceinline__ void ss(float* d, uint32_t alo, uint32_t ahi, uint32_t blo, uint32_t bhi, int sd) {
  asm volatile("{ .reg .pred p; .reg .b64 da, db; mov.b64 da, {%24,%25}; mov.b64 db, {%26,%27}; setp.ne.b32 p, %28, 0;\n"
    "wgmma.mma_async.sync.aligned.m64n48k16.f32.bf16.bf16 {%0,%1,%2,%3,%4,%5,%6,%7,%8,%9,%10,%11,%12,%13,%14,%15,%16,%17,%18,%19,%20,%21,%22,%23}, da, db, p, 1, 1, %29, %30; }"
    : "+f"(d[0]),"+f"(d[1]),"+f"(d[2]),"+f"(d[3]),"+f"(d[4]),"+f"(d[5]),"+f"(d[6]),"+f"(d[7]),"+f"(d[8]),"+f"(d[9]),"+f"(d[10]),"+f"(d[11]),"+f"(d[12]),"+f"(d[13]),"+f"(d[14]),"+f"(d[15]),"+f"(d[16]),"+f"(d[17]),"+f"(d[18]),"+f"(d[19]),"+f"(d[20]),"+f"(d[21]),"+f"(d[22]),"+f"(d[23])
    : "r"(alo), "r"(ahi), "r"(blo), "r"(bhi), "r"(sd), "n"(TA), "n"(TB)); }
};
template<> struct WG<64> { template<int TA, int TB> static __device__ __forceinline__ void ss(float* d, uint32_t alo, uint32_t ahi, uint32_t blo, uint32_t bhi, int sd) {
  asm volatile("{ .reg .pred p; .reg .b64 da, db; mov.b64 da, {%32,%33}; mov.b64 db, {%34,%35}; setp.ne.b32 p, %36, 0;\n"
    "wgmma.mma_async.sync.aligned.m64n64k16.f32.bf16.bf16 {%0,%1,%2,%3,%4,%5,%6,%7,%8,%9,%10,%11,%12,%13,%14,%15,%16,%17,%18,%19,%20,%21,%22,%23,%24,%25,%26,%27,%28,%29,%30,%31}, da, db, p, 1, 1, %37, %38; }"
    : "+f"(d[0]),"+f"(d[1]),"+f"(d[2]),"+f"(d[3]),"+f"(d[4]),"+f"(d[5]),"+f"(d[6]),"+f"(d[7]),"+f"(d[8]),"+f"(d[9]),"+f"(d[10]),"+f"(d[11]),"+f"(d[12]),"+f"(d[13]),"+f"(d[14]),"+f"(d[15]),"+f"(d[16]),"+f"(d[17]),"+f"(d[18]),"+f"(d[19]),"+f"(d[20]),"+f"(d[21]),"+f"(d[22]),"+f"(d[23]),"+f"(d[24]),"+f"(d[25]),"+f"(d[26]),"+f"(d[27]),"+f"(d[28]),"+f"(d[29]),"+f"(d[30]),"+f"(d[31])
    : "r"(alo), "r"(ahi), "r"(blo), "r"(bhi), "r"(sd), "n"(TA), "n"(TB)); }
};
template<> struct WG<80> { template<int TA, int TB> static __device__ __forceinline__ void ss(float* d, uint32_t alo, uint32_t ahi, uint32_t blo, uint32_t bhi, int sd) {
  asm volatile("{ .reg .pred p; .reg .b64 da, db; mov.b64 da, {%40,%41}; mov.b64 db, {%42,%43}; setp.ne.b32 p, %44, 0;\n"
    "wgmma.mma_async.sync.aligned.m64n80k16.f32.bf16.bf16 {%0,%1,%2,%3,%4,%5,%6,%7,%8,%9,%10,%11,%12,%13,%14,%15,%16,%17,%18,%19,%20,%21,%22,%23,%24,%25,%26,%27,%28,%29,%30,%31,%32,%33,%34,%35,%36,%37,%38,%39}, da, db, p, 1, 1, %45, %46; }"
    : "+f"(d[0]),"+f"(d[1]),"+f"(d[2]),"+f"(d[3]),"+f"(d[4]),"+f"(d[5]),"+f"(d[6]),"+f"(d[7]),"+f"(d[8]),"+f"(d[9]),"+f"(d[10]),"+f"(d[11]),"+f"(d[12]),"+f"(d[13]),"+f"(d[14]),"+f"(d[15]),"+f"(d[16]),"+f"(d[17]),"+f"(d[18]),"+f"(d[19]),"+f"(d[20]),"+f"(d[21]),"+f"(d[22]),"+f"(d[23]),"+f"(d[24]),"+f"(d[25]),"+f"(d[26]),"+f"(d[27]),"+f"(d[28]),"+f"(d[29]),"+f"(d[30]),"+f"(d[31]),"+f"(d[32]),"+f"(d[33]),"+f"(d[34]),"+f"(d[35]),"+f"(d[36]),"+f"(d[37]),"+f"(d[38]),"+f"(d[39])
    : "r"(alo), "r"(ahi), "r"(blo), "r"(bhi), "r"(sd), "n"(TA), "n"(TB)); }
};
template<> struct WG<96> { template<int TA, int TB> static __device__ __forceinline__ void ss(float* d, uint32_t alo, uint32_t ahi, uint32_t blo, uint32_t bhi, int sd) {
  asm volatile("{ .reg .pred p; .reg .b64 da, db; mov.b64 da, {%48,%49}; mov.b64 db, {%50,%51}; setp.ne.b32 p, %52, 0;\n"
    "wgmma.mma_async.sync.aligned.m64n96k16.f32.bf16.bf16 {%0,%1,%2,%3,%4,%5,%6,%7,%8,%9,%10,%11,%12,%13,%14,%15,%16,%17,%18,%19,%20,%21,%22,%23,%24,%25,%26,%27,%28,%29,%30,%31,%32,%33,%34,%35,%36,%37,%38,%39,%40,%41,%42,%43,%44,%45,%46,%47}, da, db, p, 1, 1, %53, %54; }"
    : "+f"(d[0]),"+f"(d[1]),"+f"(d[2]),"+f"(d[3]),"+f"(d[4]),"+f"(d[5]),"+f"(d[6]),"+f"(d[7]),"+f"(d[8]),"+f"(d[9]),"+f"(d[10]),"+f"(d[11]),"+f"(d[12]),"+f"(d[13]),"+f"(d[14]),"+f"(d[15]),"+f"(d[16]),"+f"(d[17]),"+f"(d[18]),"+f"(d[19]),"+f"(d[20]),"+f"(d[21]),"+f"(d[22]),"+f"(d[23]),"+f"(d[24]),"+f"(d[25]),"+f"(d[26]),"+f"(d[27]),"+f"(d[28]),"+f"(d[29]),"+f"(d[30]),"+f"(d[31]),"+f"(d[32]),"+f"(d[33]),"+f"(d[34]),"+f"(d[35]),"+f"(d[36]),"+f"(d[37]),"+f"(d[38]),"+f"(d[39]),"+f"(d[40]),"+f"(d[41]),"+f"(d[42]),"+f"(d[43]),"+f"(d[44]),"+f"(d[45]),"+f"(d[46]),"+f"(d[47])
    : "r"(alo), "r"(ahi), "r"(blo), "r"(bhi), "r"(sd), "n"(TA), "n"(TB)); }
};
template<> struct WG<112> { template<int TA, int TB> static __device__ __forceinline__ void ss(float* d, uint32_t alo, uint32_t ahi, uint32_t blo, uint32_t bhi, int sd) {
  asm volatile("{ .reg .pred p; .reg .b64 da, db; mov.b64 da, {%56,%57}; mov.b64 db, {%58,%59}; setp.ne.b32 p, %60, 0;\n"
    "wgmma.mma_async.sync.aligned.m64n112k16.f32.bf16.bf16 {%0,%1,%2,%3,%4,%5,%6,%7,%8,%9,%10,%11,%12,%13,%14,%15,%16,%17,%18,%19,%20,%21,%22,%23,%24,%25,%26,%27,%28,%29,%30,%31,%32,%33,%34,%35,%36,%37,%38,%39,%40,%41,%42,%43,%44,%45,%46,%47,%48,%49,%50,%51,%52,%53,%54,%55}, da, db, p, 1, 1, %61, %62; }"
    : "+f"(d[0]),"+f"(d[1]),"+f"(d[2]),"+f"(d[3]),"+f"(d[4]),"+f"(d[5]),"+f"(d[6]),"+f"(d[7]),"+f"(d[8]),"+f"(d[9]),"+f"(d[10]),"+f"(d[11]),"+f"(d[12]),"+f"(d[13]),"+f"(d[14]),"+f"(d[15]),"+f"(d[16]),"+f"(d[17]),"+f"(d[18]),"+f"(d[19]),"+f"(d[20]),"+f"(d[21]),"+f"(d[22]),"+f"(d[23]),"+f"(d[24]),"+f"(d[25]),"+f"(d[26]),"+f"(d[27]),"+f"(d[28]),"+f"(d[29]),"+f"(d[30]),"+f"(d[31]),"+f"(d[32]),"+f"(d[33]),"+f"(d[34]),"+f"(d[35]),"+f"(d[36]),"+f"(d[37]),"+f"(d[38]),"+f"(d[39]),"+f"(d[40]),"+f"(d[41]),"+f"(d[42]),"+f"(d[43]),"+f"(d[44]),"+f"(d[45]),"+f"(d[46]),"+f"(d[47]),"+f"(d[48]),"+f"(d[49]),"+f"(d[50]),"+f"(d[51]),"+f"(d[52]),"+f"(d[53]),"+f"(d[54]),"+f"(d[55])
    : "r"(alo), "r"(ahi), "r"(blo), "r"(bhi), "r"(sd), "n"(TA), "n"(TB)); }
};
template<> struct WG<128> { template<int TA, int TB> static __device__ __forceinline__ void ss(float* d, uint32_t alo, uint32_t ahi, uint32_t blo, uint32_t bhi, int sd) {
  asm volatile("{ .reg .pred p; .reg .b64 da, db; mov.b64 da, {%64,%65}; mov.b64 db, {%66,%67}; setp.ne.b32 p, %68, 0;\n"
    "wgmma.mma_async.sync.aligned.m64n128k16.f32.bf16.bf16 {%0,%1,%2,%3,%4,%5,%6,%7,%8,%9,%10,%11,%12,%13,%14,%15,%16,%17,%18,%19,%20,%21,%22,%23,%24,%25,%26,%27,%28,%29,%30,%31,%32,%33,%34,%35,%36,%37,%38,%39,%40,%41,%42,%43,%44,%45,%46,%47,%48,%49,%50,%51,%52,%53,%54,%55,%56,%57,%58,%59,%60,%61,%62,%63}, da, db, p, 1, 1, %69, %70; }"
    : "+f"(d[0]),"+f"(d[1]),"+f"(d[2]),"+f"(d[3]),"+f"(d[4]),"+f"(d[5]),"+f"(d[6]),"+f"(d[7]),"+f"(d[8]),"+f"(d[9]),"+f"(d[10]),"+f"(d[11]),"+f"(d[12]),"+f"(d[13]),"+f"(d[14]),"+f"(d[15]),"+f"(d[16]),"+f"(d[17]),"+f"(d[18]),"+f"(d[19]),"+f"(d[20]),"+f"(d[21]),"+f"(d[22]),"+f"(d[23]),"+f"(d[24]),"+f"(d[25]),"+f"(d[26]),"+f"(d[27]),"+f"(d[28]),"+f"(d[29]),"+f"(d[30]),"+f"(d[31]),"+f"(d[32]),"+f"(d[33]),"+f"(d[34]),"+f"(d[35]),"+f"(d[36]),"+f"(d[37]),"+f"(d[38]),"+f"(d[39]),"+f"(d[40]),"+f"(d[41]),"+f"(d[42]),"+f"(d[43]),"+f"(d[44]),"+f"(d[45]),"+f"(d[46]),"+f"(d[47]),"+f"(d[48]),"+f"(d[49]),"+f"(d[50]),"+f"(d[51]),"+f"(d[52]),"+f"(d[53]),"+f"(d[54]),"+f"(d[55]),"+f"(d[56]),"+f"(d[57]),"+f"(d[58]),"+f"(d[59]),"+f"(d[60]),"+f"(d[61]),"+f"(d[62]),"+f"(d[63])
    : "r"(alo), "r"(ahi), "r"(blo), "r"(bhi), "r"(sd), "n"(TA), "n"(TB)); }
  template<int TB> static __device__ __forceinline__ void rs(float* d, uint32_t a0, uint32_t a1, uint32_t a2, uint32_t a3, uint32_t blo, uint32_t bhi, int sd) {
  asm volatile("{ .reg .pred p; .reg .b64 db; mov.b64 db, {%68,%69}; setp.ne.b32 p, %71, 0;\n"
    "wgmma.mma_async.sync.aligned.m64n128k16.f32.bf16.bf16 {%0,%1,%2,%3,%4,%5,%6,%7,%8,%9,%10,%11,%12,%13,%14,%15,%16,%17,%18,%19,%20,%21,%22,%23,%24,%25,%26,%27,%28,%29,%30,%31,%32,%33,%34,%35,%36,%37,%38,%39,%40,%41,%42,%43,%44,%45,%46,%47,%48,%49,%50,%51,%52,%53,%54,%55,%56,%57,%58,%59,%60,%61,%62,%63}, {%64,%65,%66,%67}, db, p, 1, 1, %70; }"
    : "+f"(d[0]),"+f"(d[1]),"+f"(d[2]),"+f"(d[3]),"+f"(d[4]),"+f"(d[5]),"+f"(d[6]),"+f"(d[7]),"+f"(d[8]),"+f"(d[9]),"+f"(d[10]),"+f"(d[11]),"+f"(d[12]),"+f"(d[13]),"+f"(d[14]),"+f"(d[15]),"+f"(d[16]),"+f"(d[17]),"+f"(d[18]),"+f"(d[19]),"+f"(d[20]),"+f"(d[21]),"+f"(d[22]),"+f"(d[23]),"+f"(d[24]),"+f"(d[25]),"+f"(d[26]),"+f"(d[27]),"+f"(d[28]),"+f"(d[29]),"+f"(d[30]),"+f"(d[31]),"+f"(d[32]),"+f"(d[33]),"+f"(d[34]),"+f"(d[35]),"+f"(d[36]),"+f"(d[37]),"+f"(d[38]),"+f"(d[39]),"+f"(d[40]),"+f"(d[41]),"+f"(d[42]),"+f"(d[43]),"+f"(d[44]),"+f"(d[45]),"+f"(d[46]),"+f"(d[47]),"+f"(d[48]),"+f"(d[49]),"+f"(d[50]),"+f"(d[51]),"+f"(d[52]),"+f"(d[53]),"+f"(d[54]),"+f"(d[55]),"+f"(d[56]),"+f"(d[57]),"+f"(d[58]),"+f"(d[59]),"+f"(d[60]),"+f"(d[61]),"+f"(d[62]),"+f"(d[63])
    : "r"(a0), "r"(a1), "r"(a2), "r"(a3), "r"(blo), "r"(bhi), "n"(TB), "r"(sd)); }
};
template<> struct WG<144> { template<int TA, int TB> static __device__ __forceinline__ void ss(float* d, uint32_t alo, uint32_t ahi, uint32_t blo, uint32_t bhi, int sd) {
  asm volatile("{ .reg .pred p; .reg .b64 da, db; mov.b64 da, {%72,%73}; mov.b64 db, {%74,%75}; setp.ne.b32 p, %76, 0;\n"
    "wgmma.mma_async.sync.aligned.m64n144k16.f32.bf16.bf16 {%0,%1,%2,%3,%4,%5,%6,%7,%8,%9,%10,%11,%12,%13,%14,%15,%16,%17,%18,%19,%20,%21,%22,%23,%24,%25,%26,%27,%28,%29,%30,%31,%32,%33,%34,%35,%36,%37,%38,%39,%40,%41,%42,%43,%44,%45,%46,%47,%48,%49,%50,%51,%52,%53,%54,%55,%56,%57,%58,%59,%60,%61,%62,%63,%64,%65,%66,%67,%68,%69,%70,%71}, da, db, p, 1, 1, %77, %78; }"
    : "+f"(d[0]),"+f"(d[1]),"+f"(d[2]),"+f"(d[3]),"+f"(d[4]),"+f"(d[5]),"+f"(d[6]),"+f"(d[7]),"+f"(d[8]),"+f"(d[9]),"+f"(d[10]),"+f"(d[11]),"+f"(d[12]),"+f"(d[13]),"+f"(d[14]),"+f"(d[15]),"+f"(d[16]),"+f"(d[17]),"+f"(d[18]),"+f"(d[19]),"+f"(d[20]),"+f"(d[21]),"+f"(d[22]),"+f"(d[23]),"+f"(d[24]),"+f"(d[25]),"+f"(d[26]),"+f"(d[27]),"+f"(d[28]),"+f"(d[29]),"+f"(d[30]),"+f"(d[31]),"+f"(d[32]),"+f"(d[33]),"+f"(d[34]),"+f"(d[35]),"+f"(d[36]),"+f"(d[37]),"+f"(d[38]),"+f"(d[39]),"+f"(d[40]),"+f"(d[41]),"+f"(d[42]),"+f"(d[43]),"+f"(d[44]),"+f"(d[45]),"+f"(d[46]),"+f"(d[47]),"+f"(d[48]),"+f"(d[49]),"+f"(d[50]),"+f"(d[51]),"+f"(d[52]),"+f"(d[53]),"+f"(d[54]),"+f"(d[55]),"+f"(d[56]),"+f"(d[57]),"+f"(d[58]),"+f"(d[59]),"+f"(d[60]),"+f"(d[61]),"+f"(d[62]),"+f"(d[63]),"+f"(d[64]),"+f"(d[65]),"+f"(d[66]),"+f"(d[67]),"+f"(d[68]),"+f"(d[69]),"+f"(d[70]),"+f"(d[71])
    : "r"(alo), "r"(ahi), "r"(blo), "r"(bhi), "r"(sd), "n"(TA), "n"(TB)); }
};
template<> struct WG<160> { template<int TA, int TB> static __device__ __forceinline__ void ss(float* d, uint32_t alo, uint32_t ahi, uint32_t blo, uint32_t bhi, int sd) {
  asm volatile("{ .reg .pred p; .reg .b64 da, db; mov.b64 da, {%80,%81}; mov.b64 db, {%82,%83}; setp.ne.b32 p, %84, 0;\n"
    "wgmma.mma_async.sync.aligned.m64n160k16.f32.bf16.bf16 {%0,%1,%2,%3,%4,%5,%6,%7,%8,%9,%10,%11,%12,%13,%14,%15,%16,%17,%18,%19,%20,%21,%22,%23,%24,%25,%26,%27,%28,%29,%30,%31,%32,%33,%34,%35,%36,%37,%38,%39,%40,%41,%42,%43,%44,%45,%46,%47,%48,%49,%50,%51,%52,%53,%54,%55,%56,%57,%58,%59,%60,%61,%62,%63,%64,%65,%66,%67,%68,%69,%70,%71,%72,%73,%74,%75,%76,%77,%78,%79}, da, db, p, 1, 1, %85, %86; }"
    : "+f"(d[0]),"+f"(d[1]),"+f"(d[2]),"+f"(d[3]),"+f"(d[4]),"+f"(d[5]),"+f"(d[6]),"+f"(d[7]),"+f"(d[8]),"+f"(d[9]),"+f"(d[10]),"+f"(d[11]),"+f"(d[12]),"+f"(d[13]),"+f"(d[14]),"+f"(d[15]),"+f"(d[16]),"+f"(d[17]),"+f"(d[18]),"+f"(d[19]),"+f"(d[20]),"+f"(d[21]),"+f"(d[22]),"+f"(d[23]),"+f"(d[24]),"+f"(d[25]),"+f"(d[26]),"+f"(d[27]),"+f"(d[28]),"+f"(d[29]),"+f"(d[30]),"+f"(d[31]),"+f"(d[32]),"+f"(d[33]),"+f"(d[34]),"+f"(d[35]),"+f"(d[36]),"+f"(d[37]),"+f"(d[38]),"+f"(d[39]),"+f"(d[40]),"+f"(d[41]),"+f"(d[42]),"+f"(d[43]),"+f"(d[44]),"+f"(d[45]),"+f"(d[46]),"+f"(d[47]),"+f"(d[48]),"+f"(d[49]),"+f"(d[50]),"+f"(d[51]),"+f"(d[52]),"+f"(d[53]),"+f"(d[54]),"+f"(d[55]),"+f"(d[56]),"+f"(d[57]),"+f"(d[58]),"+f"(d[59]),"+f"(d[60]),"+f"(d[61]),"+f"(d[62]),"+f"(d[63]),"+f"(d[64]),"+f"(d[65]),"+f"(d[66]),"+f"(d[67]),"+f"(d[68]),"+f"(d[69]),"+f"(d[70]),"+f"(d[71]),"+f"(d[72]),"+f"(d[73]),"+f"(d[74]),"+f"(d[75]),"+f"(d[76]),"+f"(d[77]),"+f"(d[78]),"+f"(d[79])
    : "r"(alo), "r"(ahi), "r"(blo), "r"(bhi), "r"(sd), "n"(TA), "n"(TB)); }
  template<int TB> static __device__ __forceinline__ void rs(float* d, uint32_t a0, uint32_t a1, uint32_t a2, uint32_t a3, uint32_t blo, uint32_t bhi, int sd) {
  asm volatile("{ .reg .pred p; .reg .b64 db; mov.b64 db, {%84,%85}; setp.ne.b32 p, %87, 0;\n"
    "wgmma.mma_async.sync.aligned.m64n160k16.f32.bf16.bf16 {%0,%1,%2,%3,%4,%5,%6,%7,%8,%9,%10,%11,%12,%13,%14,%15,%16,%17,%18,%19,%20,%21,%22,%23,%24,%25,%26,%27,%28,%29,%30,%31,%32,%33,%34,%35,%36,%37,%38,%39,%40,%41,%42,%43,%44,%45,%46,%47,%48,%49,%50,%51,%52,%53,%54,%55,%56,%57,%58,%59,%60,%61,%62,%63,%64,%65,%66,%67,%68,%69,%70,%71,%72,%73,%74,%75,%76,%77,%78,%79}, {%80,%81,%82,%83}, db, p, 1, 1, %86; }"
    : "+f"(d[0]),"+f"(d[1]),"+f"(d[2]),"+f"(d[3]),"+f"(d[4]),"+f"(d[5]),"+f"(d[6]),"+f"(d[7]),"+f"(d[8]),"+f"(d[9]),"+f"(d[10]),"+f"(d[11]),"+f"(d[12]),"+f"(d[13]),"+f"(d[14]),"+f"(d[15]),"+f"(d[16]),"+f"(d[17]),"+f"(d[18]),"+f"(d[19]),"+f"(d[20]),"+f"(d[21]),"+f"(d[22]),"+f"(d[23]),"+f"(d[24]),"+f"(d[25]),"+f"(d[26]),"+f"(d[27]),"+f"(d[28]),"+f"(d[29]),"+f"(d[30]),"+f"(d[31]),"+f"(d[32]),"+f"(d[33]),"+f"(d[34]),"+f"(d[35]),"+f"(d[36]),"+f"(d[37]),"+f"(d[38]),"+f"(d[39]),"+f"(d[40]),"+f"(d[41]),"+f"(d[42]),"+f"(d[43]),"+f"(d[44]),"+f"(d[45]),"+f"(d[46]),"+f"(d[47]),"+f"(d[48]),"+f"(d[49]),"+f"(d[50]),"+f"(d[51]),"+f"(d[52]),"+f"(d[53]),"+f"(d[54]),"+f"(d[55]),"+f"(d[56]),"+f"(d[57]),"+f"(d[58]),"+f"(d[59]),"+f"(d[60]),"+f"(d[61]),"+f"(d[62]),"+f"(d[63]),"+f"(d[64]),"+f"(d[65]),"+f"(d[66]),"+f"(d[67]),"+f"(d[68]),"+f"(d[69]),"+f"(d[70]),"+f"(d[71]),"+f"(d[72]),"+f"(d[73]),"+f"(d[74]),"+f"(d[75]),"+f"(d[76]),"+f"(d[77]),"+f"(d[78]),"+f"(d[79])
    : "r"(a0), "r"(a1), "r"(a2), "r"(a3), "r"(blo), "r"(bhi), "n"(TB), "r"(sd)); }
};
template<> struct WG<176> { template<int TA, int TB> static __device__ __forceinline__ void ss(float* d, uint32_t alo, uint32_t ahi, uint32_t blo, uint32_t bhi, int sd) {
  asm volatile("{ .reg .pred p; .reg .b64 da, db; mov.b64 da, {%88,%89}; mov.b64 db, {%90,%91}; setp.ne.b32 p, %92, 0;\n"
    "wgmma.mma_async.sync.aligned.m64n176k16.f32.bf16.bf16 {%0,%1,%2,%3,%4,%5,%6,%7,%8,%9,%10,%11,%12,%13,%14,%15,%16,%17,%18,%19,%20,%21,%22,%23,%24,%25,%26,%27,%28,%29,%30,%31,%32,%33,%34,%35,%36,%37,%38,%39,%40,%41,%42,%43,%44,%45,%46,%47,%48,%49,%50,%51,%52,%53,%54,%55,%56,%57,%58,%59,%60,%61,%62,%63,%64,%65,%66,%67,%68,%69,%70,%71,%72,%73,%74,%75,%76,%77,%78,%79,%80,%81,%82,%83,%84,%85,%86,%87}, da, db, p, 1, 1, %93, %94; }"
    : "+f"(d[0]),"+f"(d[1]),"+f"(d[2]),"+f"(d[3]),"+f"(d[4]),"+f"(d[5]),"+f"(d[6]),"+f"(d[7]),"+f"(d[8]),"+f"(d[9]),"+f"(d[10]),"+f"(d[11]),"+f"(d[12]),"+f"(d[13]),"+f"(d[14]),"+f"(d[15]),"+f"(d[16]),"+f"(d[17]),"+f"(d[18]),"+f"(d[19]),"+f"(d[20]),"+f"(d[21]),"+f"(d[22]),"+f"(d[23]),"+f"(d[24]),"+f"(d[25]),"+f"(d[26]),"+f"(d[27]),"+f"(d[28]),"+f"(d[29]),"+f"(d[30]),"+f"(d[31]),"+f"(d[32]),"+f"(d[33]),"+f"(d[34]),"+f"(d[35]),"+f"(d[36]),"+f"(d[37]),"+f"(d[38]),"+f"(d[39]),"+f"(d[40]),"+f"(d[41]),"+f"(d[42]),"+f"(d[43]),"+f"(d[44]),"+f"(d[45]),"+f"(d[46]),"+f"(d[47]),"+f"(d[48]),"+f"(d[49]),"+f"(d[50]),"+f"(d[51]),"+f"(d[52]),"+f"(d[53]),"+f"(d[54]),"+f"(d[55]),"+f"(d[56]),"+f"(d[57]),"+f"(d[58]),"+f"(d[59]),"+f"(d[60]),"+f"(d[61]),"+f"(d[62]),"+f"(d[63]),"+f"(d[64]),"+f"(d[65]),"+f"(d[66]),"+f"(d[67]),"+f"(d[68]),"+f"(d[69]),"+f"(d[70]),"+f"(d[71]),"+f"(d[72]),"+f"(d[73]),"+f"(d[74]),"+f"(d[75]),"+f"(d[76]),"+f"(d[77]),"+f"(d[78]),"+f"(d[79]),"+f"(d[80]),"+f"(d[81]),"+f"(d[82]),"+f"(d[83]),"+f"(d[84]),"+f"(d[85]),"+f"(d[86]),"+f"(d[87])
    : "r"(alo), "r"(ahi), "r"(blo), "r"(bhi), "r"(sd), "n"(TA), "n"(TB)); }
};
template<> struct WG<192> { template<int TA, int TB> static __device__ __forceinline__ void ss(float* d, uint32_t alo, uint32_t ahi, uint32_t blo, uint32_t bhi, int sd) {
  asm volatile("{ .reg .pred p; .reg .b64 da, db; mov.b64 da, {%96,%97}; mov.b64 db, {%98,%99}; setp.ne.b32 p, %100, 0;\n"
    "wgmma.mma_async.sync.aligned.m64n192k16.f32.bf16.bf16 {%0,%1,%2,%3,%4,%5,%6,%7,%8,%9,%10,%11,%12,%13,%14,%15,%16,%17,%18,%19,%20,%21,%22,%23,%24,%25,%26,%27,%28,%29,%30,%31,%32,%33,%34,%35,%36,%37,%38,%39,%40,%41,%42,%43,%44,%45,%46,%47,%48,%49,%50,%51,%52,%53,%54,%55,%56,%57,%58,%59,%60,%61,%62,%63,%64,%65,%66,%67,%68,%69,%70,%71,%72,%73,%74,%75,%76,%77,%78,%79,%80,%81,%82,%83,%84,%85,%86,%87,%88,%89,%90,%91,%92,%93,%94,%95}, da, db, p, 1, 1, %101, %102; }"
    : "+f"(d[0]),"+f"(d[1]),"+f"(d[2]),"+f"(d[3]),"+f"(d[4]),"+f"(d[5]),"+f"(d[6]),"+f"(d[7]),"+f"(d[8]),"+f"(d[9]),"+f"(d[10]),"+f"(d[11]),"+f"(d[12]),"+f"(d[13]),"+f"(d[14]),"+f"(d[15]),"+f"(d[16]),"+f"(d[17]),"+f"(d[18]),"+f"(d[19]),"+f"(d[20]),"+f"(d[21]),"+f"(d[22]),"+f"(d[23]),"+f"(d[24]),"+f"(d[25]),"+f"(d[26]),"+f"(d[27]),"+f"(d[28]),"+f"(d[29]),"+f"(d[30]),"+f"(d[31]),"+f"(d[32]),"+f"(d[33]),"+f"(d[34]),"+f"(d[35]),"+f"(d[36]),"+f"(d[37]),"+f"(d[38]),"+f"(d[39]),"+f"(d[40]),"+f"(d[41]),"+f"(d[42]),"+f"(d[43]),"+f"(d[44]),"+f"(d[45]),"+f"(d[46]),"+f"(d[47]),"+f"(d[48]),"+f"(d[49]),"+f"(d[50]),"+f"(d[51]),"+f"(d[52]),"+f"(d[53]),"+f"(d[54]),"+f"(d[55]),"+f"(d[56]),"+f"(d[57]),"+f"(d[58]),"+f"(d[59]),"+f"(d[60]),"+f"(d[61]),"+f"(d[62]),"+f"(d[63]),"+f"(d[64]),"+f"(d[65]),"+f"(d[66]),"+f"(d[67]),"+f"(d[68]),"+f"(d[69]),"+f"(d[70]),"+f"(d[71]),"+f"(d[72]),"+f"(d[73]),"+f"(d[74]),"+f"(d[75]),"+f"(d[76]),"+f"(d[77]),"+f"(d[78]),"+f"(d[79]),"+f"(d[80]),"+f"(d[81]),"+f"(d[82]),"+f"(d[83]),"+f"(d[84]),"+f"(d[85]),"+f"(d[86]),"+f"(d[87]),"+f"(d[88]),"+f"(d[89]),"+f"(d[90]),"+f"(d[91]),"+f"(d[92]),"+f"(d[93]),"+f"(d[94]),"+f"(d[95])
    : "r"(alo), "r"(ahi), "r"(blo), "r"(bhi), "r"(sd), "n"(TA), "n"(TB)); }
};
template<> struct WG<208> { template<int TA, int TB> static __device__ __forceinline__ void ss(float* d, uint32_t alo, uint32_t ahi, uint32_t blo, uint32_t bhi, int sd) {
  asm volatile("{ .reg .pred p; .reg .b64 da, db; mov.b64 da, {%104,%105}; mov.b64 db, {%106,%107}; setp.ne.b32 p, %108, 0;\n"
    "wgmma.mma_async.sync.aligned.m64n208k16.f32.bf16.bf16 {%0,%1,%2,%3,%4,%5,%6,%7,%8,%9,%10,%11,%12,%13,%14,%15,%16,%17,%18,%19,%20,%21,%22,%23,%24,%25,%26,%27,%28,%29,%30,%31,%32,%33,%34,%35,%36,%37,%38,%39,%40,%41,%42,%43,%44,%45,%46,%47,%48,%49,%50,%51,%52,%53,%54,%55,%56,%57,%58,%59,%60,%61,%62,%63,%64,%65,%66,%67,%68,%69,%70,%71,%72,%73,%74,%75,%76,%77,%78,%79,%80,%81,%82,%83,%84,%85,%86,%87,%88,%89,%90,%91,%92,%93,%94,%95,%96,%97,%98,%99,%100,%101,%102,%103}, da, db, p, 1, 1, %109, %110; }"
    : "+f"(d[0]),"+f"(d[1]),"+f"(d[2]),"+f"(d[3]),"+f"(d[4]),"+f"(d[5]),"+f"(d[6]),"+f"(d[7]),"+f"(d[8]),"+f"(d[9]),"+f"(d[10]),"+f"(d[11]),"+f"(d[12]),"+f"(d[13]),"+f"(d[14]),"+f"(d[15]),"+f"(d[16]),"+f"(d[17]),"+f"(d[18]),"+f"(d[19]),"+f"(d[20]),"+f"(d[21]),"+f"(d[22]),"+f"(d[23]),"+f"(d[24]),"+f"(d[25]),"+f"(d[26]),"+f"(d[27]),"+f"(d[28]),"+f"(d[29]),"+f"(d[30]),"+f"(d[31]),"+f"(d[32]),"+f"(d[33]),"+f"(d[34]),"+f"(d[35]),"+f"(d[36]),"+f"(d[37]),"+f"(d[38]),"+f"(d[39]),"+f"(d[40]),"+f"(d[41]),"+f"(d[42]),"+f"(d[43]),"+f"(d[44]),"+f"(d[45]),"+f"(d[46]),"+f"(d[47]),"+f"(d[48]),"+f"(d[49]),"+f"(d[50]),"+f"(d[51]),"+f"(d[52]),"+f"(d[53]),"+f"(d[54]),"+f"(d[55]),"+f"(d[56]),"+f"(d[57]),"+f"(d[58]),"+f"(d[59]),"+f"(d[60]),"+f"(d[61]),"+f"(d[62]),"+f"(d[63]),"+f"(d[64]),"+f"(d[65]),"+f"(d[66]),"+f"(d[67]),"+f"(d[68]),"+f"(d[69]),"+f"(d[70]),"+f"(d[71]),"+f"(d[72]),"+f"(d[73]),"+f"(d[74]),"+f"(d[75]),"+f"(d[76]),"+f"(d[77]),"+f"(d[78]),"+f"(d[79]),"+f"(d[80]),"+f"(d[81]),"+f"(d[82]),"+f"(d[83]),"+f"(d[84]),"+f"(d[85]),"+f"(d[86]),"+f"(d[87]),"+f"(d[88]),"+f"(d[89]),"+f"(d[90]),"+f"(d[91]),"+f"(d[92]),"+f"(d[93]),"+f"(d[94]),"+f"(d[95]),"+f"(d[96]),"+f"(d[97]),"+f"(d[98]),"+f"(d[99]),"+f"(d[100]),"+f"(d[101]),"+f"(d[102]),"+f"(d[103])
    : "r"(alo), "r"(ahi), "r"(blo), "r"(bhi), "r"(sd), "n"(TA), "n"(TB)); }
};
template<> struct WG<224> { template<int TA, int TB> static __device__ __forceinline__ void ss(float* d, uint32_t alo, uint32_t ahi, uint32_t blo, uint32_t bhi, int sd) {
  asm volatile("{ .reg .pred p; .reg .b64 da, db; mov.b64 da, {%112,%113}; mov.b64 db, {%114,%115}; setp.ne.b32 p, %116, 0;\n"
    "wgmma.mma_async.sync.aligned.m64n224k16.f32.bf16.bf16 {%0,%1,%2,%3,%4,%5,%6,%7,%8,%9,%10,%11,%12,%13,%14,%15,%16,%17,%18,%19,%20,%21,%22,%23,%24,%25,%26,%27,%28,%29,%30,%31,%32,%33,%34,%35,%36,%37,%38,%39,%40,%41,%42,%43,%44,%45,%46,%47,%48,%49,%50,%51,%52,%53,%54,%55,%56,%57,%58,%59,%60,%61,%62,%63,%64,%65,%66,%67,%68,%69,%70,%71,%72,%73,%74,%75,%76,%77,%78,%79,%80,%81,%82,%83,%84,%85,%86,%87,%88,%89,%90,%91,%92,%93,%94,%95,%96,%97,%98,%99,%100,%101,%102,%103,%104,%105,%106,%107,%108,%109,%110,%111}, da, db, p, 1, 1, %117, %118; }"
    : "+f"(d[0]),"+f"(d[1]),"+f"(d[2]),"+f"(d[3]),"+f"(d[4]),"+f"(d[5]),"+f"(d[6]),"+f"(d[7]),"+f"(d[8]),"+f"(d[9]),"+f"(d[10]),"+f"(d[11]),"+f"(d[12]),"+f"(d[13]),"+f"(d[14]),"+f"(d[15]),"+f"(d[16]),"+f"(d[17]),"+f"(d[18]),"+f"(d[19]),"+f"(d[20]),"+f"(d[21]),"+f"(d[22]),"+f"(d[23]),"+f"(d[24]),"+f"(d[25]),"+f"(d[26]),"+f"(d[27]),"+f"(d[28]),"+f"(d[29]),"+f"(d[30]),"+f"(d[31]),"+f"(d[32]),"+f"(d[33]),"+f"(d[34]),"+f"(d[35]),"+f"(d[36]),"+f"(d[37]),"+f"(d[38]),"+f"(d[39]),"+f"(d[40]),"+f"(d[41]),"+f"(d[42]),"+f"(d[43]),"+f"(d[44]),"+f"(d[45]),"+f"(d[46]),"+f"(d[47]),"+f"(d[48]),"+f"(d[49]),"+f"(d[50]),"+f"(d[51]),"+f"(d[52]),"+f"(d[53]),"+f"(d[54]),"+f"(d[55]),"+f"(d[56]),"+f"(d[57]),"+f"(d[58]),"+f"(d[59]),"+f"(d[60]),"+f"(d[61]),"+f"(d[62]),"+f"(d[63]),"+f"(d[64]),"+f"(d[65]),"+f"(d[66]),"+f"(d[67]),"+f"(d[68]),"+f"(d[69]),"+f"(d[70]),"+f"(d[71]),"+f"(d[72]),"+f"(d[73]),"+f"(d[74]),"+f"(d[75]),"+f"(d[76]),"+f"(d[77]),"+f"(d[78]),"+f"(d[79]),"+f"(d[80]),"+f"(d[81]),"+f"(d[82]),"+f"(d[83]),"+f"(d[84]),"+f"(d[85]),"+f"(d[86]),"+f"(d[87]),"+f"(d[88]),"+f"(d[89]),"+f"(d[90]),"+f"(d[91]),"+f"(d[92]),"+f"(d[93]),"+f"(d[94]),"+f"(d[95]),"+f"(d[96]),"+f"(d[97]),"+f"(d[98]),"+f"(d[99]),"+f"(d[100]),"+f"(d[101]),"+f"(d[102]),"+f"(d[103]),"+f"(d[104]),"+f"(d[105]),"+f"(d[106]),"+f"(d[107]),"+f"(d[108]),"+f"(d[109]),"+f"(d[110]),"+f"(d[111])
    : "r"(alo), "r"(ahi), "r"(blo), "r"(bhi), "r"(sd), "n"(TA), "n"(TB)); }
};
template<> struct WG<240> { template<int TA, int TB> static __device__ __forceinline__ void ss(float* d, uint32_t alo, uint32_t ahi, uint32_t blo, uint32_t bhi, int sd) {
  asm volatile("{ .reg .pred p; .reg .b64 da, db; mov.b64 da, {%120,%121}; mov.b64 db, {%122,%123}; setp.ne.b32 p, %124, 0;\n"
    "wgmma.mma_async.sync.aligned.m64n240k16.f32.bf16.bf16 {%0,%1,%2,%3,%4,%5,%6,%7,%8,%9,%10,%11,%12,%13,%14,%15,%16,%17,%18,%19,%20,%21,%22,%23,%24,%25,%26,%27,%28,%29,%30,%31,%32,%33,%34,%35,%36,%37,%38,%39,%40,%41,%42,%43,%44,%45,%46,%47,%48,%49,%50,%51,%52,%53,%54,%55,%56,%57,%58,%59,%60,%61,%62,%63,%64,%65,%66,%67,%68,%69,%70,%71,%72,%73,%74,%75,%76,%77,%78,%79,%80,%81,%82,%83,%84,%85,%86,%87,%88,%89,%90,%91,%92,%93,%94,%95,%96,%97,%98,%99,%100,%101,%102,%103,%104,%105,%106,%107,%108,%109,%110,%111,%112,%113,%114,%115,%116,%117,%118,%119}, da, db, p, 1, 1, %125, %126; }"
    : "+f"(d[0]),"+f"(d[1]),"+f"(d[2]),"+f"(d[3]),"+f"(d[4]),"+f"(d[5]),"+f"(d[6]),"+f"(d[7]),"+f"(d[8]),"+f"(d[9]),"+f"(d[10]),"+f"(d[11]),"+f"(d[12]),"+f"(d[13]),"+f"(d[14]),"+f"(d[15]),"+f"(d[16]),"+f"(d[17]),"+f"(d[18]),"+f"(d[19]),"+f"(d[20]),"+f"(d[21]),"+f"(d[22]),"+f"(d[23]),"+f"(d[24]),"+f"(d[25]),"+f"(d[26]),"+f"(d[27]),"+f"(d[28]),"+f"(d[29]),"+f"(d[30]),"+f"(d[31]),"+f"(d[32]),"+f"(d[33]),"+f"(d[34]),"+f"(d[35]),"+f"(d[36]),"+f"(d[37]),"+f"(d[38]),"+f"(d[39]),"+f"(d[40]),"+f"(d[41]),"+f"(d[42]),"+f"(d[43]),"+f"(d[44]),"+f"(d[45]),"+f"(d[46]),"+f"(d[47]),"+f"(d[48]),"+f"(d[49]),"+f"(d[50]),"+f"(d[51]),"+f"(d[52]),"+f"(d[53]),"+f"(d[54]),"+f"(d[55]),"+f"(d[56]),"+f"(d[57]),"+f"(d[58]),"+f"(d[59]),"+f"(d[60]),"+f"(d[61]),"+f"(d[62]),"+f"(d[63]),"+f"(d[64]),"+f"(d[65]),"+f"(d[66]),"+f"(d[67]),"+f"(d[68]),"+f"(d[69]),"+f"(d[70]),"+f"(d[71]),"+f"(d[72]),"+f"(d[73]),"+f"(d[74]),"+f"(d[75]),"+f"(d[76]),"+f"(d[77]),"+f"(d[78]),"+f"(d[79]),"+f"(d[80]),"+f"(d[81]),"+f"(d[82]),"+f"(d[83]),"+f"(d[84]),"+f"(d[85]),"+f"(d[86]),"+f"(d[87]),"+f"(d[88]),"+f"(d[89]),"+f"(d[90]),"+f"(d[91]),"+f"(d[92]),"+f"(d[93]),"+f"(d[94]),"+f"(d[95]),"+f"(d[96]),"+f"(d[97]),"+f"(d[98]),"+f"(d[99]),"+f"(d[100]),"+f"(d[101]),"+f"(d[102]),"+f"(d[103]),"+f"(d[104]),"+f"(d[105]),"+f"(d[106]),"+f"(d[107]),"+f"(d[108]),"+f"(d[109]),"+f"(d[110]),"+f"(d[111]),"+f"(d[112]),"+f"(d[113]),"+f"(d[114]),"+f"(d[115]),"+f"(d[116]),"+f"(d[117]),"+f"(d[118]),"+f"(d[119])
    : "r"(alo), "r"(ahi), "r"(blo), "r"(bhi), "r"(sd), "n"(TA), "n"(TB)); }
};
template<> struct WG<256> { template<int TA, int TB> static __device__ __forceinline__ void ss(float* d, uint32_t alo, uint32_t ahi, uint32_t blo, uint32_t bhi, int sd) {
  asm volatile("{ .reg .pred p; .reg .b64 da, db; mov.b64 da, {%128,%129}; mov.b64 db, {%130,%131}; setp.ne.b32 p, %132, 0;\n"
    "wgmma.mma_async.sync.aligned.m64n256k16.f32.bf16.bf16 {%0,%1,%2,%3,%4,%5,%6,%7,%8,%9,%10,%11,%12,%13,%14,%15,%16,%17,%18,%19,%20,%21,%22,%23,%24,%25,%26,%27,%28,%29,%30,%31,%32,%33,%34,%35,%36,%37,%38,%39,%40,%41,%42,%43,%44,%45,%46,%47,%48,%49,%50,%51,%52,%53,%54,%55,%56,%57,%58,%59,%60,%61,%62,%63,%64,%65,%66,%67,%68,%69,%70,%71,%72,%73,%74,%75,%76,%77,%78,%79,%80,%81,%82,%83,%84,%85,%86,%87,%88,%89,%90,%91,%92,%93,%94,%95,%96,%97,%98,%99,%100,%101,%102,%103,%104,%105,%106,%107,%108,%109,%110,%111,%112,%113,%114,%115,%116,%117,%118,%119,%120,%121,%122,%123,%124,%125,%126,%127}, da, db, p, 1, 1, %133, %134; }"
    : "+f"(d[0]),"+f"(d[1]),"+f"(d[2]),"+f"(d[3]),"+f"(d[4]),"+f"(d[5]),"+f"(d[6]),"+f"(d[7]),"+f"(d[8]),"+f"(d[9]),"+f"(d[10]),"+f"(d[11]),"+f"(d[12]),"+f"(d[13]),"+f"(d[14]),"+f"(d[15]),"+f"(d[16]),"+f"(d[17]),"+f"(d[18]),"+f"(d[19]),"+f"(d[20]),"+f"(d[21]),"+f"(d[22]),"+f"(d[23]),"+f"(d[24]),"+f"(d[25]),"+f"(d[26]),"+f"(d[27]),"+f"(d[28]),"+f"(d[29]),"+f"(d[30]),"+f"(d[31]),"+f"(d[32]),"+f"(d[33]),"+f"(d[34]),"+f"(d[35]),"+f"(d[36]),"+f"(d[37]),"+f"(d[38]),"+f"(d[39]),"+f"(d[40]),"+f"(d[41]),"+f"(d[42]),"+f"(d[43]),"+f"(d[44]),"+f"(d[45]),"+f"(d[46]),"+f"(d[47]),"+f"(d[48]),"+f"(d[49]),"+f"(d[50]),"+f"(d[51]),"+f"(d[52]),"+f"(d[53]),"+f"(d[54]),"+f"(d[55]),"+f"(d[56]),"+f"(d[57]),"+f"(d[58]),"+f"(d[59]),"+f"(d[60]),"+f"(d[61]),"+f"(d[62]),"+f"(d[63]),"+f"(d[64]),"+f"(d[65]),"+f"(d[66]),"+f"(d[67]),"+f"(d[68]),"+f"(d[69]),"+f"(d[70]),"+f"(d[71]),"+f"(d[72]),"+f"(d[73]),"+f"(d[74]),"+f"(d[75]),"+f"(d[76]),"+f"(d[77]),"+f"(d[78]),"+f"(d[79]),"+f"(d[80]),"+f"(d[81]),"+f"(d[82]),"+f"(d[83]),"+f"(d[84]),"+f"(d[85]),"+f"(d[86]),"+f"(d[87]),"+f"(d[88]),"+f"(d[89]),"+f"(d[90]),"+f"(d[91]),"+f"(d[92]),"+f"(d[93]),"+f"(d[94]),"+f"(d[95]),"+f"(d[96]),"+f"(d[97]),"+f"(d[98]),"+f"(d[99]),"+f"(d[100]),"+f"(d[101]),"+f"(d[102]),"+f"(d[103]),"+f"(d[104]),"+f"(d[105]),"+f"(d[106]),"+f"(d[107]),"+f"(d[108]),"+f"(d[109]),"+f"(d[110]),"+f"(d[111]),"+f"(d[112]),"+f"(d[113]),"+f"(d[114]),"+f"(d[115]),"+f"(d[116]),"+f"(d[117]),"+f"(d[118]),"+f"(d[119]),"+f"(d[120]),"+f"(d[121]),"+f"(d[122]),"+f"(d[123]),"+f"(d[124]),"+f"(d[125]),"+f"(d[126]),"+f"(d[127])
    : "r"(alo), "r"(ahi), "r"(blo), "r"(bhi), "r"(sd), "n"(TA), "n"(TB)); }
  template<int TB> static __device__ __forceinline__ void rs(float* d, uint32_t a0, uint32_t a1, uint32_t a2, uint32_t a3, uint32_t blo, uint32_t bhi, int sd) {
  asm volatile("{ .reg .pred p; .reg .b64 db; mov.b64 db, {%132,%133}; setp.ne.b32 p, %135, 0;\n"
    "wgmma.mma_async.sync.aligned.m64n256k16.f32.bf16.bf16 {%0,%1,%2,%3,%4,%5,%6,%7,%8,%9,%10,%11,%12,%13,%14,%15,%16,%17,%18,%19,%20,%21,%22,%23,%24,%25,%26,%27,%28,%29,%30,%31,%32,%33,%34,%35,%36,%37,%38,%39,%40,%41,%42,%43,%44,%45,%46,%47,%48,%49,%50,%51,%52,%53,%54,%55,%56,%57,%58,%59,%60,%61,%62,%63,%64,%65,%66,%67,%68,%69,%70,%71,%72,%73,%74,%75,%76,%77,%78,%79,%80,%81,%82,%83,%84,%85,%86,%87,%88,%89,%90,%91,%92,%93,%94,%95,%96,%97,%98,%99,%100,%101,%102,%103,%104,%105,%106,%107,%108,%109,%110,%111,%112,%113,%114,%115,%116,%117,%118,%119,%120,%121,%122,%123,%124,%125,%126,%127}, {%128,%129,%130,%131}, db, p, 1, 1, %134; }"
    : "+f"(d[0]),"+f"(d[1]),"+f"(d[2]),"+f"(d[3]),"+f"(d[4]),"+f"(d[5]),"+f"(d[6]),"+f"(d[7]),"+f"(d[8]),"+f"(d[9]),"+f"(d[10]),"+f"(d[11]),"+f"(d[12]),"+f"(d[13]),"+f"(d[14]),"+f"(d[15]),"+f"(d[16]),"+f"(d[17]),"+f"(d[18]),"+f"(d[19]),"+f"(d[20]),"+f"(d[21]),"+f"(d[22]),"+f"(d[23]),"+f"(d[24]),"+f"(d[25]),"+f"(d[26]),"+f"(d[27]),"+f"(d[28]),"+f"(d[29]),"+f"(d[30]),"+f"(d[31]),"+f"(d[32]),"+f"(d[33]),"+f"(d[34]),"+f"(d[35]),"+f"(d[36]),"+f"(d[37]),"+f"(d[38]),"+f"(d[39]),"+f"(d[40]),"+f"(d[41]),"+f"(d[42]),"+f"(d[43]),"+f"(d[44]),"+f"(d[45]),"+f"(d[46]),"+f"(d[47]),"+f"(d[48]),"+f"(d[49]),"+f"(d[50]),"+f"(d[51]),"+f"(d[52]),"+f"(d[53]),"+f"(d[54]),"+f"(d[55]),"+f"(d[56]),"+f"(d[57]),"+f"(d[58]),"+f"(d[59]),"+f"(d[60]),"+f"(d[61]),"+f"(d[62]),"+f"(d[63]),"+f"(d[64]),"+f"(d[65]),"+f"(d[66]),"+f"(d[67]),"+f"(d[68]),"+f"(d[69]),"+f"(d[70]),"+f"(d[71]),"+f"(d[72]),"+f"(d[73]),"+f"(d[74]),"+f"(d[75]),"+f"(d[76]),"+f"(d[77]),"+f"(d[78]),"+f"(d[79]),"+f"(d[80]),"+f"(d[81]),"+f"(d[82]),"+f"(d[83]),"+f"(d[84]),"+f"(d[85]),"+f"(d[86]),"+f"(d[87]),"+f"(d[88]),"+f"(d[89]),"+f"(d[90]),"+f"(d[91]),"+f"(d[92]),"+f"(d[93]),"+f"(d[94]),"+f"(d[95]),"+f"(d[96]),"+f"(d[97]),"+f"(d[98]),"+f"(d[99]),"+f"(d[100]),"+f"(d[101]),"+f"(d[102]),"+f"(d[103]),"+f"(d[104]),"+f"(d[105]),"+f"(d[106]),"+f"(d[107]),"+f"(d[108]),"+f"(d[109]),"+f"(d[110]),"+f"(d[111]),"+f"(d[112]),"+f"(d[113]),"+f"(d[114]),"+f"(d[115]),"+f"(d[116]),"+f"(d[117]),"+f"(d[118]),"+f"(d[119]),"+f"(d[120]),"+f"(d[121]),"+f"(d[122]),"+f"(d[123]),"+f"(d[124]),"+f"(d[125]),"+f"(d[126]),"+f"(d[127])
    : "r"(a0), "r"(a1), "r"(a2), "r"(a3), "r"(blo), "r"(bhi), "n"(TB), "r"(sd)); }
};

template<int T> struct Conv {
    static __device__ __forceinline__ void run(float* acc, uint32_t da, uint32_t db) {
        WG<256 - 16 * T>::template ss<0, 0>(acc, da + (T >> 2) * 512 + (T & 3) * 2, dhi(1024, 1), db + T * 16, dhi(128, 0), T != 0);
        Conv<T + 1>::run(acc, da, db);
    }
};
template<> struct Conv<16> { static __device__ __forceinline__ void run(float*, uint32_t, uint32_t) {} };

template<int Q> __device__ __forceinline__ void ffn_epi(const float* g, const float* u, uint32_t* hq, char* dst, const uint32_t* tm, uint32_t par) {
    constexpr int U = Q >> 2, i = 4 * Q;
    uint32_t* o = hq + 8 * U;
    o[Q & 3] = hmul2(pack2relu(g[i], g[i + 1]), pack2(u[i], u[i + 1]));
    o[4 + (Q & 3)] = hmul2(pack2relu(g[i + 2], g[i + 3]), pack2(u[i + 2], u[i + 3]));
    asm volatile("" : "+r"(o[Q & 3]), "+r"(o[4 + (Q & 3)]) :: "memory");
    if ((Q & 3) == 0) {
        stg_tag(dst + U * 8192, o, tm, par);
        stg_tag(dst + U * 8192 + 512, o + 4, tm, par);
    }
}
__device__ __forceinline__ uint32_t tagged(float x, uint32_t tag) { return (__float_as_uint(x) & ~7u) | (tag & 7u); }
__device__ __forceinline__ uint32_t split2(float x) { const float h = bfround(x); return pack2(h, x - h); }
__device__ __forceinline__ float rsqrt_(float x) { float r; asm("rsqrt.approx.ftz.f32 %0, %1;" : "=f"(r) : "f"(x)); return r; }
__device__ __forceinline__ void acc_stat(float& s, float& q, uint32_t w) { const float a = bflo(w), c = bfhi(w); s += a; q = fmaf(a, a, q); s += c; q = fmaf(c, c, q); }
template<int I, int N, typename F> __device__ __forceinline__ void static_for(F&& f) {
    if constexpr (I < N) { f(std::integral_constant<int, I>{}); static_for<I + 1, N>(f); }
}

__device__ __forceinline__ int mod_col(int G) {
    const int s4 = (G >> 1) & 3;
    return G < 40 ? (s4 + (s4 == 3)) * 640 + (G >> 3) * 128 + (G & 1) * 64 : G < 50 ? 1920 + (G - 40) * 64 : 3200 + (G - 50) * 64;
}
__device__ __forceinline__ uint32_t silu2(uint32_t w) {
    const float a0 = bflo(w), a1 = bfhi(w);
    return pack2(__fdividef(a0, 1.f + __expf(-a0)), __fdividef(a1, 1.f + __expf(-a1)));
}

struct Maps { CUtensorMap k, v, q, g1, u1, g2, u2, wd, wn, wm, out; };
struct Ptrs { const char *k, *v, *shift, *ssm, *ssmD; char *scr, *out; const char *c, *Wg, *Wu, *Wd;
};

__global__ void __cluster_dims__(2, 1, 1) __launch_bounds__(384, 1)
fused_kernel(const __grid_constant__ Ptrs P, const __grid_constant__ Maps M) {
    extern __shared__ __align__(1024) char smraw[];
    const uint32_t clk0 = clock32();
    const uint32_t sb = smem_u32(smraw);
    const int tid = threadIdx.x, b = blockIdx.x;
    #define BAR(i) (sb + BARS + 8 * (i))
    if (tid < 256 && b < 128) {
        const uint32_t rv = tid >> 3, c = (tid ^ rv) & 7, rk = rv + 2 + 2 * (rv >> 3);
        const uint32_t go = ((b >> 1) * 32 + (rv & 6) * 4 + 2 * (rv >> 3) + (rv & 1)) * 1280 + (b & 1) * 128 + c * 16;
        cp16(sb + st_kv(0) + 5120 + tid * 16, padd(P.v, go));
        cp16(sb + st_kv(0) + rk * 128 + (((c ^ rk) & 7) << 4), padd(P.k, go));
        sched_bar();
        if ((rv & 22) == 16)
            asm volatile("cp.async.cg.shared.global [%0], [%1], 16, %2;" :: "r"(sb + st_kv(0) + (rk - 2) * 128 + (((c ^ (rk - 2)) & 7) << 4)), "l"(padd(P.k, b < 2 ? go : go - 10240)), "r"(b < 2 ? 0 : 16) : "memory");
        if (tid < 160) cp16(sb + ST_SH + tid * 16, padd(P.shift, (tid >> 5) * 512 + (b & 1) * 512 + tid * 16));
        asm volatile("cp.async.commit_group;" ::: "memory");
    }
    const int warp = __shfl_sync(~0u, tid >> 5, 0), lane = tid & 31;
    const int rank = b & 1, cl = b >> 1;
    #define FFN_ROLE int cl_ = cl; asm volatile("pmevent 1;" : "+r"(cl_)); const int cu = cl_ - 36, cv = (cu * 37) >> 8, \
        grp = cl_ < 4 ? 0 : cl_ < 36 ? (cl_ - 4) & 7 : 1 + cu - 7 * cv, js = cl_ < 4 ? 4 + cl_ : cl_ < 36 ? (cl_ - 4) >> 3 : 4 + cv, tile = 2 * grp + rank, dq = js & 3
    #define CNT(l, w) SC(cnt, (l) * 4096 + (w) * 4)
    uint32_t epoch;

    if (b >= 128) {
        if (tid == 256) { _Pragma("unroll") for (int i = 0; i < 20; i++) mbar_init(BAR(i), i < 10 ? 1 : 4); fence_async_smem(); }
        __syncthreads();
        epoch = ldg_late(CNT(C_Z, 6), lane);
        if (warp == 8) {
            if (elect()) {
                pf_map(&M.wm);
                wait_clock(clk0, D_SP);
                int s0 = 0, ph0 = 1;
                _Pragma("unroll 1") for (int i = 0; i < 15; i++) {
                    const int col = mod_col(4 * i + b - 128);
                    int s = s0, ph = ph0;
                    _Pragma("unroll 1") for (int j = 0; j < 4; j++) {
                        const int sl = (i & 1) * 5 + s;
                        mbar_wait(BAR(10 + sl), ph);
                        mbar_expect(BAR(sl), 20480);
                        tma2d(sb + sl * 20480, &M.wm, col, j * 160, BAR(sl));
                        if (++s == 5) { s = 0; ph ^= 1; }
                    }
                    if (i & 1) { s0 = s; ph0 = ph; }
                }
            }
        } else if (warp < 8) {
            const int wg = warp >> 2;
            sts32(sb + 204800 + tid * 4, silu2(__ldg((const uint32_t*)P.c + tid)));
            if (tid < 64) sts32(sb + 205824 + tid * 4, silu2(__ldg((const uint32_t*)P.c + 256 + tid)));
            fence_async_smem();
            bar_sync(1, 256);
            epoch = (__shfl_sync(~0u, epoch, 0) >> 7) + 1;
            int s = 0, ph = 0;
            _Pragma("unroll 1") for (int i = wg; i < 15; i += 2) {
                float acc[4];
                _Pragma("unroll 1") for (int j = 0; j < 4; j++) {
                    const int sl = wg * 5 + s;
                    mbar_wait(BAR(sl), ph);
                    wg_fence();
                    const uint32_t da = dlo(sb + sl * 20480, 16), db = dlo(sb + 204800 + j * 320, 16);
                    #pragma unroll
                    for (int ks = 0; ks < 10; ks++) WG<8>::ss<1, 0>(acc, da + ks * 128, dhi(1024, 1), db + ks * 2, dhi(128, 0), ks != 0 || j != 0);
                    wg_commit();
                    wg_wait<0>();
                    pin<4>(acc);
                    mbar_arrive_if(BAR(10 + sl), lane == 0);
                    if (++s == 5) { s = 0; ph ^= 1; }
                }
                const uint32_t m0 = pack2(acc[0], __shfl_down_sync(~0u, acc[0], 4)), m1 = pack2(acc[2], __shfl_down_sync(~0u, acc[2], 4));
                if ((lane & 7) == 0) {
                    char* mp = SC(mod, (mod_col(4 * i + b - 128) + (warp & 3) * 16 + (lane >> 2)) * 4);
                    asm volatile("{ .reg .b64 x; mov.b64 x, {%1, %3}; st.relaxed.gpu.global.b64 [%0], x; mov.b64 x, {%2, %3}; st.relaxed.gpu.global.b64 [%0+32], x; }" :: "l"(mp), "r"(m0), "r"(m1), "r"(epoch) : "memory");
                }
                STAMPIF(warp == 4, 1 + (i >> 1));
            }
        }
        return;
    }

    const bool l0 = lane == 0;
    const int q = lane & 3, rr = lane >> 2;

    if (warp < 8) {
        const int wg = warp >> 2, w = warp & 3, t = tid & 127;
        if (t < 5) sts128(wg ? sb + XB + (t & 1) * XP + 4096 : sb + ST_H + t * XP, 0, 0, 0, 0);
        bar_sync(0, 384);
        asm volatile("barrier.cluster.arrive.relaxed.aligned;" ::: "memory");
        STAMPIF(warp == 0, 1);
        asm volatile("setmaxnreg.inc.sync.aligned.u32 184;");
        uint32_t dv = 0;
        if (t < 5) asm volatile("ld.global.nc.u16 %0, [%1];" : "=r"(dv) : "l"(padd(P.ssmD, (b + 128 * t) * 2)));
        FFN_ROLE;
        epoch = ldg_late(CNT(C_Z + tile, 6), lane);
        asm volatile("cp.async.wait_group 0;" ::: "memory");
        bar_sync(2, 256);
        mbar_arrive_if(BAR(B_KV), tid == 0);
        epoch = (__shfl_sync(~0u, epoch, 0) >> 7) + 1;
        asm volatile("barrier.cluster.wait.aligned;" ::: "memory");
        uint32_t g2e;
        asm("mapa.shared::cluster.u32 %0, %1, %2;" : "=r"(g2e) : "r"(BAR(B_G2E)), "r"(rank ^ (lane & 1)));
        const bool l01 = lane < 2;
        const uint32_t wre = g2e - 8 * (B_G2E - B_WE);
        {
            const uint32_t par = epoch & 1, xa = sb + XB + wg * XP;
            const char* gp = SC(kvT, (b + 128 * wg) * 4096 + t * 16);
            if (wg) bar_arrive(1, 256);
            _Pragma("unroll 1") for (uint32_t steps = wg ? SEQ1 : SEQ0; steps; steps >>= 4) {
                const int r = (steps - 1) & 7;
                const uint32_t eb = sb + (((ESLOT >> (4 * r)) & 7) << 15);
                if (steps & 8) {
                    const int ew = (t >> 1) & 3, et = (ew + (t >> 3)) & 3, eh = (t >> 5) & 1;
                    const uint32_t ha = sb + ST_H + r * XP + ((t & 64) + 16 * et + 8 * eh + 2 * ew + (t & 1)) * 16;
                    const uint32_t ea = eb + (t & 64) * 128 + (2 * ew + eh) * 1024 + ((2 * et + (t & 1)) << 4);
                    mbar_wait(BAR(B_H + r), 0);
                    STAMPIF(warp == 1 && r == 0, 2);
                    uint4 hv4[4];
                    #pragma unroll
                    for (int i = 0; i < 4; i++) hv4[i] = lds128(ha + (i >> 1) * 2048 + (i & 1) * 16);
                    if (w == 0) { const uint32_t dr = __shfl_sync(~0u, dv, r); if (l0) hv4[1].x = hadd2(hv4[1].x, dr); }
                    #pragma unroll
                    for (int h = 0; h < 2; h++) {
                        const uint32_t* w8 = &hv4[2 * h].x;
                        #pragma unroll
                        for (int row = 0; row < 8; row++) {
                            uint32_t o[4];
                            #pragma unroll
                            for (int i = 0; i < 4; i++) o[i] = (row & 1) ? prmt(w8[(7 - row) / 2 + i], w8[(7 - row) / 2 + i + 1], 0x5432) : w8[(8 - row) / 2 + i];
                            sts128((ea ^ (row << 4)) + row * 128 + h * 16384, o[0], o[1], o[2], o[3]);
                            if (h == 1 && row == 1) mbar_arrive_if(BAR(B_EB + (r >= NEB)), l0);
                        }
                    }
                    if (!(steps & 128)) fence_async_smem();
                    STAMPIF(w == 0, wg ? 30 : 4);
                    continue;
                }
                float acc[128];
                mbar_wait(BAR(B_X + wg), (r >> 1) & 1);
                {
                    uint32_t t0, t1;
                    asm volatile("ld.shared.b32 %0, [%2]; ld.shared.b32 %1, [%2+2048];" : "=r"(t0), "=r"(t1) : "r"(xa + t * 16 + (lane >> 3) * 4) : "memory");
                    if (__any_sync(~0u, ((t0 ^ par) | (t1 ^ par)) & 1)) {

                        _Pragma("unroll 1") for (int h = 0; h < 2; h++) {
                            uint4 kx = {0, 0, 0, 0};
                            _Pragma("unroll 1") for (int it = 0; it < 20000; it++) {
                                ldg_rlx128_if(kx, gp + h * 2048, true);
                                const uint32_t tw = (lane & 16) ? ((lane & 8) ? kx.w : kx.z) : ((lane & 8) ? kx.y : kx.x);
                                if (!__any_sync(~0u, (tw ^ par) & 1)) break;
                            }
                            sts128(xa + t * 16 + h * 2048, kx.x, kx.y, kx.z, kx.w);
                        }
                        fence_async_smem();
                    }
                }
                STAMPIF(w == 0, 10 + r);
                bar_sync(1 + wg, 256);
                GSTAMPIF(w == 0 && r == 0, 7);
                gp += 2 * 524288;
                wg_fence();
                Conv<0>::run(acc, dlo(eb, 16), dlo(xa, 16));
                wg_commit();
                if (r < 4) bar_arrive(2 - wg, 256);
                wg_wait<0>();
                pin<128>(acc);
                STAMPIF(w == 0, 15 + r);
                bar_sync(5 + wg, 128);
                mbar_arrive_if(BAR(B_MD + r), t == 0 && r < 3);
                const uint32_t pw = eb + w * PP + lane * 16;
                #pragma unroll
                for (int g = 0; g < 8; g++) {
                    uint32_t o[4];
                    #pragma unroll
                    for (int l = 0; l < 4; l++) { const int i = 4 * g + l;
                        o[l] = i < 31 ? pack2(acc[4 * i] + acc[4 * i + 6], acc[4 * i + 1] + acc[4 * i + 7]) : pack2(acc[4 * i], acc[4 * i + 1]); }
                    asm volatile("stmatrix.sync.aligned.m8n8.x4.trans.shared.b16 [%0], {%1,%2,%3,%4};" :: "r"(pw + g * 512), "r"(o[0]), "r"(o[1]), "r"(o[2]), "r"(o[3]) : "memory");
                    if (g & 1) sched_bar();
                }
                if (lane < 6) sts128(pw + 4096, 0, 0, 0, 0);
                bar_sync(5 + wg, 128);
                char* yp = (char*)gp + (offsetof(Scratch, yT) - 2 * 524288);
                #pragma unroll
                for (int h = 0; h < 2; h++) {
                    uint4 p[4];
                    #pragma unroll
                    for (int k = 0; k < 4; k++) p[k] = lds128(eb + (t + 128 * h) * 16 + k * (PP + 32));
                    uint32_t y[4];
                    #pragma unroll
                    for (int j = 0; j < 4; j++) y[j] = hadd2((&p[0].x)[j], hadd2((&p[1].x)[j], hadd2((&p[2].x)[j], (&p[3].x)[j])));
                    stg_rlx128(yp + h * 2048, (y[0] & ~1u) | par, y[1], y[2], y[3]);
                    if (h == YH) red_if(CNT(C_Y + r, t), 1, t == 0);
                }
                __syncwarp();
                mbar_arrive_if(BAR(B_RD + r), l0);
                mbar_arrive_remote_if(wre + 16 * (r - 1) + (lane & 4) * 2, lane < 8 && (r == 1 || r == 2));
                STAMPIF(w == 0, 20 + r);
            }
        }
        float acc1[128];
        uint4 sv[2] = {};
        const char* s2p = SC(st2, (tile * 128 + wg * 64 + w * 16 + rr) * 16);
        auto pass1 = [&](int n0, int n1, auto&& top, auto&& mid) {
            _Pragma("unroll 1") for (int n = n0; n < n1; n++) {
                top();
                const uint32_t da = dlo(sb + wg * 4096, 16) + n * 512, db = dlo(sb + WR, 4096) + (n & 3) * 1024;
                TWAIT((n & 1) ? 91 : 10 + (n >> 1), mbar_wait(BAR(B_AF) + (n >> 1) * 8, 0));
                TWAIT(50 + n, mbar_wait(BAR(B_WF) + (n & 3) * 8, (n >> 2) & 1));
                GSTAMPIF(n == 0 && warp == 0, 8);
                STAMPIF(n == 0 && warp == 4, 9);
                STAMPI(warp == 0 && !(n & 1), 50 + (n >> 1));
                wg_fence();
                WG<256>::ss<0, 1>(acc1, da, dhi(512, 2), db, dhi(1024, 1), n0 ? 1 : n);
                WG<256>::ss<0, 1>(acc1, da + 2, dhi(512, 2), db + 128, dhi(1024, 1), 1);
                wg_commit();
                wg_wait<1>();
                mbar_arrive_remote_if(wre + ((n + 3) & 3) * 8, l01 && n > 0);
                mid(n);
            }
        };
        pass1(0, N_UT, []() {}, [](int) {});
        {
            float au[4];
            const int un = min(2 * b + wg, 239), cg = (un * 205) >> 10;
            char* up = SC(ut, ((un - 5 * cg) * 3072 + cg * 64 + w * 16 + rr) * 8);
            pass1(N_UT, N_UT + 1, [&]() {
                TWAIT(20, mbar_wait(BAR(B_UF), 0));
                const uint32_t ua = dlo(sb + UST + wg * 16384, 16), ub = dlo(sb + CS_TAB + wg * 512, 32);
                wg_fence();
                #pragma unroll
                for (int ks = 0; ks < 8; ks++) WG<8>::ss<1, 0>(au, ua + ks * 128, dhi(1024, 1), ub + ks * 4, dhi(128, 0), ks != 0);
                wg_commit();
            }, [&](int) {
                pin<4>(au);
                asm volatile("{ .reg .pred p; .reg .b64 x; setp.eq.b32 p, %5, 0; mov.b64 x, {%1, %2}; @p st.relaxed.gpu.global.b64 [%0], x; mov.b64 x, {%3, %4}; @p st.relaxed.gpu.global.b64 [%0+64], x; }"
                             :: "l"(up), "r"(tagged(au[0], epoch)), "f"(au[1]), "r"(tagged(au[2], epoch)), "f"(au[3]), "r"(q | (b >= 120)) : "memory");
                mbar_arrive_if(BAR(B_UD), l0);
                STAMPIF(warp == 0, 25);
            });
        }
        pass1(N_UT + 1, 20, []() {}, [&](int n) { ldg_rlx128_if(sv[0], s2p, n == 16); ldg_rlx128_if(sv[1], s2p + 128, n == 16); });
        _Pragma("unroll 1") for (int it = 0; it < 20000 && __any_sync(~0u, sv[0].w != epoch || sv[1].w != epoch); it++) { ldg_rlx128_if(sv[0], s2p, true); ldg_rlx128_if(sv[1], s2p + 128, true); }
        float acc2[64];
        const float rq0 = __uint_as_float(sv[0].z), rq1 = __uint_as_float(sv[1].z);
        {
            uint32_t ax[4];
            const uint32_t zm = q == 0 ? ~0u : q == 1 ? 0xffffu : 0u, sh = q ? 0x5454 : 0x5410, sl = sh + 0x2222;
            uint32_t a0 = prmt(sv[0].x, sv[0].y, sh), a1 = prmt(sv[1].x, sv[1].y, sh), a2 = prmt(sv[0].x, sv[0].y, sl), a3 = prmt(sv[1].x, sv[1].y, sl);
            TWAIT(21, mbar_wait(BAR(B_T1), 0));
            wg_wait<0>();
            mbar_arrive_remote_if(wre + 24, l01);
            asm volatile("setmaxnreg.inc.sync.aligned.u32 232;\n and.b32 %0, %4, %8; and.b32 %1, %5, %8; and.b32 %2, %6, %8; and.b32 %3, %7, %8;"
                         : "=r"(ax[0]), "=r"(ax[1]), "=r"(ax[2]), "=r"(ax[3]) : "r"(a0), "r"(a1), "r"(a2), "r"(a3), "r"(zm) : "memory");
            wg_fence();
            WG<256>::rs<1>(acc1, ax[0], ax[1], ax[2], ax[3], dlo(sb + TAB1, 0), dhi(48, 0), 1);
            WG<128>::rs<1>(acc2, ax[0], ax[1], ax[2], ax[3], dlo(sb + TAB2, 0), dhi(48, 0), 0);
            wg_commit();
        }
        char* hdst = SC(hh, (tile * 24 + js * 3) * 16384 + warp * 1024 + rr * 64 + ((q ^ (rr >> 1)) << 4));
        GSTAMPIF(warp == 0, 26);
        uint32_t hq[48];
        const uint32_t tm[4] = {lane < 8, (lane >> 3) == 1, (lane >> 3) == 2, lane >= 24};
        auto pass2 = [&](int it, auto&& epi) {
            TWAIT(70 + it, mbar_wait(BAR(B_WF) + (it & 3) * 8, ((it >> 2) & 1) ^ 1));
            STAMPI(warp == 0, 60 + it);
            const uint32_t da = dlo(sb + wg * 4096, 16) + it * 1024, db = dlo(sb + WR, 8192) + (it & 3) * 1024;
            wg_fence();
            static_for<0, 4>([&](auto KS) {
                WG<128>::ss<0, 1>(acc2, da + (KS.value >> 1) * 512 + (KS.value & 1) * 2, dhi(512, 2), db + KS.value * 128, dhi(1024, 1), 1);
                if constexpr (KS.value == 3) wg_commit();
                epi(KS);
            });
            wg_wait<1>();
        };
        pass2(0, [](auto) {});
        pin<128>(acc1);
        static_for<1, 5>([&](auto IT) {
            pass2(IT.value, [&](auto KS) {
                constexpr int sl = 4 * IT.value + KS.value - 4;
                sched_bar();
                ffn_epi<15 - sl>(acc1, acc1 + 64, hq, hdst, tm, epoch);
                if constexpr ((sl & 7) == 7) { __syncwarp(); mbar_arrive_if(BAR(B_HD + (sl >> 3)), l0); }
                sched_bar();
            });
            mbar_arrive_remote_if(wre + 8 * ((IT.value + 3) & 3), l01);
        });
        _Pragma("unroll 1") for (int it = 5; it < 10; it++) {
            pass2(it, [](auto) {});
            mbar_arrive_remote_if(wre + 8 * ((it + 3) & 3), l01 && it < 7);
            mbar_arrive_if(BAR(B_HS - 7) + 8 * it, l0 && it >= 7);
            mbar_arrive_remote_if(g2e + 8 * (it - G2R), l01 && it >= G2R);
        }
        {
            float acc[80];
            static_for<0, 3>([&](auto IT) {
                constexpr int it = IT.value;
                TWAIT(35 + it, mbar_wait(BAR(B_G2F + it), 0));
                STAMPI(warp == 0 && it == 0, 70);
                const uint32_t db = dlo(sb + G2B + it * 20480, 2048);
                #pragma unroll
                for (int i = 0; i < 16; i++) asm volatile("" : "+r"(hq[16 * it + i]) :: "memory");
                wg_fence();
                static_for<0, 4>([&](auto KS) {
                    constexpr int ks = KS.value, sl = 4 * it + ks;
                    const uint32_t* o = hq + 16 * it + 8 * (ks >> 1) + 2 * (ks & 1);
                    WG<160>::rs<1>(acc, o[0], o[4], o[1], o[5], db + (ks >> 1) * 640 + (ks & 1) * 64, dhi(512, 2), it != 0 || ks != 0);
                    if constexpr (sl == 0 || ks == 3) wg_commit();
                    if constexpr (sl == 0) {
                        wg_wait<1>();
                        pin<64>(acc2);
                        mbar_arrive_if(BAR(B_S0), l0);
                        static_for<10 - G2R, 6>([&](auto G) { mbar_arrive_remote_if(g2e + 8 * G.value, l01); });
                    }
                    if constexpr (sl < 8 / Q2) {
                        sched_bar();
                        static_for<0, Q2>([&](auto J) { ffn_epi<7 - Q2 * sl - J.value>(acc2, acc2 + 32, hq + 32, hdst + 32768, tm, epoch); });
                        if constexpr (sl == 8 / Q2 - 1) { __syncwarp(); mbar_arrive_if(BAR(B_HD + 2), l0); }
                        sched_bar();
                    }
                    if constexpr (sl == 0) wg_fence();
                });
                if (it) {
                    wg_wait<1>();
                    mbar_arrive_remote_if(g2e + 8 * (it ? it - 1 : 0), l01);
                }
            });
            mbar_wait(BAR(B_GB), 0);
            uint4 gw[5];
            #pragma unroll
            for (int i = 0; i < 5; i++) gw[i] = lds128(sb + GBT + q * 80 + i * 16);
            const uint32_t da = dlo(sb + G2A + wg * 4096, 16), db = dlo(sb + G2B, 2048);
            _Pragma("unroll 1") for (int it = 3; it < 12 - NST; it++) {
                const int g = it >= 6 ? it - 6 : it, ga = it >= 5 ? it - 5 : it + 1;
                TWAIT(35 + it, mbar_wait(BAR(B_G2F + g), it >= 6));
                TWAIT(77 + it, mbar_wait(BAR(B_AF - 3 + it), 1));
                STAMPI(warp == 0 && (it == 3 || it == 6), 70 + (it >> 2) + 1);
                wg_fence();
                #pragma unroll
                for (int ks = 0; ks < 4; ks++) WG<160>::ss<0, 1>(acc, da + ga * 1024 + (ks >> 1) * 512 + (ks & 1) * 2, dhi(512, 2), db + g * 1280 + (ks >> 1) * 640 + (ks & 1) * 64, dhi(512, 2), 1);
                wg_commit();
                wg_wait<1>();
                mbar_arrive_remote_if(g2e + 8 * (it - 1), l01 && it < 7);
                mbar_arrive_if(BAR(B_HS - 4) + 8 * it, l0 && it >= 4 && it < 7);
            }
            mbar_wait(BAR(B_G2F + 6 - NST), 1);
            mbar_wait(BAR(B_AF + 9 - NST), 1);
            if (wg) TWAIT(47, bar_sync(7, 256));
            STAMPI(warp == 0, 73);
            wg_fence();
            static_for<48 - 4 * NST, 48>([&](auto K) {
                constexpr int it = K.value >> 2, ks = K.value & 3;
                WG<160>::ss<0, 1>(acc, da + (it == 11 ? 0 : it - 5) * 1024 + (ks >> 1) * 512 + (ks & 1) * 2, dhi(512, 2), db + (it - 6) * 1280 + (ks >> 1) * 640 + (ks & 1) * 64, dhi(512, 2), 1);
                if constexpr (it < 11 && ks == 1) TWAIT(36 + it, mbar_wait(BAR(B_G2F + it - 5), 1));
                if constexpr (it < 11 && ks == 2) TWAIT(78 + it, mbar_wait(BAR(B_AF + it - 2), 1));
                if constexpr (K.value == 39) wg_commit();
                if constexpr (K.value == 46) { if (!wg) bar_arrive(7, 256); }
            });
            wg_commit();
            wg_wait<1>();
            bar_sync(5 + wg, 128);
            uint32_t osts[2];
            const uint32_t orow = (lane & 15) * 160 + (lane >> 4) * 16;
            osts[0] = sb + G2A + (1 + w) * 16384 + wg * 4096; osts[1] = osts[0] + 8192;
            wg_wait<0>();
            pin<80>(acc);
            STAMPIF(w == 0, 27 + wg);
            GSTAMPIF(warp == 4, 29);
            #pragma unroll
            for (int hf = 0; hf < 2; hf++) {
                #pragma unroll
                for (int i = 5 * hf; i < 5 * hf + 5; i++) {
                    uint32_t o[4];
                    #pragma unroll
                    for (int j = 0; j < 4; j++) { const int n = 4 * i + j; const float rq = (j & 1) ? rq1 : rq0; o[j] = hmul2(pack2(acc[2 * n] * rq, acc[2 * n + 1] * rq), (&gw[n >> 3].x)[(n >> 1) & 3]); }
                    asm volatile("stmatrix.sync.aligned.m8n8.x4.shared.b16 [%0], {%1,%2,%3,%4};" :: "r"(osts[hf] + orow + (i % 5) * 32), "r"(o[0]), "r"(o[1]), "r"(o[2]), "r"(o[3]) : "memory");
                }
                fence_async_smem();
                __syncwarp();
                if (elect()) { fence_async_glob(); tma2d_red(&M.out, osts[hf], dq * 160 + 80 * hf, 128 * tile + 16 * warp); }
            }
            STAMPIF(warp == 4, 31);
            if (elect()) asm volatile("cp.async.bulk.commit_group;\n cp.async.bulk.wait_group.read 0;" ::: "memory");
            STAMPIF(warp == 4, 33);
            GSTAMPIF(warp == 4, 34);
        }
    } else {
        const int hw = warp & 3, wv = hw & 1;
        if (elect()) {
            if (warp & 2) {
                if (warp & 1) { _Pragma("unroll") for (int i = B_UD; i < NBARS; i++) mbar_init(BAR(i), bar_count(i)); }
                else { _Pragma("unroll") for (int i = B_WF; i < B_UD; i++) mbar_init(BAR(i), bar_count(i)); }
            } else { _Pragma("unroll") for (int i = 0; i < 20; i++) mbar_init(BAR(i) + wv * 160, 1); }
            asm volatile("fence.mbarrier_init.release.cluster;" ::: "memory");
            fence_async_smem();
        }
        __syncwarp();
        asm volatile("barrier.cluster.arrive.relaxed.aligned;\n setmaxnreg.dec.sync.aligned.u32 136;" ::: "memory");
        const uint32_t t1 = clk0 + D_1 + ((((b * 37) & 127) * G_ST) >> 7);
        if (hw == 0) {
            bar_arrive(0, 384);
            if (lane < 15 && lane != B_KV) mbar_expect(BAR(lane), lane >= B_KV && lane < B_Q ? 9216 : 4096);
            __syncwarp();
            if (elect()) { wait_until(t1); bulk_g2s(sb + ST_H + 16, P.ssm + b * 4096, 4096, BAR(B_H)); }
            __syncwarp();
            bar_sync(3, 128);
        } else { bar_sync(0, 384); bar_arrive(3, 128); }
        FFN_ROLE;
        const int kh = js >> 2, ft = tile * 8 + js;
        const int oz = __shfl_sync(~0u, tid >> 9, lane);
        epoch = ldg_rlx32(CNT(C_Z + tile, 6 + oz));
        if (hw == 0) {
            if (elect()) {
                auto x_fetch = [&](int r) {
                    if (!mbar_test(BAR(B_KV + r), 0)) { mbar_wait(BAR(B_KV + r), 0); pause(D_PK); }
                    poll_cnt(CNT(C_KV + 2 * r + (b >> 6), 0), (epoch | 127) + 1);
                    fence_async_glob();
                    if (r >= 2) mbar_wait(BAR(B_MD - 2 + r), 0);
                    mbar_expect(BAR(B_X + (r & 1)), 4096);
                    bulk_g2s(sb + XB + (r & 1) * XP, SC(kvT, (b + 128 * r) * 4096), 4096, BAR(B_X + (r & 1)));
                    STAMPIF(r < 2, 5 + r);
                };
                static_for<1, NORD>([&](auto I) {
                    constexpr char kind = ord_kind(I.value); constexpr int n = ord_index(I.value);
                    if constexpr (kind == 'k' && n >= 3) mbar_wait(BAR(B_TD + n - 3), 0);
                    if constexpr (kind == 'q' && (n == 0 || n == NEB)) mbar_wait(BAR(B_EB + (n > 0)), 0);
                    if constexpr (kind != '_' && kind != 'x') wait_until(t1 + ord_slot(I.value) * G_U);
                    if constexpr (kind == 'k') { tma4d(sb + st_kv(n), &M.k, n * 128 + rank * 64, cl * 4 - 1, BAR(B_KV + n)); tma4d(sb + st_kv(n) + 5120, &M.v, n * 128 + rank * 64, cl * 4, BAR(B_KV + n)); }
                    if constexpr (kind == 'q') tma3d(sb + ST_Q + n * 4096, &M.q, ft * 16, n * 4, BAR(B_Q + n));
                    if constexpr (kind == 'h') bulk_g2s(sb + ST_H + n * XP + 16, P.ssm + (b + 128 * n) * 4096, 4096, BAR(B_H + n));
                    if constexpr (kind == 'w') pf_l2(((n & 1) ? P.Wu : P.Wg) + (b + 128 * (n >> 1)) * 3072, 3072);
                    if constexpr (kind == 'x') x_fetch(n);
                });
                _Pragma("unroll 1") for (int r = ord_count('x'); r < 5; r++) x_fetch(r);
            }
        } else if (hw == 2 && elect()) { pf_map(&M.k); pf_map(&M.v); pf_map(&M.q); }
        __syncwarp();
        const bool third = hw < 3;
        float sa[6] = {0.f, 0.f, 0.f, 0.f, 0.f, 0.f};
        uint32_t aQ[3];
        #pragma unroll
        for (int u = 0; u < 3; u++) { const int un = hw - 1 + 3 * u; aQ[u] = sb + ST_Q + (un >> 1) * 1024 + (lane & 15) * 64 + (((lane >> 1) + (lane >> 4) + 2 * un) & 3) * 16; }
        auto q_stat = [&](int r) {
            mbar_wait(BAR(B_Q + r), 0);
            STAMPIF(hw == 1 && r == 4, 44);
            uint4 v[3] = {};
            #pragma unroll
            for (int u = 0; u < 3; u++) lds128_if(v[u], aQ[u] + r * 4096, u < 2 || third);
            sched_bar();
            #pragma unroll
            for (int j = 0; j < 12; j++) acc_stat(sa[2 * (j % 3)], sa[2 * (j % 3) + 1], (&v[j % 3].x)[j / 3]);
            if (r == 4) {
                asm volatile("st.shared.v2.f32 [%0], {%1,%2};" :: "r"(sb + ST_S + (lane & 15) * 48 + (hw - 1) * 16 + (lane >> 4) * 8), "f"(sa[0] + sa[2] + sa[4]), "f"(sa[1] + sa[3] + sa[5]) : "memory");
                if (hw == 1) bar_arrive(4, 96); else bar_sync(4, 96);
            }
        };
        const char* mp = SC(mod, ((lane >> 4) * 32 + wv * 16 + (lane & 15)) * 8);
        auto maddr = [&](int i) { return mp + (i + (i == 3)) * 2560; };
        uint2 mv[4] = {};
        uint32_t hv = 0;
        const char* yc = CNT(C_Y, lane & 1);
        auto look_ahead = [&]() {
            hv = ldg_rlx32(yc);
            #pragma unroll
            for (int i = 0; i < 4; i++) mv[i] = ldg_rlx64(maddr(i));
        };
        epoch = (__shfl_sync(~0u, epoch, 0) >> 7) + 1;
        const uint32_t target = epoch << 7, par = epoch & 1;
        if (hw) {
            auto krow = [&](int o) { const int tk = 39 - 8 * ((lane & 7) >> 1) - o, ro = (tk & 1) + 2 * (tk >> 3) + 10 * ((tk >> 1) & 3); return ro * 128 + ((ro & 7) << 4); };
            const int o0 = 2 * (lane >> 3) + (lane & 1);
            const int tv = 31 - 8 * ((lane & 7) >> 1) - o0, rv = (tv & 1) + 2 * (tv >> 3) + 8 * ((tv >> 1) & 3);
            uint32_t aE[3], aH[3], aV[3];
            #pragma unroll
            for (int u = 0; u < 3; u++) {
                const uint32_t cx = (hw - 1 + 3 * u) << 4;
                aE[u] = sb + (krow(o0) ^ cx); aH[u] = sb + (krow(8 + (o0 & 3)) ^ cx); aV[u] = sb + ((5120 + rv * 128 + ((rv & 7) << 4)) ^ cx);
            }
            const uint32_t aS = sb + ST_SH + rr * 8 + (hw - 1) * 64;
            char* dst = SC(kvT, (rank * 64 + (hw - 1) * 8 + rr) * 4096 + (252 - 4 * cl + q) * 16);
            const char* hc = CNT(C_KV + rank, lane);
            uint32_t tm[4];
            #pragma unroll
            for (int j = 0; j < 4; j++) tm[j] = (((63 - cl) >> 1) & 3) == j;
            uint32_t ke[3][6] = {}, vv[3][4] = {};
            int r = 0, rq = 0;
            _Pragma("unroll 1") for (uint32_t todo = ord_tasks(); todo > (hw == 1 ? 1 : 3); todo >>= 1) {
                if (todo < (4u << NPRE) && todo >= (2u << NPRE) && hw >= 2) look_ahead();
                if (!(todo & 1)) q_stat(rq++);
                else {
                    const uint32_t so = st_kv(r);
                    mbar_wait(BAR(B_KV + r), 0);
                    STAMPIF(hw == 1 && (r & 3) == 0, 35 + r);
                    red_if(hc, 2, l0 && !third && r < NEH);
                    uint2 sw[3]; uint32_t o[3][4];
                    #pragma unroll
                    for (int u = 0; u < 3; u++) {
                        sw[u] = lds64(aS + r * 512 + u * 192);
                        if (u < 2) { ldsm4t(ke[u], aE[u] + so); ldsm2t(ke[u][4], ke[u][5], aH[u] + so); ldsm4t(vv[u], aV[u] + so); }
                        else { ldsm4t_if(ke[u], aE[u] + so, third); ldsm2t_if(ke[u] + 4, aH[u] + so, third); ldsm4t_if(vv[u], aV[u] + so, third); }
                    }
                    sched_bar();
                    #pragma unroll
                    for (int u = 0; u < 3; u++) {
                        const uint32_t w0 = prmt(sw[u].x, 0, 0x1010), w1 = prmt(sw[u].x, 0, 0x3232), w2 = prmt(sw[u].y, 0, 0x1010), w3 = prmt(sw[u].y, 0, 0x3232);
                        uint32_t ko[5];
                        #pragma unroll
                        for (int j = 0; j < 5; j++) ko[j] = prmt(ke[u][j], ke[u][j + 1], 0x5432);
                        #pragma unroll
                        for (int j = 0; j < 4; j++) o[u][j] = hmul2(hfma2(ke[u][j], w0, hfma2(ko[j], w1, hfma2(ke[u][j + 1], w2, hmul2(ko[j + 1], w3)))), vv[u][j]);
                        #pragma unroll
                        for (int j = 0; j < 4; j++) o[u][j] = (o[u][j] & ~tm[j]) | (par & tm[j]);
                    }
                    asm volatile("{ .reg .pred p, h; setp.ne.b32 p, %13, 0; setp.ne.b32 h, %15, 0; pmevent 1;\n"
                                 " @h red.relaxed.gpu.global.add.u32 [%14], 2;\n"
                                 " st.relaxed.gpu.global.v4.b32 [%0], {%1,%2,%3,%4}; st.relaxed.gpu.global.v4.b32 [%0+98304], {%5,%6,%7,%8}; @p st.relaxed.gpu.global.v4.b32 [%0+196608], {%9,%10,%11,%12}; }"
                                 :: "l"(dst), "r"(o[0][0]), "r"(o[0][1]), "r"(o[0][2]), "r"(o[0][3]), "r"(o[1][0]), "r"(o[1][1]), "r"(o[1][2]), "r"(o[1][3]),
                                    "r"(o[2][0]), "r"(o[2][1]), "r"(o[2][2]), "r"(o[2][3]), "r"((int)third), "l"(hc), "r"((int)(r >= NEH && l0 && hw == 1)) : "memory");
                    mbar_arrive_if(BAR(B_TD + r), l0 && r < 2);
                    if (r == 2 && hw == 1) bar_arrive(8, 96);
                    STAMPIF(hw == 1 && (r & 3) == 0, r ? 3 : 45);
                    r++; dst += 524288; hc += 8192;
                }
            }
        }
        if (hw >= 2) {
            const uint32_t ys = sb + ST_Y + wv * 2048, ct = sb + ST_C + wv * 384;
            const uint32_t yd = ys + ((lane & 1) * 4 + ((lane >> 2) & 3)) * 128 + (((2 * (lane >> 4) + ((lane >> 1) & 1)) ^ (2 * ((lane >> 2) & 1) + 4 * (lane & 1))) << 4);
            const uint32_t yl = ys + (lane >> 3) * 128 + (((lane & 7) ^ (2 * ((lane >> 3) & 1))) << 4);
            const uint32_t ym = rr ? 0u : 0x00010001u;
            const char* yp = SC(yT, (wv * 32 + (lane >> 1)) * 4096 + (254 - 2 * ft + (lane & 1)) * 16);
            auto y_fetch = [&]() {
                #pragma unroll
                for (int i = 0; i < 4; i++) cp16((yd ^ ((i & 1) << 6)) + (i >> 1) * 1024, yp + (i & 1) * 65536 + (i >> 1) * 262144);
                asm volatile("cp.async.commit_group;" ::: "memory");
            };
            bar_sync(8, 96);
            bool early = false;
            uint32_t rs[2] = {}, mr[2] = {};
            const int un = min(2 * b + wv, 239), cg = (un * 205) >> 10, ur = un - 5 * cg;
            char* zp = SC(z, tile * 163840 + wv * 8192 + (16 * js + 15 - rr) * 64 + ((q ^ 3 ^ (rr >> 1)) << 4));
            char* op = padd(P.out, (ft * 16 + 15 - rr) * 1280 + wv * 64 + q * 16);
            uint32_t xs = sb + ST_Q + wv * 1024 + (15 - rr) * 64 + q * 16;
            const uint32_t tm[4] = {lane >= 24, (lane >> 3) == 2, (lane >> 3) == 1, lane < 8};
            const char* zc = CNT(C_Z + tile, lane & 7);
            _Pragma("unroll 1") for (int r = 0; r < 5; r++) {
                STAMPR(0);
                if (!early) { early = reached(hv, target); if (early) y_fetch(); }
                ll_wait<4>(mv, epoch, maddr);
                STAMPR(1);
                {
                    const uint32_t ca = ct + (lane >> 4) * 192 + (lane & 15) * 4;
                    sts32(ca, hmul2(mv[2].x, hadd2(mv[1].x, 0x3f803f80u))); sts32(ca + 64, hmul2(mv[2].x, mv[0].x)); sts32(ca + 128, hadd2(mv[3].x, 0x3f803f80u));
                }
                __syncwarp();
                STAMPIF(wv == 0 && r == 0, 47);
                mp += 512; yc += 4096;
                uint4 x[4], cA[2], cB[2], cC[2];
                #pragma unroll
                for (int i = 0; i < 4; i++) x[i] = lds128(xs + (i >> 1) * 2048 - (i & 1) * 512);
                #pragma unroll
                for (int o = 0; o < 2; o++) { cA[o] = lds128(ct + q * 16 + o * 192); cB[o] = lds128(ct + q * 16 + o * 192 + 64); cC[o] = lds128(ct + q * 16 + o * 192 + 128); }
                STAMPR(2);
                STAMPR(3);
                if (r == 0) {
                    q_stat(4);
                    STAMPIF(wv, 46);
                    #pragma unroll
                    for (int h = 0; h < 2; h++) {
                        float f[2] = {0.f, 0.f};
                        #pragma unroll
                        for (int i = 0; i < 3; i++) { const uint4 a = lds128(sb + ST_S + (15 - 8 * h - rr) * 48 + i * 16); f[0] += __uint_as_float(a.x) + __uint_as_float(a.z); f[1] += __uint_as_float(a.y) + __uint_as_float(a.w); }
                        const float mu = f[0] * (1.f / D_), r_ = rsqrt_(fmaxf(f[1] * (1.f / D_) - mu * mu, 0.f) + 1e-5f);
                        rs[h] = pack2(r_, r_); const float m_ = -mu * bflo(rs[h]); mr[h] = pack2(m_, m_);
                        sa[2 * h] = sa[2 * h + 1] = 0.f;
                    }
                }
                STAMPR(4);
                uint32_t y[4][4];
                _Pragma("unroll 1") for (int it = 0; it < 20000; it++) {
                    if (!early) { if (!mbar_test(BAR(B_RD + r), 0)) { mbar_wait(BAR(B_RD + r), 0); pause(D_PY); } poll_cnt(CNT(C_Y + r, 0), target); y_fetch(); }
                    STAMPIF(wv == 0 && r == 0, 48);
                    look_ahead();
                    asm volatile("cp.async.wait_group 0;" ::: "memory");
                    __syncwarp();
                    STAMPR(5);
                    uint32_t all = ~0u, any = 0;
                    #pragma unroll
                    for (int i = 0; i < 4; i++) ldsm4t(y[i], (yl ^ ((i & 1) << 6)) + i * 512);
                    #pragma unroll
                    for (int j = 0; j < 16; j++) { all &= y[j >> 2][j & 3]; any |= y[j >> 2][j & 3]; }
                    if (!__any_sync(~0u, ((par ? ~all : any) & ym) != 0)) break;
                    early = false;
                }
                STAMPR(6);
                mbar_arrive_if(BAR(B_TD), lane <= wv && r == 4);
                #pragma unroll
                for (int j = 0; j < 16; j++) {
                    uint32_t& xv = (&x[j >> 2].x)[j & 3];
                    xv = hfma2(hfma2(hfma2(xv, rs[(j >> 2) & 1], mr[(j >> 2) & 1]), (&cA[j >> 3].x)[j & 3], (&cB[j >> 3].x)[j & 3]), y[j >> 2][j & 3], xv);
                    y[j >> 2][j & 3] = (hmul2(xv, (&cC[j >> 3].x)[j & 3]) & ~tm[j & 3]) | (par & tm[j & 3]);
                    asm volatile("" : "+r"(y[j >> 2][j & 3]) :: "memory");
                }
                sched_bar();
                #pragma unroll
                for (int i = 0; i < 4; i++) asm volatile("st.relaxed.gpu.global.v4.b32 [%0], {%1,%2,%3,%4};" :: "l"(zp + (i >> 1) * 16384 - (i & 1) * 512), "r"(y[i][0]), "r"(y[i][1]), "r"(y[i][2]), "r"(y[i][3]) : "memory");
                red_if(zc, 8, lane == r);
                mbar_arrive_if(BAR(B_KV + r), tid == 352);
                STAMPIF(wv, 75 + r);
                STAMPIF(wv == 0 && r == 0, 49); STAMPR(7);
                yp += 524288;
                early = reached(hv, target) && r < 4;
                if (early) y_fetch();
                asm volatile("{ .reg .pred p; setp.eq.b32 p, %2, 0; @p ld.relaxed.gpu.global.u32 %0, [%1]; }" : "+r"(hv) : "l"(yc), "r"((int)early) : "memory");
                if (r == 4) {
                    mbar_wait(BAR(B_TD), 1);
                    if (elect()) {
                        mbar_expect(BAR(B_UF), 16384);
                        #pragma unroll
                        for (int i = 0; i < 2; i++) tma2d(sb + UST + wv * 16384 + i * 8192, cg >= 24 ? &M.u2 : &M.g2, (cg >= 24 ? cg - 24 : cg) * 64, ur * 128 + i * 64, BAR(B_UF));
                    }
                    __syncwarp();
                }
                sched_bar();
                STAMPR(8);
                #pragma unroll
                for (int j = 0; j < 16; j++) acc_stat(sa[j & 2], sa[(j & 2) + 1], (&x[(j >> 1) & 3].x)[(j & 1) + (j >> 3) * 2]);
                #pragma unroll
                for (int j = 0; j < 4; j++) asm volatile("" : "+f"(sa[j]) :: "memory");
                sched_bar();
                STAMPR(9);
                #pragma unroll
                for (int i = 0; i < 4; i++) stg128(op + (i >> 1) * 128 - (i & 1) * 10240, x[i].x, x[i].y, x[i].z, x[i].w);
                zp += 32768; op += 256; xs += 4096;
                STAMPR(10);
            }
            {
                const char* cp_ = SC(mod, (3 * 320 + ur * 64 + lane) * 8);
                auto caddr = [&](int i) { return cp_ + (i & 1) * 256 + (i >> 1) * 2560; };
                #pragma unroll
                for (int i = 0; i < 4; i++) mv[i] = ldg_rlx64(caddr(i));
                ll_wait<4>(mv, epoch, caddr);
                #pragma unroll
                for (int i = 0; i < 4; i++) sts32(sb + CS_TAB + wv * 512 + ((i & 1) * 8 + rr) * 32 + q * 4 + (i < 2 ? 16 : 0), i < 2 ? mv[i].x : hadd2(mv[i].x, 0x3f803f80u));
                fence_async_smem(); __syncwarp(); mbar_arrive_if(BAR(B_UF), l0);
                STAMPIF(wv, 41);
            }
            const float e0 = ((q & 2) ? sa[2] : sa[0]) + __shfl_xor_sync(~0u, (q & 2) ? sa[0] : sa[2], 2), e1 = ((q & 2) ? sa[3] : sa[1]) + __shfl_xor_sync(~0u, (q & 2) ? sa[1] : sa[3], 2);
            float e = ((q & 1) ? e1 : e0) + __shfl_xor_sync(~0u, (q & 1) ? e0 : e1, 1);
            if (wv) sts32(sb + TAB1 + 1280 + lane * 4, __float_as_uint(e));
            bar_sync(4, 64);
            if (wv) {
                if (l0) asm volatile("fence.release.gpu;\n red.relaxed.gpu.global.add.u32 [%0], 16;" :: "l"(CNT(C_Z + tile, 6)) : "memory");
                __syncwarp();
            } else {
                uint32_t oth; asm volatile("ld.shared.b32 %0, [%1];" : "=r"(oth) : "r"(sb + TAB1 + 1280 + lane * 4) : "memory");
                e += __uint_as_float(oth);
                const float mu = e * (1.f / D_), ve = fmaxf(__shfl_down_sync(~0u, e, 1) * (1.f / D_) - mu * mu, 0.f) + 1e-5f, r_ = rsqrt_(ve);
                if (!(q & 1)) stg_rlx128(SC(st2, (ft * 16 + 15 - rr - 4 * q) * 16), split2(-mu), split2(ve * r_), __float_as_uint(r_ * r_), epoch);
            }
            if (!wv && elect()) pf_l2(P.Wd + b * 15360, 15360);
            mbar_wait(BAR(B_UD), 0);
            pause(D_UT);
            _Pragma("unroll 1") for (int n = wv ^ 1; n < 3; n += 2) {
            const char* up = SC(ut, (js * 192 + n * 64 + 2 * lane) * 8);
            uint4 v[10];
            _Pragma("unroll 1") for (int it = 0; it < 20000; it++) {
                uint32_t bad = 0;
                #pragma unroll
                for (int i = 0; i < 10; i++) v[i] = ldg_rlx2x64(up + i * 12288);
                #pragma unroll
                for (int i = 0; i < 10; i++) bad |= (v[i].x ^ epoch) | (v[i].z ^ epoch);
                if (!__any_sync(~0u, (bad & 7) != 0)) break;
            }
            #pragma unroll
            for (int h = 0; h < 2; h++) {
                float f[4];
                #pragma unroll
                for (int j = 0; j < 4; j++) f[j] = (__uint_as_float((&v[h].x)[j]) + __uint_as_float((&v[2 + h].x)[j])) + (__uint_as_float((&v[4 + h].x)[j]) + __uint_as_float((&v[6 + h].x)[j])) + __uint_as_float((&v[8 + h].x)[j]);
                const uint32_t ta = sb + TAB1 + ((n == 2 ? 32 + h * 8 : n * 8 + h * 16) + rr) * 48 + q * 4, th2 = pack2(f[1], f[3]);
                sts32(ta, pack2(f[0], f[2])); sts32(ta + 16, th2); sts32(ta + 32, pack2(f[1] - bflo(th2), f[3] - bfhi(th2)));
            }
            }
            if (lane < 20) sts32(sb + TAB1 + 48 * 48 + lane * 4, 0);
            fence_async_smem();
            __syncwarp();
            mbar_arrive_if(BAR(B_T1), l0);
            STAMPIF(hw == 3, 43);
        }
        asm volatile("setmaxnreg.dec.sync.aligned.u32 40;");
        const uint32_t ep2 = __shfl_sync(~0u, epoch, 0), tg2 = ep2 << 7;
        const char* hfl = CNT(C_HH + tile * 2 + kh, 0);
        auto hh_src = [&](int j) { const int c = (j * 11) >> 5, m = j - 3 * c; return SC(hh, (tile * 24 + (kh * 4 + m + (m >= dq)) * 3 + (c ^ (c < 2))) * 16384); };
        if (hw == 0) {
            if (elect()) {
                const CUtensorMap *m1 = rank ? &M.u1 : &M.g1, *m2 = rank ? &M.u2 : &M.g2;
                const char* pw = P.Wg + (b + 128 * (NWP >> 1)) * 3072;
                const long long dw = P.Wu - P.Wg;
                pf_map(m1);
                _Pragma("unroll 1") for (int n = 0; n < 20; n += 2) {
                    #pragma unroll
                    for (int h = 0; h < 2; h++) {
                        const uint32_t so = (n & 2) + h;
                        mbar_wait(BAR(B_WE) + so * 8, (n >> 2) & 1);
                        mbar_expect(BAR(B_WF) + so * 8, 16384);
                        tma3d_mc(sb + WR + rank * 8192 + so * 16384, m1, (n + h) * 32, js * 3, BAR(B_WF) + so * 8);
                        if (n >= WP0 && n < WP0 + 10 - NWP) pf_l2(pw + h * dw, 3072);
                    }
                    if (n >= WP0) pw += 128 * 3072;
                }
                _Pragma("unroll 1") for (int n = 0; n < 10; n++) {
                    const uint32_t so = n & 3;
                    mbar_wait(BAR(B_WE) + so * 8, ((n >> 2) & 1) ^ 1);
                    mbar_expect(BAR(B_WF) + so * 8, 16384);
                    tma2d_mc(sb + WR + rank * 8192 + so * 16384, m2, js * 192 + 128, n * 64, BAR(B_WF) + so * 8);
                }
                _Pragma("unroll 1") for (int j = 0; j < 9; j++) {
                    const int c = (j * 11) >> 5;
                    const char* src = hh_src(j);
                    mbar_expect(BAR(B_AL + j), 16384);
                    if (j == 3 * c) { mbar_wait(BAR(B_HD + c), 0); poll_cnt(hfl + c * 4, tg2); fence_async_glob(); STAMPIF(c != 1, c ? 32 : 38); }
                    mbar_wait(c == 1 ? BAR(B_S0) : BAR(B_HS + j - 3 * c), c == 2);
                    bulk_g2s(sb + (j < 2 ? j + 12 : j < 8 ? j + 6 : 8) * 16384, src, 16384, BAR(B_AL + j));
                }
            }
        } else if (wv) {
            if (hw == 3) {
                const char* gp = SC(mod, (5 * 320 + dq * 80 + lane) * 8);
                auto gaddr = [&](int i) { return gp + i * 192; };
                uint2 gv[3];
                #pragma unroll
                for (int i = 0; i < 3; i++) gv[i] = ldg_rlx64(gaddr(i));
                ll_wait<3>(gv, ep2, gaddr);
                poll_cnt(CNT(C_Z + tile, 6), tg2);
                fence_acq();
                mbar_wait(BAR(B_HD), 0);
                red_if(hfl + lane * 4, 32, l0);
                STAMP(36);
                #pragma unroll
                for (int n = 0; n < 3; n++) sts32(sb + GBT + q * 80 + (rr + 6 * n) * 4, gv[n].x);
                __syncwarp();
                mbar_arrive_if(BAR(B_GB), l0);
                mbar_wait(BAR(B_HD + 1), 0);
                red_if(hfl + lane * 4, 32, lane == 1);
                mbar_wait(BAR(B_HD + 2), 0);
                red_if(hfl + lane * 4, 32, lane == 2);
                STAMP(40);
            } else {
                if (lane < 10) mbar_expect(BAR(B_AL + lane), 16384);
                if (elect()) { pf_map(&M.g2); pf_map(&M.u2); }
                const char *zc = CNT(C_Z + tile, lane & 7), *zp = SC(z, tile * 163840);
                uint32_t rtp = 0, zv = tg2 - 1, al = BAR(B_AL), dst = sb;
                int zr = 0;
                _Pragma("unroll 1") for (int i = 0; i < 19; i++) {
                    if (zr < 5) {
                        const uint32_t fre = BAR(zr == 4 ? B_UD : zr ? B_RD + 3 + (zr > 1) : B_RD);
                        bool go = (__ballot_sync(~0u, (int)(zv - tg2) >= 0) >> zr) & 1;
                        if (2 * zr <= i) {
                            if (!go) {
                                if (!mbar_test(BAR(B_KV + zr), 1)) { mbar_wait(BAR(B_KV + zr), 1); pause(D_PZ); }
                                poll_cnt(CNT(C_Z + tile, zr), tg2);
                            }
                            mbar_wait(fre, 0);
                            go = true;
                        } else go = go && mbar_test(fre, 0);
                        if (go) {
                            if (elect()) {
                                fence_async_glob();
                                bulk_g2s(sb + zr * 32768, zp, 16384, BAR(B_AL + 2 * zr));
                                bulk_g2s(sb + zr * 32768 + 16384, zp + 16384, 16384, BAR(B_AL + 2 * zr + 1));
                            }
                            STAMP(80 + zr);
                            zr++; zp += 32768;
                        }
                    }
                    mbar_wait(al, i >= 10);
                    _Pragma("unroll 1") for (int rt = 0; rt < 2000; rt++) {
                        uint32_t v[4];
                        #pragma unroll
                        for (int k = 0; k < 4; k++) asm volatile("ld.shared.b32 %0, [%1];" : "=r"(v[k]) : "r"(dst + lane * 132 + k * 4096) : "memory");
                        if (!__any_sync(~0u, ((v[0] ^ ep2) | (v[1] ^ ep2) | (v[2] ^ ep2) | (v[3] ^ ep2)) & 1)) break;
                        int i_ = i; asm volatile("" : "+r"(i_));
                        VALIF(true, 87 + (i >= 10), 1);
                        if (elect()) { mbar_expect(BAR(B_RT), 16384); bulk_g2s(dst, i_ < 10 ? SC(z, (tile * 10 + i_) * 16384) : hh_src(i_ - 10), 16384, BAR(B_RT)); }
                        mbar_wait(BAR(B_RT), rtp);
                        rtp ^= 1;
                    }
                    mbar_arrive_if(al - 8 * (B_AL - B_AF), l0);
                    if (zr < 5) zv = ldg_rlx32(zc);
                    al += i == 9 ? -72 : 8; dst += i == 9 ? 49152 : i == 11 || i == 17 ? -81920 : 16384;
                    STAMPIF(i == 0 || i == 10 || i == 16, i == 10 ? 37 : i ? 74 : 42);
                }
            }
        } else if (elect()) {
            pf_map(&M.wn); pf_map(&M.wd); pf_map(&M.out);
            int g = 0, c = 0, m = -3;
            _Pragma("unroll 1") for (int n = 0; n < 12; n++) {
                const uint32_t st = sb + G2B + g * 20480 + rank * 10240, f = BAR(B_G2F + g);
                mbar_wait(BAR(B_G2E + g), n >= 6);
                mbar_expect(f, 20480);
                if (m < 0) tma3d_mc(st, &M.wn, (js * 3 + n) * 64 + rank * 32, dq * 5, f);
                else tma5d_mc(st, &M.wd, ((kh * 4 + m + (m >= dq)) * 3 + (c ^ (c < 2))) * 8 + rank * 4, dq * 5, f);
                g = g == 5 ? 0 : g + 1;
                if (++m == 3) { m = 0; c++; }
            }
        }
    }
}

typedef CUresult (*EncodeFn)(CUtensorMap*, CUtensorMapDataType, cuuint32_t, void*, const cuuint64_t*, const cuuint64_t*, const cuuint32_t*, const cuuint32_t*,
                             CUtensorMapInterleave, CUtensorMapSwizzle, CUtensorMapL2promotion, CUtensorMapFloatOOBfill);
void enc(EncodeFn fn, CUtensorMap* m, const void* ptr, int rank, const cuuint64_t* dims, const cuuint64_t* strides, const cuuint32_t* box, CUtensorMapSwizzle sw) {
    cuuint32_t es[5] = {1, 1, 1, 1, 1};
    fn(m, CU_TENSOR_MAP_DATA_TYPE_BFLOAT16, rank, (void*)ptr, dims, strides, box, es, CU_TENSOR_MAP_INTERLEAVE_NONE, sw,
       CU_TENSOR_MAP_L2_PROMOTION_L2_128B, CU_TENSOR_MAP_FLOAT_OOB_FILL_NONE);
}
}

extern "C" void kernel_launch(void* const* d_in, const int* in_sizes, int n_in, void* d_out, int out_size) {
    void* fnp = nullptr; cudaDriverEntryPointQueryResult st;
    cudaGetDriverEntryPoint("cuTensorMapEncodeTiled", &fnp, cudaEnableDefault, &st);
    EncodeFn fn = (EncodeFn)fnp;
    void* scr;
    cudaGetSymbolAddress(&scr, g_s);
    Maps M; Ptrs P;
    P.k = (const char*)d_in[1]; P.v = (const char*)d_in[2]; P.shift = (const char*)d_in[3]; P.ssm = (const char*)d_in[4]; P.ssmD = (const char*)d_in[5]; P.Wg = (const char*)d_in[7]; P.Wu = (const char*)d_in[8];
    P.Wd = (const char*)d_in[9]; P.c = (const char*)d_in[10]; P.out = (char*)d_out; P.scr = (char*)scr;
    { cuuint64_t d[4] = {640, 2, 256, 4}, s[3] = {1280, 8 * 1280, 2 * 1280}; cuuint32_t b1[4] = {64, 2, 5, 4}, b2[4] = {64, 2, 4, 4};
      enc(fn, &M.k, d_in[1], 4, d, s, b1, CU_TENSOR_MAP_SWIZZLE_128B); enc(fn, &M.v, d_in[2], 4, d, s, b2, CU_TENSOR_MAP_SWIZZLE_128B); }
    { cuuint64_t d[3] = {32, 2048, 20}, s[2] = {1280, 64}; cuuint32_t b1[3] = {32, 16, 4};
      enc(fn, &M.q, d_in[0], 3, d, s, b1, CU_TENSOR_MAP_SWIZZLE_NONE); }
    { cuuint64_t d[3] = {64, 640, 24}, s[2] = {3072, 128}; cuuint32_t b1[3] = {64, 32, 2};
      enc(fn, &M.g1, P.Wg, 3, d, s, b1, CU_TENSOR_MAP_SWIZZLE_128B); enc(fn, &M.u1, P.Wu, 3, d, s, b1, CU_TENSOR_MAP_SWIZZLE_128B); }
    { cuuint64_t d[2] = {1536, 640}, s[1] = {3072}; cuuint32_t b1[2] = {64, 64};
      enc(fn, &M.g2, P.Wg, 2, d, s, b1, CU_TENSOR_MAP_SWIZZLE_128B); enc(fn, &M.u2, P.Wu, 2, d, s, b1, CU_TENSOR_MAP_SWIZZLE_128B); }
    { cuuint64_t d[5] = {32, 2, 192, 4, 20}, s[4] = {1280, 8 * 1280, 2 * 1280, 64}; cuuint32_t b1[5] = {32, 2, 4, 4, 5};
      enc(fn, &M.wd, P.Wd, 5, d, s, b1, CU_TENSOR_MAP_SWIZZLE_64B); }
    { cuuint64_t d[3] = {32, 1536, 20}, s[2] = {1280, 64}; cuuint32_t b1[3] = {32, 32, 5};
      enc(fn, &M.wn, P.Wd, 3, d, s, b1, CU_TENSOR_MAP_SWIZZLE_64B); }
    { cuuint64_t d[2] = {3840, 640}, s[1] = {7680}; cuuint32_t b1[2] = {64, 160};
      enc(fn, &M.wm, d_in[11], 2, d, s, b1, CU_TENSOR_MAP_SWIZZLE_128B); }
    { cuuint64_t d[2] = {640, 2048}, s[1] = {1280}; cuuint32_t b1[2] = {80, 16};
      enc(fn, &M.out, d_out, 2, d, s, b1, CU_TENSOR_MAP_SWIZZLE_NONE); }
    cudaFuncSetAttribute(fused_kernel, cudaFuncAttributeMaxDynamicSharedMemorySize, SMEM_BYTES);
    fused_kernel<<<132, 384, SMEM_BYTES>>>(P, M);
}
```

```cpp
#include <cuda_runtime.h>
#include <cuda_bf16.h>
#include <cuda.h>
#include <stdint.h>
#include <stddef.h>
#include <type_traits>

namespace {

constexpr int D_ = 640;

struct Scratch {
    uint4 kvT[D_ * 256], yT[D_ * 256];
    uint4 z[16 * 10 * 1024];
    uint4 hh[16 * 24 * 1024];
    uint4 st2[2048];
    uint4 abc[320];
    uint2 mod[640];
    uint2 ut[5 * 3072];
    uint32_t cnt[64 * 1024];
};
__device__ __align__(1024) Scratch g_s;
#define SC(f, off) padd(P.scr, (uint32_t)offsetof(Scratch, f) + (off))
constexpr int C_KV = 0  , C_Y = 10  , C_Z = 16  , C_HH = 32  ;

constexpr uint32_t WR = 163840, MISC = 229376, SMEM_BYTES = 232448;
constexpr uint32_t ESLOT = 0x31650;
constexpr uint32_t XP = 4112, XB = 65536 + 18432, ST_SH = XB + 2 * XP;
constexpr uint32_t ST_Q = 131072, ST_Y = ST_Q + 20480, ST_S = ST_Y + 10240  , UST = ST_Q;
__host__ __device__ constexpr uint32_t st_kv(int r) { return r == 2 ? ST_Y : r == 1 || r == 4 ? 65536 + 9216 : 65536; }
__host__ __device__ constexpr uint32_t eslot(int r) { return ((ESLOT >> (4 * r)) & 7) << 15; }
constexpr uint32_t PP = 4352;
constexpr uint32_t BARS = MISC, TAB1 = MISC + 672, TAB2 = TAB1 + 32 * 48, CS_TAB = TAB1  , PRF = -256;
constexpr uint32_t GBT = 0, G2B = 8192, G2A = 131072;
enum { B_H = 0, B_KV = 5, B_Q = 10, B_X = 15  , B_MD = 17  , B_AF = 20, B_AL = 30, B_WF = 40, B_G2F = 44, B_GB = 50, B_RT = 51, B_Y = 52  ,
       B_WE = 54, B_G2E = 58,
       B_UD = 64, B_HD = 65  , B_S0 = 68, B_HS = 69  ,
       B_RD = 72, B_UF = 77, B_TD = 78  , B_T1 = 81, B_YE = 82  , NBARS = 84 };
__host__ __device__ constexpr uint32_t bar_count(int i) {
    return i < B_WE ? 1 : i < B_UD ? 16 : i < B_RD ? 8 : i < B_T1 ? 4 : 2;
}
#define GSTAMPIF(c, i) do {} while (0)
#define STAMPIF(c, i) do {} while (0)
#define STAMP(i) do {} while (0)
#define VALIF(c, i, v) do {} while (0)
#define STAMPI STAMPIF
#define STAMPR(i) do {} while (0)
#define TWAIT(i, stmt) stmt
#define STAMPS(k) do {} while (0)
#define QS 4
__host__ __device__ constexpr int epi_slot(int e) { return e * QS / 4; }
#define ER 7
#define Q2 2
#define G2R 5
#define YH 0
#define WP0 2
#define SEQ0 0x14124310224120ull
#define SEQ1 0x1324441123422140ull
#define NFAST 7
#define EARLYH 0
#define ZE 1
#define MPF 1
#define N_UT 13
#define NST 5
#define TN(i, v) v
#define ORDER hkhhkxhqkxqqkqxqhwwww
#define STR2(x) #x
#define STR(x) STR2(x)
constexpr int NORD = sizeof(STR(ORDER)) - 1;
__host__ __device__ constexpr char ord_kind(int i) { return STR(ORDER)[i]; }
__host__ __device__ constexpr int ord_index(int i) { int n = ord_kind(i) == 'k'; for (int j = 0; j < i; j++) n += ord_kind(j) == ord_kind(i); return n; }
__host__ __device__ constexpr int ord_slot(int i) { int n = 0; for (int j = 0; j < i; j++) n += ord_kind(j) == 'k' ? 2 : ord_kind(j) != 'x'; return n; }
__host__ __device__ constexpr int ord_find(char c, int n) { for (int i = 0; i < NORD; i++) if (ord_kind(i) == c && ord_index(i) == n) return i; return -1; }
__host__ __device__ constexpr int ord_count(char c) { int n = 0; for (int i = 0; i < NORD; i++) n += ord_kind(i) == c; return n; }
__host__ __device__ constexpr uint32_t ord_mask(char c) { uint32_t m = 0; for (int i = 0; i < NORD; i++) m |= (uint32_t)(ord_kind(i) == c) << i; return m; }
constexpr int NWP = ord_count('w');
static_assert(NWP % 2 == 0 && ord_kind(0) == 'h' && ord_count('x') >= 2 && ord_count('k') == 4 && ord_count('q') == 5 && ord_count('h') == 5, "order");
#define TV0 600
#define D_1 TN(0, TV0)
#define TV1 420
#define G_U TN(1, TV1)
#define TV2 420
#define G_ST TN(2, TV2)
#define TV4 1500
#define D_SP TN(4, TV4)
#define TV5 0
#define G_F TN(5, TV5)
#define TV6 8000
#define D_M TN(6, TV6)
#define TV7 700
#define D_PK TN(7, TV7)
#define TV8 600
#define D_PY TN(8, TV8)
#define TV9 300
#define D_PZ TN(9, TV9)
#define TV10 0
#define D_PS TN(10, TV10)
#define TV11 1400
#define D_UT TN(11, TV11)

__device__ __forceinline__ uint32_t smem_u32(const void* p) { return (uint32_t)__cvta_generic_to_shared(p); }
__device__ __forceinline__ void mbar_init(uint32_t bar, uint32_t cnt) { asm volatile("mbarrier.init.shared::cta.b64 [%0], %1;" :: "r"(bar), "r"(cnt) : "memory"); }
__device__ __forceinline__ void mbar_expect(uint32_t bar, uint32_t bytes) { asm volatile("mbarrier.arrive.expect_tx.shared::cta.b64 _, [%0], %1;" :: "r"(bar), "r"(bytes) : "memory"); }
__device__ __forceinline__ void mbar_arrive_if(uint32_t bar, bool p) { asm volatile("{ .reg .pred p; setp.ne.b32 p, %1, 0; @p mbarrier.arrive.shared::cta.b64 _, [%0]; }" :: "r"(bar), "r"((int)p) : "memory"); }
__device__ __forceinline__ void mbar_arrive_remote_if(uint32_t bar, bool p) { asm volatile("{ .reg .pred p; setp.ne.b32 p, %1, 0; @p mbarrier.arrive.shared::cluster.b64 _, [%0]; }" :: "r"(bar), "r"((int)p) : "memory"); }
#define WAIT_LOOP(op) "{\n .reg .pred p, q; .reg .u32 c; mov.u32 c, 0;\n LAB_WAIT:\n " op " p, [%0], %1;\n @p bra LAB_DONE;\n add.u32 c, c, 1; setp.lt.u32 q, c, 16384;\n @q bra LAB_WAIT;\n LAB_DONE:\n }"
__device__ __forceinline__ void mbar_wait(uint32_t bar, uint32_t parity) { asm volatile(WAIT_LOOP("mbarrier.try_wait.parity.shared::cta.b64") :: "r"(bar), "r"(parity) : "memory"); }
__device__ __forceinline__ bool mbar_test(uint32_t bar, uint32_t parity) {
    uint32_t ok; asm volatile("{ .reg .pred p; mbarrier.test_wait.parity.shared::cta.b64 p, [%1], %2; selp.u32 %0, 1, 0, p; }" : "=r"(ok) : "r"(bar), "r"(parity) : "memory"); return ok;
}
__device__ __forceinline__ uint32_t clock32() { uint32_t t; asm volatile("mov.u32 %0, %%clock;" : "=r"(t) :: "memory"); return t; }
__device__ __forceinline__ void wait_clock(uint32_t t0, uint32_t d) {
    asm volatile("{\n .reg .pred p; .reg .u32 t;\n LAB_CLK:\n mov.u32 t, %%clock; sub.u32 t, t, %0; setp.lt.u32 p, t, %1;\n @p bra LAB_CLK;\n }" :: "r"(t0), "r"(d) : "memory");
}
__device__ __forceinline__ bool elect() { uint32_t p; asm volatile("{ .reg .pred p; elect.sync _|p, 0xffffffff; selp.u32 %0, 1, 0, p; }" : "=r"(p)); return p; }
__device__ __forceinline__ void pf_map(const CUtensorMap* m) { asm volatile("prefetch.tensormap [%0];" :: "l"(m) : "memory"); }
__device__ __forceinline__ void bar_sync(int id, int n) { asm volatile("bar.sync %0, %1;" :: "r"(id), "r"(n) : "memory"); }
__device__ __forceinline__ bool bar_or(int id, int n, bool c) {
    uint32_t r; asm volatile("{ .reg .pred p, q; setp.ne.b32 p, %3, 0; bar.red.or.pred q, %1, %2, p; selp.u32 %0, 1, 0, q; }" : "=r"(r) : "r"(id), "r"(n), "r"((int)c) : "memory"); return r;
}
__device__ __forceinline__ void wait_until(uint32_t t1) {
    asm volatile("{\n .reg .pred p; .reg .s32 t;\n LAB_CLK:\n mov.u32 t, %%clock; sub.s32 t, t, %0; setp.lt.s32 p, t, 0;\n @p bra LAB_CLK;\n }" :: "r"(t1) : "memory");
}
__device__ __forceinline__ void pause(uint32_t d) { wait_clock(clock32(), d); }
__device__ __forceinline__ void bar_arrive(int id, int n) { asm volatile("bar.arrive %0, %1;" :: "r"(id), "r"(n) : "memory"); }
__device__ __forceinline__ void fence_async_smem() { asm volatile("fence.proxy.async.shared::cta;" ::: "memory"); }
__device__ __forceinline__ void fence_async_glob() { asm volatile("fence.proxy.async.global;" ::: "memory"); }
__device__ __forceinline__ void fence_acq() { asm volatile("fence.acquire.gpu;" ::: "memory"); }
__device__ __forceinline__ void bulk_g2s(uint32_t dst, const void* src, uint32_t bytes, uint32_t bar) {
    asm volatile("cp.async.bulk.shared::cluster.global.mbarrier::complete_tx::bytes [%0], [%1], %2, [%3];" :: "r"(dst), "l"(src), "r"(bytes), "r"(bar) : "memory");
}
__device__ __forceinline__ void pf_l2(const void* src, uint32_t bytes) { asm volatile("cp.async.bulk.prefetch.L2.global [%0], %1;" :: "l"(src), "r"(bytes) : "memory"); }
__device__ __forceinline__ void tma2d(uint32_t dst, const CUtensorMap* m, int c0, int c1, uint32_t bar) {
    asm volatile("cp.async.bulk.tensor.2d.shared::cluster.global.mbarrier::complete_tx::bytes [%0], [%1, {%3, %4}], [%2];" :: "r"(dst), "l"(m), "r"(bar), "r"(c0), "r"(c1) : "memory");
}
__device__ __forceinline__ void tma3d(uint32_t dst, const CUtensorMap* m, int c1, int c2, uint32_t bar) {
    asm volatile("cp.async.bulk.tensor.3d.shared::cluster.global.mbarrier::complete_tx::bytes [%0], [%1, {%5, %3, %4}], [%2];" :: "r"(dst), "l"(m), "r"(bar), "r"(c1), "r"(c2), "r"(0) : "memory");
}
__device__ __forceinline__ void tma4d(uint32_t dst, const CUtensorMap* m, int c0, int c2, uint32_t bar) {
    asm volatile("cp.async.bulk.tensor.4d.shared::cluster.global.mbarrier::complete_tx::bytes [%0], [%1, {%3, %5, %4, %5}], [%2];" :: "r"(dst), "l"(m), "r"(bar), "r"(c0), "r"(c2), "r"(0) : "memory");
}
__device__ __forceinline__ void tma5d(uint32_t dst, const CUtensorMap* m, int c0, int c4, uint32_t bar) {
    asm volatile("cp.async.bulk.tensor.5d.shared::cluster.global.mbarrier::complete_tx::bytes [%0], [%1, {%3, %5, %5, %5, %4}], [%2];" :: "r"(dst), "l"(m), "r"(bar), "r"(c0), "r"(c4), "r"(0) : "memory");
}
__device__ __forceinline__ void tma5d_mc(uint32_t dst, const CUtensorMap* m, int c2, int c4, uint32_t bar) {
    asm volatile("cp.async.bulk.tensor.5d.shared::cluster.global.mbarrier::complete_tx::bytes.multicast::cluster [%0], [%1, {%5, %5, %3, %5, %4}], [%2], %6;"
                 :: "r"(dst), "l"(m), "r"(bar), "r"(c2), "r"(c4), "r"(0), "h"((uint16_t)3) : "memory");
}
__device__ __forceinline__ void tma3d_mc(uint32_t dst, const CUtensorMap* m, int c1, int c2, uint32_t bar) {
    asm volatile("cp.async.bulk.tensor.3d.shared::cluster.global.mbarrier::complete_tx::bytes.multicast::cluster [%0], [%1, {%5, %3, %4}], [%2], %6;"
                 :: "r"(dst), "l"(m), "r"(bar), "r"(c1), "r"(c2), "r"(0), "h"((uint16_t)3) : "memory");
}
__device__ __forceinline__ void tma2d_mc(uint32_t dst, const CUtensorMap* m, int c0, int c1, uint32_t bar) {
    asm volatile("cp.async.bulk.tensor.2d.shared::cluster.global.mbarrier::complete_tx::bytes.multicast::cluster [%0], [%1, {%3, %4}], [%2], %5;"
                 :: "r"(dst), "l"(m), "r"(bar), "r"(c0), "r"(c1), "h"((uint16_t)3) : "memory");
}
__device__ __forceinline__ void tma2d_red(const CUtensorMap* m, uint32_t src, int c0, int c1) {
    asm volatile("cp.reduce.async.bulk.tensor.2d.global.shared::cta.add.bulk_group [%0, {%2, %3}], [%1];" :: "l"(m), "r"(src), "r"(c0), "r"(c1) : "memory");
}
__device__ __forceinline__ void pf_tma3d(const CUtensorMap* m, int c0, int c1, int c2) { asm volatile("cp.async.bulk.prefetch.tensor.3d.L2.global [%0, {%1, %2, %3}];" :: "l"(m), "r"(c0), "r"(c1), "r"(c2) : "memory"); }
__device__ __forceinline__ void red_if(const void* c, uint32_t inc, bool p) { asm volatile("{ .reg .pred p; setp.ne.b32 p, %2, 0; @p red.relaxed.gpu.global.add.u32 [%0], %1; }" :: "l"(c), "r"(inc), "r"((int)p) : "memory"); }
__device__ __forceinline__ uint32_t ldg_rlx32(const void* p) { uint32_t v; asm volatile("ld.relaxed.gpu.global.u32 %0, [%1];" : "=r"(v) : "l"(p) : "memory"); return v; }
__device__ __forceinline__ uint32_t ldg_late(const char* p, int lane) { return ldg_rlx32(p + (lane & 1) * 4); }
__device__ __forceinline__ bool reached(uint32_t v, uint32_t target) { return __ballot_sync(~0u, (int)(v - target) >= 0) & 1; }
__device__ __forceinline__ uint2 ldg_rlx64(const void* p) { uint2 v; asm volatile("{ .reg .b64 x; ld.relaxed.gpu.global.b64 x, [%2]; mov.b64 {%0, %1}, x; }" : "=r"(v.x), "=r"(v.y) : "l"(p) : "memory"); return v; }
__device__ __forceinline__ void ldg_rlx128_if(uint4& v, const void* p, bool c) {
    asm volatile("{ .reg .b128 t; .reg .b64 x, y; .reg .pred p; setp.ne.b32 p, %5, 0; mov.b64 x, {%0, %1}; mov.b64 y, {%2, %3}; mov.b128 t, {x, y};\n"
                 " @p ld.relaxed.gpu.global.b128 t, [%4]; mov.b128 {x, y}, t; mov.b64 {%0, %1}, x; mov.b64 {%2, %3}, y; }"
                 : "+r"(v.x), "+r"(v.y), "+r"(v.z), "+r"(v.w) : "l"(p), "r"((int)c) : "memory");
}
__device__ __forceinline__ uint4 ldg_rlx2x64(const void* p) { uint4 v; asm volatile("{ .reg .b64 x, y; ld.relaxed.gpu.global.v2.b64 {x, y}, [%4]; mov.b64 {%0, %1}, x; mov.b64 {%2, %3}, y; }" : "=r"(v.x), "=r"(v.y), "=r"(v.z), "=r"(v.w) : "l"(p) : "memory"); return v; }
__device__ __forceinline__ void stg_rlx128(void* p, uint32_t x, uint32_t y, uint32_t z, uint32_t w) {
    asm volatile("{ .reg .b128 t; .reg .b64 a, b; mov.b64 a, {%1, %2}; mov.b64 b, {%3, %4}; mov.b128 t, {a, b}; st.relaxed.gpu.global.b128 [%0], t; }" :: "l"(p), "r"(x), "r"(y), "r"(z), "r"(w) : "memory");
}
__device__ __forceinline__ void stg_rlx128_if(void* p, const uint32_t* v, bool c) {
    asm volatile("{ .reg .pred p; .reg .b128 t; .reg .b64 a, b; setp.ne.b32 p, %5, 0; mov.b64 a, {%1, %2}; mov.b64 b, {%3, %4}; mov.b128 t, {a, b}; @p st.relaxed.gpu.global.b128 [%0], t; }" :: "l"(p), "r"(v[0]), "r"(v[1]), "r"(v[2]), "r"(v[3]), "r"((int)c) : "memory");
}
__device__ __forceinline__ void stg128(void* p, uint32_t x, uint32_t y, uint32_t z, uint32_t w) { asm volatile("st.global.v4.b32 [%0], {%1,%2,%3,%4};" :: "l"(p), "r"(x), "r"(y), "r"(z), "r"(w) : "memory"); }
template<int W> __device__ __forceinline__ void stg_tag(void* p, const uint32_t* o, uint32_t tm, uint32_t par) {
    const uint32_t t = (o[W] & ~tm) | (par & tm);
    asm volatile("st.relaxed.gpu.global.v4.b32 [%0], {%1,%2,%3,%4};" :: "l"(p), "r"(W ? o[0] : t), "r"(W ? t : o[1]), "r"(o[2]), "r"(o[3]) : "memory");
}
__device__ __forceinline__ void poll_cnt(const void* c, uint32_t target) {
    asm volatile("{\n .reg .pred p, q; .reg .u32 c, v; mov.u32 c, 0;\n LAB_POLL:\n ld.relaxed.gpu.global.u32 v, [%0];\n sub.u32 v, v, %1; setp.ge.s32 p, v, 0;\n @p bra LAB_PDONE;\n"
                 " add.u32 c, c, 1; setp.lt.u32 q, c, 20000;\n @q bra LAB_POLL;\n LAB_PDONE:\n }" :: "l"(c), "r"(target) : "memory");
}
template<int N, typename F> __device__ __forceinline__ void ll_wait(uint2* v, uint32_t tag, F&& addr) {
    #pragma unroll 1
    for (int it = 0; it < 20000; it++) {
        uint32_t bad = 0;
        #pragma unroll
        for (int i = 0; i < N; i++) bad |= v[i].y ^ tag;
        if (!__any_sync(~0u, bad != 0)) break;
        asm volatile("nanosleep.u32 100;");
        #pragma unroll
        for (int i = 0; i < N; i++) v[i] = ldg_rlx64(addr(i));
    }
}
__device__ __forceinline__ uint4 lds128(uint32_t a) { uint4 v; asm volatile("ld.shared.v4.b32 {%0,%1,%2,%3}, [%4];" : "=r"(v.x), "=r"(v.y), "=r"(v.z), "=r"(v.w) : "r"(a) : "memory"); return v; }
__device__ __forceinline__ uint2 lds64(uint32_t a) { uint2 v; asm volatile("ld.shared.v2.b32 {%0,%1}, [%2];" : "=r"(v.x), "=r"(v.y) : "r"(a) : "memory"); return v; }
__device__ __forceinline__ void sts128(uint32_t a, uint32_t x, uint32_t y, uint32_t z, uint32_t w) { asm volatile("st.shared.v4.b32 [%0], {%1,%2,%3,%4};" :: "r"(a), "r"(x), "r"(y), "r"(z), "r"(w) : "memory"); }
__device__ __forceinline__ void sts32(uint32_t a, uint32_t x) { asm volatile("st.shared.b32 [%0], %1;" :: "r"(a), "r"(x) : "memory"); }
__device__ __forceinline__ void ldsm4t(uint32_t* r, uint32_t a) { asm volatile("ldmatrix.sync.aligned.m8n8.x4.trans.shared.b16 {%0,%1,%2,%3}, [%4];" : "=r"(r[0]), "=r"(r[1]), "=r"(r[2]), "=r"(r[3]) : "r"(a) : "memory"); }
__device__ __forceinline__ void ldsm2t(uint32_t& r0, uint32_t& r1, uint32_t a) { asm volatile("ldmatrix.sync.aligned.m8n8.x2.trans.shared.b16 {%0,%1}, [%2];" : "=r"(r0), "=r"(r1) : "r"(a) : "memory"); }
__device__ __forceinline__ void ldsm4t_if(uint32_t* r, uint32_t a, bool c) { asm volatile("{ .reg .pred p; setp.ne.b32 p, %5, 0; @p ldmatrix.sync.aligned.m8n8.x4.trans.shared.b16 {%0,%1,%2,%3}, [%4]; }" : "+r"(r[0]), "+r"(r[1]), "+r"(r[2]), "+r"(r[3]) : "r"(a), "r"((int)c) : "memory"); }
__device__ __forceinline__ void ldsm2t_if(uint32_t* r, uint32_t a, bool c) { asm volatile("{ .reg .pred p; setp.ne.b32 p, %3, 0; @p ldmatrix.sync.aligned.m8n8.x2.trans.shared.b16 {%0,%1}, [%2]; }" : "+r"(r[0]), "+r"(r[1]) : "r"(a), "r"((int)c) : "memory"); }
__device__ __forceinline__ void lds128_if(uint4& v, uint32_t a, bool c) { asm volatile("{ .reg .pred p; setp.ne.b32 p, %5, 0; @p ld.shared.v4.b32 {%0,%1,%2,%3}, [%4]; }" : "+r"(v.x), "+r"(v.y), "+r"(v.z), "+r"(v.w) : "r"(a), "r"((int)c) : "memory"); }
__device__ __forceinline__ void cp16(uint32_t d, const void* s) { asm volatile("cp.async.cg.shared.global [%0], [%1], 16;" :: "r"(d), "l"(s) : "memory"); }
__device__ __forceinline__ char* padd(const void* p, uint32_t off) { char* r; asm("{ .reg .u64 t; cvt.u64.u32 t, %2; add.u64 %0, %1, t; }" : "=l"(r) : "l"(p), "r"(off)); return r; }
__device__ __forceinline__ uint32_t prmt(uint32_t a, uint32_t b, uint32_t s) { uint32_t r; asm("prmt.b32 %0, %1, %2, %3;" : "=r"(r) : "r"(a), "r"(b), "r"(s)); return r; }
__device__ __forceinline__ uint32_t pack2(float lo, float hi) { uint32_t r; asm("cvt.rn.bf16x2.f32 %0, %1, %2;" : "=r"(r) : "f"(hi), "f"(lo)); return r; }
__device__ __forceinline__ uint32_t pack2relu(float lo, float hi) { uint32_t r; asm("cvt.rn.relu.bf16x2.f32 %0, %1, %2;" : "=r"(r) : "f"(hi), "f"(lo)); return r; }
__device__ __forceinline__ float bflo(uint32_t w) { return __uint_as_float(w << 16); }
__device__ __forceinline__ float bfhi(uint32_t w) { return __uint_as_float(w & 0xffff0000u); }
__device__ __forceinline__ float bfround(float x) { return bflo(pack2(x, x)); }
__device__ __forceinline__ uint32_t hmul2(uint32_t a, uint32_t b) { uint32_t r; asm("mul.rn.bf16x2 %0, %1, %2;" : "=r"(r) : "r"(a), "r"(b)); return r; }
__device__ __forceinline__ uint32_t hadd2(uint32_t a, uint32_t b) { uint32_t r; asm("add.rn.bf16x2 %0, %1, %2;" : "=r"(r) : "r"(a), "r"(b)); return r; }
__device__ __forceinline__ uint32_t hfma2(uint32_t a, uint32_t b, uint32_t c) { uint32_t r; asm("fma.rn.bf16x2 %0, %1, %2, %3;" : "=r"(r) : "r"(a), "r"(b), "r"(c)); return r; }
__device__ __forceinline__ void sched_bar() { asm volatile("pmevent 1;" ::: "memory"); }
template<int H> __device__ __forceinline__ uint32_t hfma2s(uint32_t a, uint32_t w, uint32_t c) {
    uint32_t r;
    if (H) asm("{ .reg .b16 l, h; .reg .b32 t; mov.b32 {l, h}, %2; mov.b32 t, {h, h}; fma.rn.bf16x2 %0, %1, t, %3; }" : "=r"(r) : "r"(a), "r"(w), "r"(c));
    else asm("{ .reg .b16 l, h; .reg .b32 t; mov.b32 {l, h}, %2; mov.b32 t, {l, l}; fma.rn.bf16x2 %0, %1, t, %3; }" : "=r"(r) : "r"(a), "r"(w), "r"(c));
    return r;
}
__device__ __forceinline__ void bump(uint32_t& a, uint32_t d) { asm volatile("add.u32 %0, %0, %1;" : "+r"(a) : "r"(d) : "memory"); }
template<int D> __device__ __forceinline__ void bump(char*& p) { asm volatile("add.s64 %0, %0, %1;" : "+l"(p) : "n"(D) : "memory"); }
__device__ __forceinline__ void wg_fence() { asm volatile("wgmma.fence.sync.aligned;" ::: "memory"); }
__device__ __forceinline__ void wg_commit() { asm volatile("wgmma.commit_group.sync.aligned;" ::: "memory"); }
template<int N> __device__ __forceinline__ void wg_wait() { asm volatile("wgmma.wait_group.sync.aligned %0;" :: "n"(N) : "memory"); }
template<int N> __device__ __forceinline__ void pin(float* d) {
    #pragma unroll
    for (int i = 0; i < N; i++) asm volatile("" : "+f"(d[i]) :: "memory");
}
__device__ __forceinline__ uint32_t dlo(uint32_t addr, uint32_t lbo) { return ((addr & 0x3FFFF) >> 4) | ((lbo >> 4) << 16); }
__host__ __device__ constexpr uint32_t dhi(uint32_t sbo, uint32_t sw) { return (sbo >> 4) | (sw << 30); }

template<int N> struct WG;
template<> struct WG<8> { template<int TA, int TB> static __device__ __forceinline__ void ss(float* d, uint32_t alo, uint32_t ahi, uint32_t blo, uint32_t bhi, int sd) {
  asm volatile("{ .reg .pred p; .reg .b64 da, db; mov.b64 da, {%4,%5}; mov.b64 db, {%6,%7}; setp.ne.b32 p, %8, 0;\n"
    "wgmma.mma_async.sync.aligned.m64n8k16.f32.bf16.bf16 {%0,%1,%2,%3}, da, db, p, 1, 1, %9, %10; }"
    : "+f"(d[0]),"+f"(d[1]),"+f"(d[2]),"+f"(d[3])
    : "r"(alo), "r"(ahi), "r"(blo), "r"(bhi), "r"(sd), "n"(TA), "n"(TB)); }
};
template<> struct WG<16> { template<int TA, int TB> static __device__ __forceinline__ void ss(float* d, uint32_t alo, uint32_t ahi, uint32_t blo, uint32_t bhi, int sd) {
  asm volatile("{ .reg .pred p; .reg .b64 da, db; mov.b64 da, {%8,%9}; mov.b64 db, {%10,%11}; setp.ne.b32 p, %12, 0;\n"
    "wgmma.mma_async.sync.aligned.m64n16k16.f32.bf16.bf16 {%0,%1,%2,%3,%4,%5,%6,%7}, da, db, p, 1, 1, %13, %14; }"
    : "+f"(d[0]),"+f"(d[1]),"+f"(d[2]),"+f"(d[3]),"+f"(d[4]),"+f"(d[5]),"+f"(d[6]),"+f"(d[7])
    : "r"(alo), "r"(ahi), "r"(blo), "r"(bhi), "r"(sd), "n"(TA), "n"(TB)); }
};
template<> struct WG<32> { template<int TA, int TB> static __device__ __forceinline__ void ss(float* d, uint32_t alo, uint32_t ahi, uint32_t blo, uint32_t bhi, int sd) {
  asm volatile("{ .reg .pred p; .reg .b64 da, db; mov.b64 da, {%16,%17}; mov.b64 db, {%18,%19}; setp.ne.b32 p, %20, 0;\n"
    "wgmma.mma_async.sync.aligned.m64n32k16.f32.bf16.bf16 {%0,%1,%2,%3,%4,%5,%6,%7,%8,%9,%10,%11,%12,%13,%14,%15}, da, db, p, 1, 1, %21, %22; }"
    : "+f"(d[0]),"+f"(d[1]),"+f"(d[2]),"+f"(d[3]),"+f"(d[4]),"+f"(d[5]),"+f"(d[6]),"+f"(d[7]),"+f"(d[8]),"+f"(d[9]),"+f"(d[10]),"+f"(d[11]),"+f"(d[12]),"+f"(d[13]),"+f"(d[14]),"+f"(d[15])
    : "r"(alo), "r"(ahi), "r"(blo), "r"(bhi), "r"(sd), "n"(TA), "n"(TB)); }
};
template<> struct WG<48> { template<int TA, int TB> static __device__ __forceinline__ void ss(float* d, uint32_t alo, uint32_t ahi, uint32_t blo, uint32_t bhi, int sd) {
  asm volatile("{ .reg .pred p; .reg .b64 da, db; mov.b64 da, {%24,%25}; mov.b64 db, {%26,%27}; setp.ne.b32 p, %28, 0;\n"
    "wgmma.mma_async.sync.aligned.m64n48k16.f32.bf16.bf16 {%0,%1,%2,%3,%4,%5,%6,%7,%8,%9,%10,%11,%12,%13,%14,%15,%16,%17,%18,%19,%20,%21,%22,%23}, da, db, p, 1, 1, %29, %30; }"
    : "+f"(d[0]),"+f"(d[1]),"+f"(d[2]),"+f"(d[3]),"+f"(d[4]),"+f"(d[5]),"+f"(d[6]),"+f"(d[7]),"+f"(d[8]),"+f"(d[9]),"+f"(d[10]),"+f"(d[11]),"+f"(d[12]),"+f"(d[13]),"+f"(d[14]),"+f"(d[15]),"+f"(d[16]),"+f"(d[17]),"+f"(d[18]),"+f"(d[19]),"+f"(d[20]),"+f"(d[21]),"+f"(d[22]),"+f"(d[23])
    : "r"(alo), "r"(ahi), "r"(blo), "r"(bhi), "r"(sd), "n"(TA), "n"(TB)); }
};
template<> struct WG<64> { template<int TA, int TB> static __device__ __forceinline__ void ss(float* d, uint32_t alo, uint32_t ahi, uint32_t blo, uint32_t bhi, int sd) {
  asm volatile("{ .reg .pred p; .reg .b64 da, db; mov.b64 da, {%32,%33}; mov.b64 db, {%34,%35}; setp.ne.b32 p, %36, 0;\n"
    "wgmma.mma_async.sync.aligned.m64n64k16.f32.bf16.bf16 {%0,%1,%2,%3,%4,%5,%6,%7,%8,%9,%10,%11,%12,%13,%14,%15,%16,%17,%18,%19,%20,%21,%22,%23,%24,%25,%26,%27,%28,%29,%30,%31}, da, db, p, 1, 1, %37, %38; }"
    : "+f"(d[0]),"+f"(d[1]),"+f"(d[2]),"+f"(d[3]),"+f"(d[4]),"+f"(d[5]),"+f"(d[6]),"+f"(d[7]),"+f"(d[8]),"+f"(d[9]),"+f"(d[10]),"+f"(d[11]),"+f"(d[12]),"+f"(d[13]),"+f"(d[14]),"+f"(d[15]),"+f"(d[16]),"+f"(d[17]),"+f"(d[18]),"+f"(d[19]),"+f"(d[20]),"+f"(d[21]),"+f"(d[22]),"+f"(d[23]),"+f"(d[24]),"+f"(d[25]),"+f"(d[26]),"+f"(d[27]),"+f"(d[28]),"+f"(d[29]),"+f"(d[30]),"+f"(d[31])
    : "r"(alo), "r"(ahi), "r"(blo), "r"(bhi), "r"(sd), "n"(TA), "n"(TB)); }
};
template<> struct WG<80> { template<int TA, int TB> static __device__ __forceinline__ void ss(float* d, uint32_t alo, uint32_t ahi, uint32_t blo, uint32_t bhi, int sd) {
  asm volatile("{ .reg .pred p; .reg .b64 da, db; mov.b64 da, {%40,%41}; mov.b64 db, {%42,%43}; setp.ne.b32 p, %44, 0;\n"
    "wgmma.mma_async.sync.aligned.m64n80k16.f32.bf16.bf16 {%0,%1,%2,%3,%4,%5,%6,%7,%8,%9,%10,%11,%12,%13,%14,%15,%16,%17,%18,%19,%20,%21,%22,%23,%24,%25,%26,%27,%28,%29,%30,%31,%32,%33,%34,%35,%36,%37,%38,%39}, da, db, p, 1, 1, %45, %46; }"
    : "+f"(d[0]),"+f"(d[1]),"+f"(d[2]),"+f"(d[3]),"+f"(d[4]),"+f"(d[5]),"+f"(d[6]),"+f"(d[7]),"+f"(d[8]),"+f"(d[9]),"+f"(d[10]),"+f"(d[11]),"+f"(d[12]),"+f"(d[13]),"+f"(d[14]),"+f"(d[15]),"+f"(d[16]),"+f"(d[17]),"+f"(d[18]),"+f"(d[19]),"+f"(d[20]),"+f"(d[21]),"+f"(d[22]),"+f"(d[23]),"+f"(d[24]),"+f"(d[25]),"+f"(d[26]),"+f"(d[27]),"+f"(d[28]),"+f"(d[29]),"+f"(d[30]),"+f"(d[31]),"+f"(d[32]),"+f"(d[33]),"+f"(d[34]),"+f"(d[35]),"+f"(d[36]),"+f"(d[37]),"+f"(d[38]),"+f"(d[39])
    : "r"(alo), "r"(ahi), "r"(blo), "r"(bhi), "r"(sd), "n"(TA), "n"(TB)); }
};
template<> struct WG<96> { template<int TA, int TB> static __device__ __forceinline__ void ss(float* d, uint32_t alo, uint32_t ahi, uint32_t blo, uint32_t bhi, int sd) {
  asm volatile("{ .reg .pred p; .reg .b64 da, db; mov.b64 da, {%48,%49}; mov.b64 db, {%50,%51}; setp.ne.b32 p, %52, 0;\n"
    "wgmma.mma_async.sync.aligned.m64n96k16.f32.bf16.bf16 {%0,%1,%2,%3,%4,%5,%6,%7,%8,%9,%10,%11,%12,%13,%14,%15,%16,%17,%18,%19,%20,%21,%22,%23,%24,%25,%26,%27,%28,%29,%30,%31,%32,%33,%34,%35,%36,%37,%38,%39,%40,%41,%42,%43,%44,%45,%46,%47}, da, db, p, 1, 1, %53, %54; }"
    : "+f"(d[0]),"+f"(d[1]),"+f"(d[2]),"+f"(d[3]),"+f"(d[4]),"+f"(d[5]),"+f"(d[6]),"+f"(d[7]),"+f"(d[8]),"+f"(d[9]),"+f"(d[10]),"+f"(d[11]),"+f"(d[12]),"+f"(d[13]),"+f"(d[14]),"+f"(d[15]),"+f"(d[16]),"+f"(d[17]),"+f"(d[18]),"+f"(d[19]),"+f"(d[20]),"+f"(d[21]),"+f"(d[22]),"+f"(d[23]),"+f"(d[24]),"+f"(d[25]),"+f"(d[26]),"+f"(d[27]),"+f"(d[28]),"+f"(d[29]),"+f"(d[30]),"+f"(d[31]),"+f"(d[32]),"+f"(d[33]),"+f"(d[34]),"+f"(d[35]),"+f"(d[36]),"+f"(d[37]),"+f"(d[38]),"+f"(d[39]),"+f"(d[40]),"+f"(d[41]),"+f"(d[42]),"+f"(d[43]),"+f"(d[44]),"+f"(d[45]),"+f"(d[46]),"+f"(d[47])
    : "r"(alo), "r"(ahi), "r"(blo), "r"(bhi), "r"(sd), "n"(TA), "n"(TB)); }
};
template<> struct WG<112> { template<int TA, int TB> static __device__ __forceinline__ void ss(float* d, uint32_t alo, uint32_t ahi, uint32_t blo, uint32_t bhi, int sd) {
  asm volatile("{ .reg .pred p; .reg .b64 da, db; mov.b64 da, {%56,%57}; mov.b64 db, {%58,%59}; setp.ne.b32 p, %60, 0;\n"
    "wgmma.mma_async.sync.aligned.m64n112k16.f32.bf16.bf16 {%0,%1,%2,%3,%4,%5,%6,%7,%8,%9,%10,%11,%12,%13,%14,%15,%16,%17,%18,%19,%20,%21,%22,%23,%24,%25,%26,%27,%28,%29,%30,%31,%32,%33,%34,%35,%36,%37,%38,%39,%40,%41,%42,%43,%44,%45,%46,%47,%48,%49,%50,%51,%52,%53,%54,%55}, da, db, p, 1, 1, %61, %62; }"
    : "+f"(d[0]),"+f"(d[1]),"+f"(d[2]),"+f"(d[3]),"+f"(d[4]),"+f"(d[5]),"+f"(d[6]),"+f"(d[7]),"+f"(d[8]),"+f"(d[9]),"+f"(d[10]),"+f"(d[11]),"+f"(d[12]),"+f"(d[13]),"+f"(d[14]),"+f"(d[15]),"+f"(d[16]),"+f"(d[17]),"+f"(d[18]),"+f"(d[19]),"+f"(d[20]),"+f"(d[21]),"+f"(d[22]),"+f"(d[23]),"+f"(d[24]),"+f"(d[25]),"+f"(d[26]),"+f"(d[27]),"+f"(d[28]),"+f"(d[29]),"+f"(d[30]),"+f"(d[31]),"+f"(d[32]),"+f"(d[33]),"+f"(d[34]),"+f"(d[35]),"+f"(d[36]),"+f"(d[37]),"+f"(d[38]),"+f"(d[39]),"+f"(d[40]),"+f"(d[41]),"+f"(d[42]),"+f"(d[43]),"+f"(d[44]),"+f"(d[45]),"+f"(d[46]),"+f"(d[47]),"+f"(d[48]),"+f"(d[49]),"+f"(d[50]),"+f"(d[51]),"+f"(d[52]),"+f"(d[53]),"+f"(d[54]),"+f"(d[55])
    : "r"(alo), "r"(ahi), "r"(blo), "r"(bhi), "r"(sd), "n"(TA), "n"(TB)); }
};
template<> struct WG<128> { template<int TA, int TB> static __device__ __forceinline__ void ss(float* d, uint32_t alo, uint32_t ahi, uint32_t blo, uint32_t bhi, int sd) {
  asm volatile("{ .reg .pred p; .reg .b64 da, db; mov.b64 da, {%64,%65}; mov.b64 db, {%66,%67}; setp.ne.b32 p, %68, 0;\n"
    "wgmma.mma_async.sync.aligned.m64n128k16.f32.bf16.bf16 {%0,%1,%2,%3,%4,%5,%6,%7,%8,%9,%10,%11,%12,%13,%14,%15,%16,%17,%18,%19,%20,%21,%22,%23,%24,%25,%26,%27,%28,%29,%30,%31,%32,%33,%34,%35,%36,%37,%38,%39,%40,%41,%42,%43,%44,%45,%46,%47,%48,%49,%50,%51,%52,%53,%54,%55,%56,%57,%58,%59,%60,%61,%62,%63}, da, db, p, 1, 1, %69, %70; }"
    : "+f"(d[0]),"+f"(d[1]),"+f"(d[2]),"+f"(d[3]),"+f"(d[4]),"+f"(d[5]),"+f"(d[6]),"+f"(d[7]),"+f"(d[8]),"+f"(d[9]),"+f"(d[10]),"+f"(d[11]),"+f"(d[12]),"+f"(d[13]),"+f"(d[14]),"+f"(d[15]),"+f"(d[16]),"+f"(d[17]),"+f"(d[18]),"+f"(d[19]),"+f"(d[20]),"+f"(d[21]),"+f"(d[22]),"+f"(d[23]),"+f"(d[24]),"+f"(d[25]),"+f"(d[26]),"+f"(d[27]),"+f"(d[28]),"+f"(d[29]),"+f"(d[30]),"+f"(d[31]),"+f"(d[32]),"+f"(d[33]),"+f"(d[34]),"+f"(d[35]),"+f"(d[36]),"+f"(d[37]),"+f"(d[38]),"+f"(d[39]),"+f"(d[40]),"+f"(d[41]),"+f"(d[42]),"+f"(d[43]),"+f"(d[44]),"+f"(d[45]),"+f"(d[46]),"+f"(d[47]),"+f"(d[48]),"+f"(d[49]),"+f"(d[50]),"+f"(d[51]),"+f"(d[52]),"+f"(d[53]),"+f"(d[54]),"+f"(d[55]),"+f"(d[56]),"+f"(d[57]),"+f"(d[58]),"+f"(d[59]),"+f"(d[60]),"+f"(d[61]),"+f"(d[62]),"+f"(d[63])
    : "r"(alo), "r"(ahi), "r"(blo), "r"(bhi), "r"(sd), "n"(TA), "n"(TB)); }
  template<int TB> static __device__ __forceinline__ void rs(float* d, uint32_t a0, uint32_t a1, uint32_t a2, uint32_t a3, uint32_t blo, uint32_t bhi, int sd) {
  asm volatile("{ .reg .pred p; .reg .b64 db; mov.b64 db, {%68,%69}; setp.ne.b32 p, %71, 0;\n"
    "wgmma.mma_async.sync.aligned.m64n128k16.f32.bf16.bf16 {%0,%1,%2,%3,%4,%5,%6,%7,%8,%9,%10,%11,%12,%13,%14,%15,%16,%17,%18,%19,%20,%21,%22,%23,%24,%25,%26,%27,%28,%29,%30,%31,%32,%33,%34,%35,%36,%37,%38,%39,%40,%41,%42,%43,%44,%45,%46,%47,%48,%49,%50,%51,%52,%53,%54,%55,%56,%57,%58,%59,%60,%61,%62,%63}, {%64,%65,%66,%67}, db, p, 1, 1, %70; }"
    : "+f"(d[0]),"+f"(d[1]),"+f"(d[2]),"+f"(d[3]),"+f"(d[4]),"+f"(d[5]),"+f"(d[6]),"+f"(d[7]),"+f"(d[8]),"+f"(d[9]),"+f"(d[10]),"+f"(d[11]),"+f"(d[12]),"+f"(d[13]),"+f"(d[14]),"+f"(d[15]),"+f"(d[16]),"+f"(d[17]),"+f"(d[18]),"+f"(d[19]),"+f"(d[20]),"+f"(d[21]),"+f"(d[22]),"+f"(d[23]),"+f"(d[24]),"+f"(d[25]),"+f"(d[26]),"+f"(d[27]),"+f"(d[28]),"+f"(d[29]),"+f"(d[30]),"+f"(d[31]),"+f"(d[32]),"+f"(d[33]),"+f"(d[34]),"+f"(d[35]),"+f"(d[36]),"+f"(d[37]),"+f"(d[38]),"+f"(d[39]),"+f"(d[40]),"+f"(d[41]),"+f"(d[42]),"+f"(d[43]),"+f"(d[44]),"+f"(d[45]),"+f"(d[46]),"+f"(d[47]),"+f"(d[48]),"+f"(d[49]),"+f"(d[50]),"+f"(d[51]),"+f"(d[52]),"+f"(d[53]),"+f"(d[54]),"+f"(d[55]),"+f"(d[56]),"+f"(d[57]),"+f"(d[58]),"+f"(d[59]),"+f"(d[60]),"+f"(d[61]),"+f"(d[62]),"+f"(d[63])
    : "r"(a0), "r"(a1), "r"(a2), "r"(a3), "r"(blo), "r"(bhi), "n"(TB), "r"(sd)); }
};
template<> struct WG<144> { template<int TA, int TB> static __device__ __forceinline__ void ss(float* d, uint32_t alo, uint32_t ahi, uint32_t blo, uint32_t bhi, int sd) {
  asm volatile("{ .reg .pred p; .reg .b64 da, db; mov.b64 da, {%72,%73}; mov.b64 db, {%74,%75}; setp.ne.b32 p, %76, 0;\n"
    "wgmma.mma_async.sync.aligned.m64n144k16.f32.bf16.bf16 {%0,%1,%2,%3,%4,%5,%6,%7,%8,%9,%10,%11,%12,%13,%14,%15,%16,%17,%18,%19,%20,%21,%22,%23,%24,%25,%26,%27,%28,%29,%30,%31,%32,%33,%34,%35,%36,%37,%38,%39,%40,%41,%42,%43,%44,%45,%46,%47,%48,%49,%50,%51,%52,%53,%54,%55,%56,%57,%58,%59,%60,%61,%62,%63,%64,%65,%66,%67,%68,%69,%70,%71}, da, db, p, 1, 1, %77, %78; }"
    : "+f"(d[0]),"+f"(d[1]),"+f"(d[2]),"+f"(d[3]),"+f"(d[4]),"+f"(d[5]),"+f"(d[6]),"+f"(d[7]),"+f"(d[8]),"+f"(d[9]),"+f"(d[10]),"+f"(d[11]),"+f"(d[12]),"+f"(d[13]),"+f"(d[14]),"+f"(d[15]),"+f"(d[16]),"+f"(d[17]),"+f"(d[18]),"+f"(d[19]),"+f"(d[20]),"+f"(d[21]),"+f"(d[22]),"+f"(d[23]),"+f"(d[24]),"+f"(d[25]),"+f"(d[26]),"+f"(d[27]),"+f"(d[28]),"+f"(d[29]),"+f"(d[30]),"+f"(d[31]),"+f"(d[32]),"+f"(d[33]),"+f"(d[34]),"+f"(d[35]),"+f"(d[36]),"+f"(d[37]),"+f"(d[38]),"+f"(d[39]),"+f"(d[40]),"+f"(d[41]),"+f"(d[42]),"+f"(d[43]),"+f"(d[44]),"+f"(d[45]),"+f"(d[46]),"+f"(d[47]),"+f"(d[48]),"+f"(d[49]),"+f"(d[50]),"+f"(d[51]),"+f"(d[52]),"+f"(d[53]),"+f"(d[54]),"+f"(d[55]),"+f"(d[56]),"+f"(d[57]),"+f"(d[58]),"+f"(d[59]),"+f"(d[60]),"+f"(d[61]),"+f"(d[62]),"+f"(d[63]),"+f"(d[64]),"+f"(d[65]),"+f"(d[66]),"+f"(d[67]),"+f"(d[68]),"+f"(d[69]),"+f"(d[70]),"+f"(d[71])
    : "r"(alo), "r"(ahi), "r"(blo), "r"(bhi), "r"(sd), "n"(TA), "n"(TB)); }
};
template<> struct WG<160> { template<int TA, int TB> static __device__ __forceinline__ void ss(float* d, uint32_t alo, uint32_t ahi, uint32_t blo, uint32_t bhi, int sd) {
  asm volatile("{ .reg .pred p; .reg .b64 da, db; mov.b64 da, {%80,%81}; mov.b64 db, {%82,%83}; setp.ne.b32 p, %84, 0;\n"
    "wgmma.mma_async.sync.aligned.m64n160k16.f32.bf16.bf16 {%0,%1,%2,%3,%4,%5,%6,%7,%8,%9,%10,%11,%12,%13,%14,%15,%16,%17,%18,%19,%20,%21,%22,%23,%24,%25,%26,%27,%28,%29,%30,%31,%32,%33,%34,%35,%36,%37,%38,%39,%40,%41,%42,%43,%44,%45,%46,%47,%48,%49,%50,%51,%52,%53,%54,%55,%56,%57,%58,%59,%60,%61,%62,%63,%64,%65,%66,%67,%68,%69,%70,%71,%72,%73,%74,%75,%76,%77,%78,%79}, da, db, p, 1, 1, %85, %86; }"
    : "+f"(d[0]),"+f"(d[1]),"+f"(d[2]),"+f"(d[3]),"+f"(d[4]),"+f"(d[5]),"+f"(d[6]),"+f"(d[7]),"+f"(d[8]),"+f"(d[9]),"+f"(d[10]),"+f"(d[11]),"+f"(d[12]),"+f"(d[13]),"+f"(d[14]),"+f"(d[15]),"+f"(d[16]),"+f"(d[17]),"+f"(d[18]),"+f"(d[19]),"+f"(d[20]),"+f"(d[21]),"+f"(d[22]),"+f"(d[23]),"+f"(d[24]),"+f"(d[25]),"+f"(d[26]),"+f"(d[27]),"+f"(d[28]),"+f"(d[29]),"+f"(d[30]),"+f"(d[31]),"+f"(d[32]),"+f"(d[33]),"+f"(d[34]),"+f"(d[35]),"+f"(d[36]),"+f"(d[37]),"+f"(d[38]),"+f"(d[39]),"+f"(d[40]),"+f"(d[41]),"+f"(d[42]),"+f"(d[43]),"+f"(d[44]),"+f"(d[45]),"+f"(d[46]),"+f"(d[47]),"+f"(d[48]),"+f"(d[49]),"+f"(d[50]),"+f"(d[51]),"+f"(d[52]),"+f"(d[53]),"+f"(d[54]),"+f"(d[55]),"+f"(d[56]),"+f"(d[57]),"+f"(d[58]),"+f"(d[59]),"+f"(d[60]),"+f"(d[61]),"+f"(d[62]),"+f"(d[63]),"+f"(d[64]),"+f"(d[65]),"+f"(d[66]),"+f"(d[67]),"+f"(d[68]),"+f"(d[69]),"+f"(d[70]),"+f"(d[71]),"+f"(d[72]),"+f"(d[73]),"+f"(d[74]),"+f"(d[75]),"+f"(d[76]),"+f"(d[77]),"+f"(d[78]),"+f"(d[79])
    : "r"(alo), "r"(ahi), "r"(blo), "r"(bhi), "r"(sd), "n"(TA), "n"(TB)); }
  template<int TB> static __device__ __forceinline__ void rs(float* d, uint32_t a0, uint32_t a1, uint32_t a2, uint32_t a3, uint32_t blo, uint32_t bhi, int sd) {
  asm volatile("{ .reg .pred p; .reg .b64 db; mov.b64 db, {%84,%85}; setp.ne.b32 p, %87, 0;\n"
    "wgmma.mma_async.sync.aligned.m64n160k16.f32.bf16.bf16 {%0,%1,%2,%3,%4,%5,%6,%7,%8,%9,%10,%11,%12,%13,%14,%15,%16,%17,%18,%19,%20,%21,%22,%23,%24,%25,%26,%27,%28,%29,%30,%31,%32,%33,%34,%35,%36,%37,%38,%39,%40,%41,%42,%43,%44,%45,%46,%47,%48,%49,%50,%51,%52,%53,%54,%55,%56,%57,%58,%59,%60,%61,%62,%63,%64,%65,%66,%67,%68,%69,%70,%71,%72,%73,%74,%75,%76,%77,%78,%79}, {%80,%81,%82,%83}, db, p, 1, 1, %86; }"
    : "+f"(d[0]),"+f"(d[1]),"+f"(d[2]),"+f"(d[3]),"+f"(d[4]),"+f"(d[5]),"+f"(d[6]),"+f"(d[7]),"+f"(d[8]),"+f"(d[9]),"+f"(d[10]),"+f"(d[11]),"+f"(d[12]),"+f"(d[13]),"+f"(d[14]),"+f"(d[15]),"+f"(d[16]),"+f"(d[17]),"+f"(d[18]),"+f"(d[19]),"+f"(d[20]),"+f"(d[21]),"+f"(d[22]),"+f"(d[23]),"+f"(d[24]),"+f"(d[25]),"+f"(d[26]),"+f"(d[27]),"+f"(d[28]),"+f"(d[29]),"+f"(d[30]),"+f"(d[31]),"+f"(d[32]),"+f"(d[33]),"+f"(d[34]),"+f"(d[35]),"+f"(d[36]),"+f"(d[37]),"+f"(d[38]),"+f"(d[39]),"+f"(d[40]),"+f"(d[41]),"+f"(d[42]),"+f"(d[43]),"+f"(d[44]),"+f"(d[45]),"+f"(d[46]),"+f"(d[47]),"+f"(d[48]),"+f"(d[49]),"+f"(d[50]),"+f"(d[51]),"+f"(d[52]),"+f"(d[53]),"+f"(d[54]),"+f"(d[55]),"+f"(d[56]),"+f"(d[57]),"+f"(d[58]),"+f"(d[59]),"+f"(d[60]),"+f"(d[61]),"+f"(d[62]),"+f"(d[63]),"+f"(d[64]),"+f"(d[65]),"+f"(d[66]),"+f"(d[67]),"+f"(d[68]),"+f"(d[69]),"+f"(d[70]),"+f"(d[71]),"+f"(d[72]),"+f"(d[73]),"+f"(d[74]),"+f"(d[75]),"+f"(d[76]),"+f"(d[77]),"+f"(d[78]),"+f"(d[79])
    : "r"(a0), "r"(a1), "r"(a2), "r"(a3), "r"(blo), "r"(bhi), "n"(TB), "r"(sd)); }
};
template<> struct WG<176> { template<int TA, int TB> static __device__ __forceinline__ void ss(float* d, uint32_t alo, uint32_t ahi, uint32_t blo, uint32_t bhi, int sd) {
  asm volatile("{ .reg .pred p; .reg .b64 da, db; mov.b64 da, {%88,%89}; mov.b64 db, {%90,%91}; setp.ne.b32 p, %92, 0;\n"
    "wgmma.mma_async.sync.aligned.m64n176k16.f32.bf16.bf16 {%0,%1,%2,%3,%4,%5,%6,%7,%8,%9,%10,%11,%12,%13,%14,%15,%16,%17,%18,%19,%20,%21,%22,%23,%24,%25,%26,%27,%28,%29,%30,%31,%32,%33,%34,%35,%36,%37,%38,%39,%40,%41,%42,%43,%44,%45,%46,%47,%48,%49,%50,%51,%52,%53,%54,%55,%56,%57,%58,%59,%60,%61,%62,%63,%64,%65,%66,%67,%68,%69,%70,%71,%72,%73,%74,%75,%76,%77,%78,%79,%80,%81,%82,%83,%84,%85,%86,%87}, da, db, p, 1, 1, %93, %94; }"
    : "+f"(d[0]),"+f"(d[1]),"+f"(d[2]),"+f"(d[3]),"+f"(d[4]),"+f"(d[5]),"+f"(d[6]),"+f"(d[7]),"+f"(d[8]),"+f"(d[9]),"+f"(d[10]),"+f"(d[11]),"+f"(d[12]),"+f"(d[13]),"+f"(d[14]),"+f"(d[15]),"+f"(d[16]),"+f"(d[17]),"+f"(d[18]),"+f"(d[19]),"+f"(d[20]),"+f"(d[21]),"+f"(d[22]),"+f"(d[23]),"+f"(d[24]),"+f"(d[25]),"+f"(d[26]),"+f"(d[27]),"+f"(d[28]),"+f"(d[29]),"+f"(d[30]),"+f"(d[31]),"+f"(d[32]),"+f"(d[33]),"+f"(d[34]),"+f"(d[35]),"+f"(d[36]),"+f"(d[37]),"+f"(d[38]),"+f"(d[39]),"+f"(d[40]),"+f"(d[41]),"+f"(d[42]),"+f"(d[43]),"+f"(d[44]),"+f"(d[45]),"+f"(d[46]),"+f"(d[47]),"+f"(d[48]),"+f"(d[49]),"+f"(d[50]),"+f"(d[51]),"+f"(d[52]),"+f"(d[53]),"+f"(d[54]),"+f"(d[55]),"+f"(d[56]),"+f"(d[57]),"+f"(d[58]),"+f"(d[59]),"+f"(d[60]),"+f"(d[61]),"+f"(d[62]),"+f"(d[63]),"+f"(d[64]),"+f"(d[65]),"+f"(d[66]),"+f"(d[67]),"+f"(d[68]),"+f"(d[69]),"+f"(d[70]),"+f"(d[71]),"+f"(d[72]),"+f"(d[73]),"+f"(d[74]),"+f"(d[75]),"+f"(d[76]),"+f"(d[77]),"+f"(d[78]),"+f"(d[79]),"+f"(d[80]),"+f"(d[81]),"+f"(d[82]),"+f"(d[83]),"+f"(d[84]),"+f"(d[85]),"+f"(d[86]),"+f"(d[87])
    : "r"(alo), "r"(ahi), "r"(blo), "r"(bhi), "r"(sd), "n"(TA), "n"(TB)); }
};
template<> struct WG<192> { template<int TA, int TB> static __device__ __forceinline__ void ss(float* d, uint32_t alo, uint32_t ahi, uint32_t blo, uint32_t bhi, int sd) {
  asm volatile("{ .reg .pred p; .reg .b64 da, db; mov.b64 da, {%96,%97}; mov.b64 db, {%98,%99}; setp.ne.b32 p, %100, 0;\n"
    "wgmma.mma_async.sync.aligned.m64n192k16.f32.bf16.bf16 {%0,%1,%2,%3,%4,%5,%6,%7,%8,%9,%10,%11,%12,%13,%14,%15,%16,%17,%18,%19,%20,%21,%22,%23,%24,%25,%26,%27,%28,%29,%30,%31,%32,%33,%34,%35,%36,%37,%38,%39,%40,%41,%42,%43,%44,%45,%46,%47,%48,%49,%50,%51,%52,%53,%54,%55,%56,%57,%58,%59,%60,%61,%62,%63,%64,%65,%66,%67,%68,%69,%70,%71,%72,%73,%74,%75,%76,%77,%78,%79,%80,%81,%82,%83,%84,%85,%86,%87,%88,%89,%90,%91,%92,%93,%94,%95}, da, db, p, 1, 1, %101, %102; }"
    : "+f"(d[0]),"+f"(d[1]),"+f"(d[2]),"+f"(d[3]),"+f"(d[4]),"+f"(d[5]),"+f"(d[6]),"+f"(d[7]),"+f"(d[8]),"+f"(d[9]),"+f"(d[10]),"+f"(d[11]),"+f"(d[12]),"+f"(d[13]),"+f"(d[14]),"+f"(d[15]),"+f"(d[16]),"+f"(d[17]),"+f"(d[18]),"+f"(d[19]),"+f"(d[20]),"+f"(d[21]),"+f"(d[22]),"+f"(d[23]),"+f"(d[24]),"+f"(d[25]),"+f"(d[26]),"+f"(d[27]),"+f"(d[28]),"+f"(d[29]),"+f"(d[30]),"+f"(d[31]),"+f"(d[32]),"+f"(d[33]),"+f"(d[34]),"+f"(d[35]),"+f"(d[36]),"+f"(d[37]),"+f"(d[38]),"+f"(d[39]),"+f"(d[40]),"+f"(d[41]),"+f"(d[42]),"+f"(d[43]),"+f"(d[44]),"+f"(d[45]),"+f"(d[46]),"+f"(d[47]),"+f"(d[48]),"+f"(d[49]),"+f"(d[50]),"+f"(d[51]),"+f"(d[52]),"+f"(d[53]),"+f"(d[54]),"+f"(d[55]),"+f"(d[56]),"+f"(d[57]),"+f"(d[58]),"+f"(d[59]),"+f"(d[60]),"+f"(d[61]),"+f"(d[62]),"+f"(d[63]),"+f"(d[64]),"+f"(d[65]),"+f"(d[66]),"+f"(d[67]),"+f"(d[68]),"+f"(d[69]),"+f"(d[70]),"+f"(d[71]),"+f"(d[72]),"+f"(d[73]),"+f"(d[74]),"+f"(d[75]),"+f"(d[76]),"+f"(d[77]),"+f"(d[78]),"+f"(d[79]),"+f"(d[80]),"+f"(d[81]),"+f"(d[82]),"+f"(d[83]),"+f"(d[84]),"+f"(d[85]),"+f"(d[86]),"+f"(d[87]),"+f"(d[88]),"+f"(d[89]),"+f"(d[90]),"+f"(d[91]),"+f"(d[92]),"+f"(d[93]),"+f"(d[94]),"+f"(d[95])
    : "r"(alo), "r"(ahi), "r"(blo), "r"(bhi), "r"(sd), "n"(TA), "n"(TB)); }
};
template<> struct WG<208> { template<int TA, int TB> static __device__ __forceinline__ void ss(float* d, uint32_t alo, uint32_t ahi, uint32_t blo, uint32_t bhi, int sd) {
  asm volatile("{ .reg .pred p; .reg .b64 da, db; mov.b64 da, {%104,%105}; mov.b64 db, {%106,%107}; setp.ne.b32 p, %108, 0;\n"
    "wgmma.mma_async.sync.aligned.m64n208k16.f32.bf16.bf16 {%0,%1,%2,%3,%4,%5,%6,%7,%8,%9,%10,%11,%12,%13,%14,%15,%16,%17,%18,%19,%20,%21,%22,%23,%24,%25,%26,%27,%28,%29,%30,%31,%32,%33,%34,%35,%36,%37,%38,%39,%40,%41,%42,%43,%44,%45,%46,%47,%48,%49,%50,%51,%52,%53,%54,%55,%56,%57,%58,%59,%60,%61,%62,%63,%64,%65,%66,%67,%68,%69,%70,%71,%72,%73,%74,%75,%76,%77,%78,%79,%80,%81,%82,%83,%84,%85,%86,%87,%88,%89,%90,%91,%92,%93,%94,%95,%96,%97,%98,%99,%100,%101,%102,%103}, da, db, p, 1, 1, %109, %110; }"
    : "+f"(d[0]),"+f"(d[1]),"+f"(d[2]),"+f"(d[3]),"+f"(d[4]),"+f"(d[5]),"+f"(d[6]),"+f"(d[7]),"+f"(d[8]),"+f"(d[9]),"+f"(d[10]),"+f"(d[11]),"+f"(d[12]),"+f"(d[13]),"+f"(d[14]),"+f"(d[15]),"+f"(d[16]),"+f"(d[17]),"+f"(d[18]),"+f"(d[19]),"+f"(d[20]),"+f"(d[21]),"+f"(d[22]),"+f"(d[23]),"+f"(d[24]),"+f"(d[25]),"+f"(d[26]),"+f"(d[27]),"+f"(d[28]),"+f"(d[29]),"+f"(d[30]),"+f"(d[31]),"+f"(d[32]),"+f"(d[33]),"+f"(d[34]),"+f"(d[35]),"+f"(d[36]),"+f"(d[37]),"+f"(d[38]),"+f"(d[39]),"+f"(d[40]),"+f"(d[41]),"+f"(d[42]),"+f"(d[43]),"+f"(d[44]),"+f"(d[45]),"+f"(d[46]),"+f"(d[47]),"+f"(d[48]),"+f"(d[49]),"+f"(d[50]),"+f"(d[51]),"+f"(d[52]),"+f"(d[53]),"+f"(d[54]),"+f"(d[55]),"+f"(d[56]),"+f"(d[57]),"+f"(d[58]),"+f"(d[59]),"+f"(d[60]),"+f"(d[61]),"+f"(d[62]),"+f"(d[63]),"+f"(d[64]),"+f"(d[65]),"+f"(d[66]),"+f"(d[67]),"+f"(d[68]),"+f"(d[69]),"+f"(d[70]),"+f"(d[71]),"+f"(d[72]),"+f"(d[73]),"+f"(d[74]),"+f"(d[75]),"+f"(d[76]),"+f"(d[77]),"+f"(d[78]),"+f"(d[79]),"+f"(d[80]),"+f"(d[81]),"+f"(d[82]),"+f"(d[83]),"+f"(d[84]),"+f"(d[85]),"+f"(d[86]),"+f"(d[87]),"+f"(d[88]),"+f"(d[89]),"+f"(d[90]),"+f"(d[91]),"+f"(d[92]),"+f"(d[93]),"+f"(d[94]),"+f"(d[95]),"+f"(d[96]),"+f"(d[97]),"+f"(d[98]),"+f"(d[99]),"+f"(d[100]),"+f"(d[101]),"+f"(d[102]),"+f"(d[103])
    : "r"(alo), "r"(ahi), "r"(blo), "r"(bhi), "r"(sd), "n"(TA), "n"(TB)); }
};
template<> struct WG<224> { template<int TA, int TB> static __device__ __forceinline__ void ss(float* d, uint32_t alo, uint32_t ahi, uint32_t blo, uint32_t bhi, int sd) {
  asm volatile("{ .reg .pred p; .reg .b64 da, db; mov.b64 da, {%112,%113}; mov.b64 db, {%114,%115}; setp.ne.b32 p, %116, 0;\n"
    "wgmma.mma_async.sync.aligned.m64n224k16.f32.bf16.bf16 {%0,%1,%2,%3,%4,%5,%6,%7,%8,%9,%10,%11,%12,%13,%14,%15,%16,%17,%18,%19,%20,%21,%22,%23,%24,%25,%26,%27,%28,%29,%30,%31,%32,%33,%34,%35,%36,%37,%38,%39,%40,%41,%42,%43,%44,%45,%46,%47,%48,%49,%50,%51,%52,%53,%54,%55,%56,%57,%58,%59,%60,%61,%62,%63,%64,%65,%66,%67,%68,%69,%70,%71,%72,%73,%74,%75,%76,%77,%78,%79,%80,%81,%82,%83,%84,%85,%86,%87,%88,%89,%90,%91,%92,%93,%94,%95,%96,%97,%98,%99,%100,%101,%102,%103,%104,%105,%106,%107,%108,%109,%110,%111}, da, db, p, 1, 1, %117, %118; }"
    : "+f"(d[0]),"+f"(d[1]),"+f"(d[2]),"+f"(d[3]),"+f"(d[4]),"+f"(d[5]),"+f"(d[6]),"+f"(d[7]),"+f"(d[8]),"+f"(d[9]),"+f"(d[10]),"+f"(d[11]),"+f"(d[12]),"+f"(d[13]),"+f"(d[14]),"+f"(d[15]),"+f"(d[16]),"+f"(d[17]),"+f"(d[18]),"+f"(d[19]),"+f"(d[20]),"+f"(d[21]),"+f"(d[22]),"+f"(d[23]),"+f"(d[24]),"+f"(d[25]),"+f"(d[26]),"+f"(d[27]),"+f"(d[28]),"+f"(d[29]),"+f"(d[30]),"+f"(d[31]),"+f"(d[32]),"+f"(d[33]),"+f"(d[34]),"+f"(d[35]),"+f"(d[36]),"+f"(d[37]),"+f"(d[38]),"+f"(d[39]),"+f"(d[40]),"+f"(d[41]),"+f"(d[42]),"+f"(d[43]),"+f"(d[44]),"+f"(d[45]),"+f"(d[46]),"+f"(d[47]),"+f"(d[48]),"+f"(d[49]),"+f"(d[50]),"+f"(d[51]),"+f"(d[52]),"+f"(d[53]),"+f"(d[54]),"+f"(d[55]),"+f"(d[56]),"+f"(d[57]),"+f"(d[58]),"+f"(d[59]),"+f"(d[60]),"+f"(d[61]),"+f"(d[62]),"+f"(d[63]),"+f"(d[64]),"+f"(d[65]),"+f"(d[66]),"+f"(d[67]),"+f"(d[68]),"+f"(d[69]),"+f"(d[70]),"+f"(d[71]),"+f"(d[72]),"+f"(d[73]),"+f"(d[74]),"+f"(d[75]),"+f"(d[76]),"+f"(d[77]),"+f"(d[78]),"+f"(d[79]),"+f"(d[80]),"+f"(d[81]),"+f"(d[82]),"+f"(d[83]),"+f"(d[84]),"+f"(d[85]),"+f"(d[86]),"+f"(d[87]),"+f"(d[88]),"+f"(d[89]),"+f"(d[90]),"+f"(d[91]),"+f"(d[92]),"+f"(d[93]),"+f"(d[94]),"+f"(d[95]),"+f"(d[96]),"+f"(d[97]),"+f"(d[98]),"+f"(d[99]),"+f"(d[100]),"+f"(d[101]),"+f"(d[102]),"+f"(d[103]),"+f"(d[104]),"+f"(d[105]),"+f"(d[106]),"+f"(d[107]),"+f"(d[108]),"+f"(d[109]),"+f"(d[110]),"+f"(d[111])
    : "r"(alo), "r"(ahi), "r"(blo), "r"(bhi), "r"(sd), "n"(TA), "n"(TB)); }
};
template<> struct WG<240> { template<int TA, int TB> static __device__ __forceinline__ void ss(float* d, uint32_t alo, uint32_t ahi, uint32_t blo, uint32_t bhi, int sd) {
  asm volatile("{ .reg .pred p; .reg .b64 da, db; mov.b64 da, {%120,%121}; mov.b64 db, {%122,%123}; setp.ne.b32 p, %124, 0;\n"
    "wgmma.mma_async.sync.aligned.m64n240k16.f32.bf16.bf16 {%0,%1,%2,%3,%4,%5,%6,%7,%8,%9,%10,%11,%12,%13,%14,%15,%16,%17,%18,%19,%20,%21,%22,%23,%24,%25,%26,%27,%28,%29,%30,%31,%32,%33,%34,%35,%36,%37,%38,%39,%40,%41,%42,%43,%44,%45,%46,%47,%48,%49,%50,%51,%52,%53,%54,%55,%56,%57,%58,%59,%60,%61,%62,%63,%64,%65,%66,%67,%68,%69,%70,%71,%72,%73,%74,%75,%76,%77,%78,%79,%80,%81,%82,%83,%84,%85,%86,%87,%88,%89,%90,%91,%92,%93,%94,%95,%96,%97,%98,%99,%100,%101,%102,%103,%104,%105,%106,%107,%108,%109,%110,%111,%112,%113,%114,%115,%116,%117,%118,%119}, da, db, p, 1, 1, %125, %126; }"
    : "+f"(d[0]),"+f"(d[1]),"+f"(d[2]),"+f"(d[3]),"+f"(d[4]),"+f"(d[5]),"+f"(d[6]),"+f"(d[7]),"+f"(d[8]),"+f"(d[9]),"+f"(d[10]),"+f"(d[11]),"+f"(d[12]),"+f"(d[13]),"+f"(d[14]),"+f"(d[15]),"+f"(d[16]),"+f"(d[17]),"+f"(d[18]),"+f"(d[19]),"+f"(d[20]),"+f"(d[21]),"+f"(d[22]),"+f"(d[23]),"+f"(d[24]),"+f"(d[25]),"+f"(d[26]),"+f"(d[27]),"+f"(d[28]),"+f"(d[29]),"+f"(d[30]),"+f"(d[31]),"+f"(d[32]),"+f"(d[33]),"+f"(d[34]),"+f"(d[35]),"+f"(d[36]),"+f"(d[37]),"+f"(d[38]),"+f"(d[39]),"+f"(d[40]),"+f"(d[41]),"+f"(d[42]),"+f"(d[43]),"+f"(d[44]),"+f"(d[45]),"+f"(d[46]),"+f"(d[47]),"+f"(d[48]),"+f"(d[49]),"+f"(d[50]),"+f"(d[51]),"+f"(d[52]),"+f"(d[53]),"+f"(d[54]),"+f"(d[55]),"+f"(d[56]),"+f"(d[57]),"+f"(d[58]),"+f"(d[59]),"+f"(d[60]),"+f"(d[61]),"+f"(d[62]),"+f"(d[63]),"+f"(d[64]),"+f"(d[65]),"+f"(d[66]),"+f"(d[67]),"+f"(d[68]),"+f"(d[69]),"+f"(d[70]),"+f"(d[71]),"+f"(d[72]),"+f"(d[73]),"+f"(d[74]),"+f"(d[75]),"+f"(d[76]),"+f"(d[77]),"+f"(d[78]),"+f"(d[79]),"+f"(d[80]),"+f"(d[81]),"+f"(d[82]),"+f"(d[83]),"+f"(d[84]),"+f"(d[85]),"+f"(d[86]),"+f"(d[87]),"+f"(d[88]),"+f"(d[89]),"+f"(d[90]),"+f"(d[91]),"+f"(d[92]),"+f"(d[93]),"+f"(d[94]),"+f"(d[95]),"+f"(d[96]),"+f"(d[97]),"+f"(d[98]),"+f"(d[99]),"+f"(d[100]),"+f"(d[101]),"+f"(d[102]),"+f"(d[103]),"+f"(d[104]),"+f"(d[105]),"+f"(d[106]),"+f"(d[107]),"+f"(d[108]),"+f"(d[109]),"+f"(d[110]),"+f"(d[111]),"+f"(d[112]),"+f"(d[113]),"+f"(d[114]),"+f"(d[115]),"+f"(d[116]),"+f"(d[117]),"+f"(d[118]),"+f"(d[119])
    : "r"(alo), "r"(ahi), "r"(blo), "r"(bhi), "r"(sd), "n"(TA), "n"(TB)); }
};
template<> struct WG<256> { template<int TA, int TB> static __device__ __forceinline__ void ss(float* d, uint32_t alo, uint32_t ahi, uint32_t blo, uint32_t bhi, int sd) {
  asm volatile("{ .reg .pred p; .reg .b64 da, db; mov.b64 da, {%128,%129}; mov.b64 db, {%130,%131}; setp.ne.b32 p, %132, 0;\n"
    "wgmma.mma_async.sync.aligned.m64n256k16.f32.bf16.bf16 {%0,%1,%2,%3,%4,%5,%6,%7,%8,%9,%10,%11,%12,%13,%14,%15,%16,%17,%18,%19,%20,%21,%22,%23,%24,%25,%26,%27,%28,%29,%30,%31,%32,%33,%34,%35,%36,%37,%38,%39,%40,%41,%42,%43,%44,%45,%46,%47,%48,%49,%50,%51,%52,%53,%54,%55,%56,%57,%58,%59,%60,%61,%62,%63,%64,%65,%66,%67,%68,%69,%70,%71,%72,%73,%74,%75,%76,%77,%78,%79,%80,%81,%82,%83,%84,%85,%86,%87,%88,%89,%90,%91,%92,%93,%94,%95,%96,%97,%98,%99,%100,%101,%102,%103,%104,%105,%106,%107,%108,%109,%110,%111,%112,%113,%114,%115,%116,%117,%118,%119,%120,%121,%122,%123,%124,%125,%126,%127}, da, db, p, 1, 1, %133, %134; }"
    : "+f"(d[0]),"+f"(d[1]),"+f"(d[2]),"+f"(d[3]),"+f"(d[4]),"+f"(d[5]),"+f"(d[6]),"+f"(d[7]),"+f"(d[8]),"+f"(d[9]),"+f"(d[10]),"+f"(d[11]),"+f"(d[12]),"+f"(d[13]),"+f"(d[14]),"+f"(d[15]),"+f"(d[16]),"+f"(d[17]),"+f"(d[18]),"+f"(d[19]),"+f"(d[20]),"+f"(d[21]),"+f"(d[22]),"+f"(d[23]),"+f"(d[24]),"+f"(d[25]),"+f"(d[26]),"+f"(d[27]),"+f"(d[28]),"+f"(d[29]),"+f"(d[30]),"+f"(d[31]),"+f"(d[32]),"+f"(d[33]),"+f"(d[34]),"+f"(d[35]),"+f"(d[36]),"+f"(d[37]),"+f"(d[38]),"+f"(d[39]),"+f"(d[40]),"+f"(d[41]),"+f"(d[42]),"+f"(d[43]),"+f"(d[44]),"+f"(d[45]),"+f"(d[46]),"+f"(d[47]),"+f"(d[48]),"+f"(d[49]),"+f"(d[50]),"+f"(d[51]),"+f"(d[52]),"+f"(d[53]),"+f"(d[54]),"+f"(d[55]),"+f"(d[56]),"+f"(d[57]),"+f"(d[58]),"+f"(d[59]),"+f"(d[60]),"+f"(d[61]),"+f"(d[62]),"+f"(d[63]),"+f"(d[64]),"+f"(d[65]),"+f"(d[66]),"+f"(d[67]),"+f"(d[68]),"+f"(d[69]),"+f"(d[70]),"+f"(d[71]),"+f"(d[72]),"+f"(d[73]),"+f"(d[74]),"+f"(d[75]),"+f"(d[76]),"+f"(d[77]),"+f"(d[78]),"+f"(d[79]),"+f"(d[80]),"+f"(d[81]),"+f"(d[82]),"+f"(d[83]),"+f"(d[84]),"+f"(d[85]),"+f"(d[86]),"+f"(d[87]),"+f"(d[88]),"+f"(d[89]),"+f"(d[90]),"+f"(d[91]),"+f"(d[92]),"+f"(d[93]),"+f"(d[94]),"+f"(d[95]),"+f"(d[96]),"+f"(d[97]),"+f"(d[98]),"+f"(d[99]),"+f"(d[100]),"+f"(d[101]),"+f"(d[102]),"+f"(d[103]),"+f"(d[104]),"+f"(d[105]),"+f"(d[106]),"+f"(d[107]),"+f"(d[108]),"+f"(d[109]),"+f"(d[110]),"+f"(d[111]),"+f"(d[112]),"+f"(d[113]),"+f"(d[114]),"+f"(d[115]),"+f"(d[116]),"+f"(d[117]),"+f"(d[118]),"+f"(d[119]),"+f"(d[120]),"+f"(d[121]),"+f"(d[122]),"+f"(d[123]),"+f"(d[124]),"+f"(d[125]),"+f"(d[126]),"+f"(d[127])
    : "r"(alo), "r"(ahi), "r"(blo), "r"(bhi), "r"(sd), "n"(TA), "n"(TB)); }
  template<int TB> static __device__ __forceinline__ void rs(float* d, uint32_t a0, uint32_t a1, uint32_t a2, uint32_t a3, uint32_t blo, uint32_t bhi, int sd) {
  asm volatile("{ .reg .pred p; .reg .b64 db; mov.b64 db, {%132,%133}; setp.ne.b32 p, %135, 0;\n"
    "wgmma.mma_async.sync.aligned.m64n256k16.f32.bf16.bf16 {%0,%1,%2,%3,%4,%5,%6,%7,%8,%9,%10,%11,%12,%13,%14,%15,%16,%17,%18,%19,%20,%21,%22,%23,%24,%25,%26,%27,%28,%29,%30,%31,%32,%33,%34,%35,%36,%37,%38,%39,%40,%41,%42,%43,%44,%45,%46,%47,%48,%49,%50,%51,%52,%53,%54,%55,%56,%57,%58,%59,%60,%61,%62,%63,%64,%65,%66,%67,%68,%69,%70,%71,%72,%73,%74,%75,%76,%77,%78,%79,%80,%81,%82,%83,%84,%85,%86,%87,%88,%89,%90,%91,%92,%93,%94,%95,%96,%97,%98,%99,%100,%101,%102,%103,%104,%105,%106,%107,%108,%109,%110,%111,%112,%113,%114,%115,%116,%117,%118,%119,%120,%121,%122,%123,%124,%125,%126,%127}, {%128,%129,%130,%131}, db, p, 1, 1, %134; }"
    : "+f"(d[0]),"+f"(d[1]),"+f"(d[2]),"+f"(d[3]),"+f"(d[4]),"+f"(d[5]),"+f"(d[6]),"+f"(d[7]),"+f"(d[8]),"+f"(d[9]),"+f"(d[10]),"+f"(d[11]),"+f"(d[12]),"+f"(d[13]),"+f"(d[14]),"+f"(d[15]),"+f"(d[16]),"+f"(d[17]),"+f"(d[18]),"+f"(d[19]),"+f"(d[20]),"+f"(d[21]),"+f"(d[22]),"+f"(d[23]),"+f"(d[24]),"+f"(d[25]),"+f"(d[26]),"+f"(d[27]),"+f"(d[28]),"+f"(d[29]),"+f"(d[30]),"+f"(d[31]),"+f"(d[32]),"+f"(d[33]),"+f"(d[34]),"+f"(d[35]),"+f"(d[36]),"+f"(d[37]),"+f"(d[38]),"+f"(d[39]),"+f"(d[40]),"+f"(d[41]),"+f"(d[42]),"+f"(d[43]),"+f"(d[44]),"+f"(d[45]),"+f"(d[46]),"+f"(d[47]),"+f"(d[48]),"+f"(d[49]),"+f"(d[50]),"+f"(d[51]),"+f"(d[52]),"+f"(d[53]),"+f"(d[54]),"+f"(d[55]),"+f"(d[56]),"+f"(d[57]),"+f"(d[58]),"+f"(d[59]),"+f"(d[60]),"+f"(d[61]),"+f"(d[62]),"+f"(d[63]),"+f"(d[64]),"+f"(d[65]),"+f"(d[66]),"+f"(d[67]),"+f"(d[68]),"+f"(d[69]),"+f"(d[70]),"+f"(d[71]),"+f"(d[72]),"+f"(d[73]),"+f"(d[74]),"+f"(d[75]),"+f"(d[76]),"+f"(d[77]),"+f"(d[78]),"+f"(d[79]),"+f"(d[80]),"+f"(d[81]),"+f"(d[82]),"+f"(d[83]),"+f"(d[84]),"+f"(d[85]),"+f"(d[86]),"+f"(d[87]),"+f"(d[88]),"+f"(d[89]),"+f"(d[90]),"+f"(d[91]),"+f"(d[92]),"+f"(d[93]),"+f"(d[94]),"+f"(d[95]),"+f"(d[96]),"+f"(d[97]),"+f"(d[98]),"+f"(d[99]),"+f"(d[100]),"+f"(d[101]),"+f"(d[102]),"+f"(d[103]),"+f"(d[104]),"+f"(d[105]),"+f"(d[106]),"+f"(d[107]),"+f"(d[108]),"+f"(d[109]),"+f"(d[110]),"+f"(d[111]),"+f"(d[112]),"+f"(d[113]),"+f"(d[114]),"+f"(d[115]),"+f"(d[116]),"+f"(d[117]),"+f"(d[118]),"+f"(d[119]),"+f"(d[120]),"+f"(d[121]),"+f"(d[122]),"+f"(d[123]),"+f"(d[124]),"+f"(d[125]),"+f"(d[126]),"+f"(d[127])
    : "r"(a0), "r"(a1), "r"(a2), "r"(a3), "r"(blo), "r"(bhi), "n"(TB), "r"(sd)); }
};

template<int T> struct Conv {
    static __device__ __forceinline__ void run(float* acc, uint32_t da, uint32_t db) {
        WG<256 - 16 * T>::template ss<0, 0>(acc, da + (T >> 2) * 512 + (T & 3) * 2, dhi(1024, 1), db + T * 16, dhi(128, 0), T != 0);
        Conv<T + 1>::run(acc, da, db);
    }
};
template<> struct Conv<16> { static __device__ __forceinline__ void run(float*, uint32_t, uint32_t) {} };

template<int Q> __device__ __forceinline__ void ffn_epi(const float* g, const float* u, uint32_t* hq, char* dst, uint32_t tm, uint32_t par) {
    constexpr int U = Q >> 2, i = 4 * Q;
    uint32_t* o = hq + 8 * U;
    o[Q & 3] = hmul2(pack2relu(g[i], g[i + 1]), pack2(u[i], u[i + 1]));
    o[4 + (Q & 3)] = hmul2(pack2relu(g[i + 2], g[i + 3]), pack2(u[i + 2], u[i + 3]));
    asm volatile("" : "+r"(o[Q & 3]), "+r"(o[4 + (Q & 3)]) :: "memory");
    if ((Q & 3) == 0) {
        stg_tag<0>(dst + U * 8192, o, tm, par);
        stg_tag<1>(dst + U * 8192 + 512, o + 4, tm, par);
    }
}
__device__ __forceinline__ uint32_t tagged(float x, uint32_t tag) { return (__float_as_uint(x) & ~7u) | (tag & 7u); }
__device__ __forceinline__ uint32_t split2(float x) { const float h = bfround(x); return pack2(h, x - h); }
__device__ __forceinline__ float rsqrt_(float x) { float r; asm("rsqrt.approx.ftz.f32 %0, %1;" : "=f"(r) : "f"(x)); return r; }
__device__ __forceinline__ void acc_stat(float& s, float& q, uint32_t w) { const float a = bflo(w), c = bfhi(w); s += a; q = fmaf(a, a, q); s += c; q = fmaf(c, c, q); }
template<int I, int N, typename F> __device__ __forceinline__ void static_for(F&& f) {
    if constexpr (I < N) { f(std::integral_constant<int, I>{}); static_for<I + 1, N>(f); }
}

__device__ __forceinline__ int mod_col(int i, int s) {
    const int g = 4 * i + s - 40;
    return i < 10 ? ((s & 1) ? 1280 + 1280 * (i & 1) : 640 * (i & 1)) + (i >> 1) * 128 + (s >> 1) * 64 : (g < 10 ? 1920 : 2560) + g * 64;
}
__device__ __forceinline__ uint32_t silu2(uint32_t w) {
    const float a0 = bflo(w), a1 = bfhi(w);
    return pack2(__fdividef(a0, 1.f + __expf(-a0)), __fdividef(a1, 1.f + __expf(-a1)));
}

struct Maps { CUtensorMap k, v, q, y, g1, u1, g2, u2, wd, wn, wm, wp, out; };
struct Ptrs { const char *k, *v, *shift, *ssm, *ssmD; char *scr, *out; const char *c, *Wg, *Wu, *Wd;
};

__global__ void __cluster_dims__(2, 1, 1) __launch_bounds__(384, 1)
fused_kernel(const __grid_constant__ Ptrs P, const __grid_constant__ Maps M) {
    extern __shared__ __align__(1024) char smraw[];
    const uint32_t clk0 = clock32();
    const uint32_t sb = smem_u32(smraw);
    const int tid = threadIdx.x, b = blockIdx.x;
    #define BAR(i) (sb + BARS + 8 * (i))
    if (tid < 256 && b < 128) {
        const uint32_t rv = tid >> 3, c = (tid ^ rv) & 7, rk = rv + 2 + 2 * (rv >> 3);
        const uint32_t go = ((b >> 1) * 32 + (rv & 6) * 4 + 2 * (rv >> 3) + (rv & 1)) * 1280 + (b & 1) * 128 + c * 16;
        cp16(sb + st_kv(0) + 5120 + tid * 16, padd(P.v, go));
        cp16(sb + st_kv(0) + rk * 128 + (((c ^ rk) & 7) << 4), padd(P.k, go));
        sched_bar();
        if ((rv & 22) == 16)
            asm volatile("cp.async.cg.shared.global [%0], [%1], 16, %2;" :: "r"(sb + st_kv(0) + (rk - 2) * 128 + (((c ^ (rk - 2)) & 7) << 4)), "l"(padd(P.k, b < 2 ? go : go - 10240)), "r"(b < 2 ? 0 : 16) : "memory");
        if (tid < 160) cp16(sb + ST_SH + tid * 16, padd(P.shift, (tid >> 5) * 512 + (b & 1) * 512 + tid * 16));
        asm volatile("cp.async.commit_group;" ::: "memory");
    }
    const int warp = __shfl_sync(~0u, tid >> 5, 0), lane = tid & 31;
    const int rank = b & 1, cl = b >> 1;
    #define FFN_ROLE int cl_ = cl; asm volatile("pmevent 1;" : "+r"(cl_)); const int cu = cl_ - 36, cv = (cu * 37) >> 8, \
        grp = cl_ < 4 ? 0 : cl_ < 36 ? (cl_ - 4) & 7 : 1 + cu - 7 * cv, js = cl_ < 4 ? 4 + cl_ : cl_ < 36 ? (cl_ - 4) >> 3 : 4 + cv, tile = 2 * grp + rank, dq = js & 3
    #define CNT(l, w) SC(cnt, (l) * 4096 + (w) * 4)
    uint32_t epoch = 0;

    if (b >= 128) {
        if (warp == 11) {
            if (elect()) {
                _Pragma("unroll") for (int i = 0; i < 25; i++) mbar_init(BAR(i), i < 10 || i >= 20 ? 1 : 4);
                asm volatile("fence.mbarrier_init.release.cluster;" ::: "memory");
                fence_async_smem();
                pf_map(&M.wm);
            }
            __syncwarp();
            asm volatile("barrier.cluster.arrive.relaxed.aligned;" ::: "memory");
            bar_arrive(0, 384);
        } else {
            epoch = ldg_late(CNT(C_Z, 6), lane);
            if (tid < 320) sts32(sb + 204800 + tid * 4, silu2(__ldg((const uint32_t*)P.c + tid)));
            fence_async_smem();
            __syncwarp();
            asm volatile("barrier.cluster.arrive.relaxed.aligned;\n barrier.cluster.wait.aligned;" ::: "memory");
            bar_sync(0, 384);
            STAMPIF(warp == 0, 7);
        }
        if (warp == 11) {
            if (elect()) {
                wait_clock(clk0, D_SP);
                int s0 = 0, ph0 = 1;
                _Pragma("unroll 1") for (int i = 0; i < 15; i++) {
                    const int col = mod_col(i, b - 128);
                    int s = s0, ph = ph0;
                    _Pragma("unroll 1") for (int j = 0; j < 4; j++) {
                        const int sl = (i & 1) * 5 + s;
                        mbar_wait(BAR(10 + sl), ph);
                        mbar_expect(BAR(sl), 20480);
                        tma2d(sb + sl * 20480, &M.wm, col, j * 160, BAR(sl));
                        if (++s == 5) { s = 0; ph ^= 1; }
                    }
                    if (i & 1) { s0 = s; ph0 = ph; }
                }
            }
        } else if (warp == 9 && !rank) {
            epoch = (__shfl_sync(~0u, epoch, 0) >> 7) + 1;
            _Pragma("unroll 1") for (int r = 0; r < 5; r++) {
                if (lane == 0) mbar_expect(BAR(20 + r), 512);
                mbar_wait(BAR(20 + r), 0);
                uint32_t v[4];
                #pragma unroll
                for (int k = 0; k < 4; k++) asm volatile("ld.shared.b32 %0, [%1];" : "=r"(v[k]) : "r"(sb + 206336 + r * 512 + k * 128 + (lane & 16) * 4 + (lane & 3) * 16 + (lane & 12)) : "memory");
                stg_rlx128(SC(abc, (r * 64 + (b - 128) * 16 + lane) * 16), hmul2(v[2], hadd2(v[1], 0x3f803f80u)), hmul2(v[2], v[0]), hadd2(v[3], 0x3f803f80u), epoch);
                STAMP(1 + r);
            }
        } else if (warp < 8) {
            const int wg = warp >> 2;
            epoch = (__shfl_sync(~0u, epoch, 0) >> 7) + 1;
            int s = 0, ph = 0;
            _Pragma("unroll 1") for (int i = wg; i < 15; i += 2) {
                float ac5[20];
                uint32_t prev = 0;
                _Pragma("unroll 1") for (int j = 0; j < 4; j++) {
                    const int sl = wg * 5 + s;
                    mbar_wait(BAR(sl), ph);
                    wg_fence();
                    const uint32_t da = dlo(sb + sl * 20480, 16), db = dlo(sb + 204800 + j * 320, 16);
                    #pragma unroll
                    for (int ks = 0; ks < 10; ks++) WG<8>::ss<1, 0>(ac5 + 4 * (ks % 5), da + ks * 128, dhi(1024, 1), db + ks * 2, dhi(128, 0), ks >= 5 || j != 0);
                    wg_commit();
                    wg_wait<1>();
                    mbar_arrive_if(prev, lane == 0 && j);
                    prev = BAR(10 + sl);
                    if (++s == 5) { s = 0; ph ^= 1; }
                }
                wg_wait<0>();
                pin<20>(ac5);
                mbar_arrive_if(prev, lane == 0);
                const float acc[3] = {ac5[0] + ac5[4] + ac5[8] + ac5[12] + ac5[16], 0.f, ac5[2] + ac5[6] + ac5[10] + ac5[14] + ac5[18]};
                const uint32_t m0 = pack2(acc[0], __shfl_down_sync(~0u, acc[0], 4)), m1 = pack2(acc[2], __shfl_down_sync(~0u, acc[2], 4));
                if (i < 10) {
                    if ((lane & 7) == 0)
                        asm volatile("{ .reg .u32 a, m; mapa.shared::cluster.u32 a, %0, 0; mapa.shared::cluster.u32 m, %1, 0; \n"
                                     " st.async.shared::cluster.mbarrier::complete_tx::bytes.b32 [a], %2, [m]; st.async.shared::cluster.mbarrier::complete_tx::bytes.b32 [a+16], %3, [m]; }"
                                     :: "r"(sb + 206336 + (i >> 1) * 512 + rank * 256 + warp * 32 + (lane >> 3) * 4), "r"(BAR(20 + (i >> 1))), "r"(m0), "r"(m1) : "memory");
                } else if ((lane & 7) == 0) {
                    char* mp = SC(mod, ((4 * i + b - 168) * 64 + (warp & 3) * 16 + (lane >> 2)) * 4);
                    asm volatile("{ .reg .b64 x; mov.b64 x, {%1, %3}; st.relaxed.gpu.global.b64 [%0], x; mov.b64 x, {%2, %3}; st.relaxed.gpu.global.b64 [%0+32], x; }" :: "l"(mp), "r"(m0), "r"(m1), "r"(epoch) : "memory");
                }
                STAMPIF(warp == 0 && i == 12, 6); STAMPIF(warp == 0 && i == 0, 8);
            }
        }
        return;
    }

    const bool l0 = lane == 0;
    const int q = lane & 3, rr = lane >> 2;

    if (warp < 8) {
        const int wg = warp >> 2, w = warp & 3, t = tid & 127;
        if (t < 5) sts128(wg ? sb + XB + (t & 1) * XP + 4096 : sb + eslot(t), 0, 0, 0, 0);
        bar_sync(0, 384);
        asm volatile("barrier.cluster.arrive.relaxed.aligned;" ::: "memory");
        STAMPIF(warp == 0, 1);
        uint32_t dv = 0;
        if (t < 5) asm volatile("ld.global.nc.u16 %0, [%1];" : "=r"(dv) : "l"(padd(P.ssmD, (b + 128 * t) * 2)));
        FFN_ROLE;
        epoch = ldg_late(CNT(C_Z + tile, 6), lane);
        asm volatile("cp.async.wait_group 0;" ::: "memory");
        bar_sync(2, 256);
        mbar_arrive_if(BAR(B_KV), tid == 0);
        epoch = (__shfl_sync(~0u, epoch, 0) >> 7) + 1;
        asm volatile("barrier.cluster.wait.aligned;" ::: "memory");
        uint32_t g2e;
        asm("mapa.shared::cluster.u32 %0, %1, %2;" : "=r"(g2e) : "r"(BAR(B_G2E)), "r"(rank ^ (lane & 1)));
        const bool l01 = lane < 2;
        const uint32_t wre = g2e - 8 * (B_G2E - B_WE);
        {
            const uint32_t par = epoch & 1, xa = sb + XB + wg * XP;
            const char* gp = SC(kvT, (b + 128 * wg) * 4096 + t * 16);
            if (wg) bar_arrive(1, 256);
            auto krow = [&](int o) { const int tk = 39 - 8 * ((lane & 7) >> 1) - o, ro = (tk & 1) + 2 * (tk >> 3) + 10 * ((tk >> 1) & 3); return sb + ro * 128 + (((ro & 7) ^ (2 * w)) << 4); };
            const int o0 = 2 * (lane >> 3) + (lane & 1);
            const int tv = 31 - 8 * ((lane & 7) >> 1) - o0, rv = (tv & 1) + 2 * (tv >> 3) + 8 * ((tv >> 1) & 3);
            uint32_t aE = krow(o0), aH = krow(8 + (o0 & 3)), aV = sb + 5120 + rv * 128 + (((rv & 7) ^ (2 * w)) << 4);
            uint32_t tdo = (rank * 64 + w * 16 + rr) * 4096 + (252 - 4 * cl + q) * 16;
            asm volatile("" : "+r"(aE), "+r"(aH), "+r"(aV), "+r"(tdo));
            _Pragma("unroll 1") for (unsigned long long steps = wg ? SEQ1 : SEQ0; steps; steps >>= 8) {
                const int r = steps & 7;
                STAMPS(0);
                if (steps & 0x40) {
                    const uint32_t so = st_kv(r);
                    const char *dst = SC(kvT, tdo + r * 524288), *hc = CNT(C_KV + 2 * r + rank, t);
                    mbar_wait(BAR(B_KV + r), 0);
                    STAMPIF(w == 1 && (r & 3) == 0, 35 + r); STAMPS(1);
                    red_if(hc, 2, t == 0 && ((EARLYH >> r) & 1));
                    uint2 sw[2]; uint32_t ke[2][6], vv[2][4], o[2][4];
                    #pragma unroll
                    for (int u = 0; u < 2; u++) {
                        sw[u] = lds64(sb + ST_SH + r * 512 + w * 128 + rr * 8 + u * 64);
                        ldsm4t(ke[u], (aE ^ (u << 4)) + so); ldsm2t(ke[u][4], ke[u][5], (aH ^ (u << 4)) + so); ldsm4t(vv[u], (aV ^ (u << 4)) + so);
                    }
                    sched_bar();
                    #pragma unroll
                    for (int u = 0; u < 2; u++) {
                        uint32_t ko[5];
                        #pragma unroll
                        for (int j = 0; j < 5; j++) ko[j] = prmt(ke[u][j], ke[u][j + 1], 0x5432);
                        #pragma unroll
                        for (int j = 0; j < 4; j++) o[u][j] = hmul2(hfma2s<0>(ke[u][j], sw[u].x, hfma2s<1>(ko[j], sw[u].x, hfma2s<0>(ke[u][j + 1], sw[u].y, hfma2s<1>(ko[j + 1], sw[u].y, 0x80008000u)))), vv[u][j]);
                        o[u][0] = (o[u][0] & ~1u) | par;
                    }
                    asm volatile("{ .reg .pred h; setp.ne.b32 h, %10, 0; pmevent 1;\n @h red.relaxed.gpu.global.add.u32 [%9], 2;\n"
                                 " st.relaxed.gpu.global.v4.b32 [%0], {%1,%2,%3,%4}; st.relaxed.gpu.global.v4.b32 [%0+32768], {%5,%6,%7,%8}; }"
                                 :: "l"(dst), "r"(o[0][0]), "r"(o[0][1]), "r"(o[0][2]), "r"(o[0][3]), "r"(o[1][0]), "r"(o[1][1]), "r"(o[1][2]), "r"(o[1][3]),
                                    "l"(hc), "r"((int)(t == 0 && !((EARLYH >> r) & 1))) : "memory");
                    mbar_arrive_if(BAR(B_TD + r), l0 && r < 3);
                    STAMPIF(w == 1 && (r & 3) == 0, r ? 3 : 45);
                    continue;
                }
                const uint32_t eb = sb + eslot(r);
                if (steps & 0x20) {
                    const int ew = (t >> 1) & 3, et = (ew + (t >> 3)) & 3, eh = (t >> 5) & 1;
                    const uint32_t ha = eb + ((t & 64) + 16 * et + 8 * eh + 2 * ew + (t & 1)) * 16;
                    const uint32_t ea = eb + (t & 64) * 128 + (2 * ew + eh) * 1024 + ((2 * et + (t & 1)) << 4);
                    mbar_wait(BAR(B_H + r), 0);
                    STAMPIF(warp == 1 && r == 0, 2); STAMPS(1);
                    uint4 hv4[4];
                    #pragma unroll
                    for (int i = 0; i < 4; i++) hv4[i] = lds128(ha + (i >> 1) * 2048 + (i & 1) * 16);
                    if (w == 0) { const uint32_t dr = __shfl_sync(~0u, dv, r); if (l0) hv4[1].x = hadd2(hv4[1].x, dr); }
                    bar_sync(5 + wg, 128);
                    #pragma unroll
                    for (int h = 0; h < 2; h++) {
                        const uint32_t* w8 = &hv4[2 * h].x;
                        #pragma unroll
                        for (int row = 0; row < 8; row++) {
                            uint32_t o[4];
                            #pragma unroll
                            for (int i = 0; i < 4; i++) o[i] = (row & 1) ? prmt(w8[(7 - row) / 2 + i], w8[(7 - row) / 2 + i + 1], 0x5432) : w8[(8 - row) / 2 + i];
                            sts128((ea ^ (row << 4)) + row * 128 + h * 16384, o[0], o[1], o[2], o[3]);
                        }
                    }
                    if (!(steps & 0x2000)) fence_async_smem();
                    STAMPIF(w == 0, wg ? 30 : 4);
                    continue;
                }
                float acc[128];
                mbar_wait(BAR(B_X + wg), (r >> 1) & 1); STAMPS(1);
                STAMPIF(w == 0, 10 + r);
                bar_sync(1 + wg, 256);
                GSTAMPIF(w == 0 && r == 0, 7); STAMPS(2);
                _Pragma("unroll 1") for (int rep = 0;; rep++) {
                    wg_fence();
                    Conv<0>::run(acc, dlo(eb, 16), dlo(xa, 16));
                    wg_commit();
                    if (r < 4 && !rep) bar_arrive(2 - wg, 256);
                    uint32_t t0;
                    asm volatile("ld.shared.b32 %0, [%1];" : "=r"(t0) : "r"(xa + w * 512 + (lane >> 4) * 2048 + (lane & 15) * 32 + (lane & 4) * 4) : "memory");
                    wg_wait<0>();
                    pin<128>(acc);
                    STAMPIF(w == 0, 15 + r);
                    if (!bar_or(5 + wg, 128, (t0 ^ par) & 1) || rep) break;
                    VALIF(true, 90, 1);
                    _Pragma("unroll 1") for (int h = 0; h < 2; h++) {
                        uint4 kx = {0, 0, 0, 0};
                        _Pragma("unroll 1") for (int it = 0; it < 20000; it++) {
                            ldg_rlx128_if(kx, gp + h * 2048, true);
                            if (!__any_sync(~0u, (kx.x ^ par) & 1)) break;
                        }
                        sts128(xa + t * 16 + h * 2048, kx.x, kx.y, kx.z, kx.w);
                    }
                    fence_async_smem();
                    bar_sync(5 + wg, 128);
                }
                gp += 2 * 524288;
                mbar_arrive_if(BAR(B_MD + r), t == 0 && r < 3);
                const uint32_t pw = eb + w * PP + lane * 16;
                #pragma unroll
                for (int g = 0; g < 8; g++) {
                    uint32_t o[4];
                    #pragma unroll
                    for (int l = 0; l < 4; l++) { const int i = 4 * g + l;
                        o[l] = i < 31 ? pack2(acc[4 * i] + acc[4 * i + 6], acc[4 * i + 1] + acc[4 * i + 7]) : pack2(acc[4 * i], acc[4 * i + 1]); }
                    asm volatile("stmatrix.sync.aligned.m8n8.x4.trans.shared.b16 [%0], {%1,%2,%3,%4};" :: "r"(pw + g * 512), "r"(o[0]), "r"(o[1]), "r"(o[2]), "r"(o[3]) : "memory");
                    if (g & 1) sched_bar();
                }
                if (lane < 6) sts128(pw + 4096, 0, 0, 0, 0);
                bar_sync(5 + wg, 128);
                if (YH < 0) red_if(CNT(C_Y + r, t), 1, t == 0);
                char* yp = (char*)gp + (offsetof(Scratch, yT) - 2 * 524288);
                #pragma unroll
                for (int h = 0; h < 2; h++) {
                    uint4 p[4];
                    #pragma unroll
                    for (int k = 0; k < 4; k++) p[k] = lds128(eb + (t + 128 * h) * 16 + k * (PP + 32));
                    uint32_t y[4];
                    #pragma unroll
                    for (int j = 0; j < 4; j++) y[j] = hadd2((&p[0].x)[j], hadd2((&p[1].x)[j], hadd2((&p[2].x)[j], (&p[3].x)[j])));
                    stg_rlx128(yp + h * 2048, (y[0] & ~1u) | par, y[1], y[2], y[3]);
                    if (h == YH) red_if(CNT(C_Y + r, t), 1, t == 0);
                }
                __syncwarp();
                mbar_arrive_if(BAR(B_RD + r), l0);
                mbar_arrive_remote_if(wre + 16 * (r - 1) + (lane & 4) * 2, lane < 8 && (r == 1 || r == 2));
                STAMPIF(w == 0, 20 + r);
            }
        }
        float acc1[128];
        uint4 sv[2] = {};
        const char* s2p = SC(st2, (tile * 128 + wg * 64 + w * 16 + rr) * 16);
        auto pass1 = [&](int n0, int n1, auto&& top, auto&& mid) {
            _Pragma("unroll 1") for (int n = n0; n < n1; n++) {
                top();
                const uint32_t da = dlo(sb + wg * 4096, 16) + n * 512, db = dlo(sb + WR, 4096) + (n & 3) * 1024;
                TWAIT((n & 1) ? 91 : 10 + (n >> 1), mbar_wait(BAR(B_AF) + (n >> 1) * 8, 0));
                TWAIT(50 + n, mbar_wait(BAR(B_WF) + (n & 3) * 8, (n >> 2) & 1));
                GSTAMPIF(n == 0 && warp == 0, 8);
                STAMPIF(n == 0 && warp == 4, 9);
                STAMPI(warp == 0 && !(n & 1), 50 + (n >> 1));
                wg_fence();
                WG<256>::ss<0, 1>(acc1, da, dhi(512, 2), db, dhi(1024, 1), n0 ? 1 : n);
                if (ER & 1) {
                    wg_commit();
                    wg_wait<1>();
                    mbar_arrive_remote_if(wre + ((n + 3) & 3) * 8, l01 && n > 0);
                }
                WG<256>::ss<0, 1>(acc1, da + 2, dhi(512, 2), db + 128, dhi(1024, 1), 1);
                wg_commit();
                if (!(ER & 1)) {
                    wg_wait<1>();
                    mbar_arrive_remote_if(wre + ((n + 3) & 3) * 8, l01 && n > 0);
                }
                mid(n);
            }
        };
        pass1(0, N_UT, []() {}, [](int) {});
        {
            float au[8];
            const int un = min(2 * b + wg, 239), cg = (un * 205) >> 10;
            char* up = SC(ut, ((un - 5 * cg) * 3072 + cg * 64 + w * 16 + rr) * 8);
            pass1(N_UT, N_UT + 1, [&]() {
                TWAIT(20, mbar_wait(BAR(B_UF), 0));
                const uint32_t ua = dlo(sb + UST + wg * 16384, 16), ub = dlo(sb + CS_TAB + wg * 512, 32);
                wg_fence();
                #pragma unroll
                for (int ks = 0; ks < 8; ks++) WG<8>::ss<1, 0>(au + 4 * (ks & 1), ua + ks * 128, dhi(1024, 1), ub + ks * 4, dhi(128, 0), ks >= 2);
                wg_commit();
            }, [&](int) {
                pin<8>(au);
                asm volatile("{ .reg .pred p; .reg .b64 x; setp.eq.b32 p, %5, 0; mov.b64 x, {%1, %2}; @p st.relaxed.gpu.global.b64 [%0], x; mov.b64 x, {%3, %4}; @p st.relaxed.gpu.global.b64 [%0+64], x; }"
                             :: "l"(up), "r"(tagged(au[0] + au[4], epoch)), "f"(au[1] + au[5]), "r"(tagged(au[2] + au[6], epoch)), "f"(au[3] + au[7]), "r"(q | (b >= 120)) : "memory");
                mbar_arrive_if(BAR(B_UD), l0);
                STAMPIF(warp == 0, 25);
            });
        }
        pass1(N_UT + 1, 20, []() {}, [&](int n) { ldg_rlx128_if(sv[0], s2p, n == 16); ldg_rlx128_if(sv[1], s2p + 128, n == 16); });
        _Pragma("unroll 1") for (int it = 0; it < 20000 && __any_sync(~0u, sv[0].w != epoch || sv[1].w != epoch); it++) { ldg_rlx128_if(sv[0], s2p, true); ldg_rlx128_if(sv[1], s2p + 128, true); }
        float acc2[64];
        const float rq0 = __uint_as_float(sv[0].z), rq1 = __uint_as_float(sv[1].z);
        {
            uint32_t ax[4];
            const uint32_t zm = q == 0 ? ~0u : q == 1 ? 0xffffu : 0u, sh = q ? 0x5454 : 0x5410, sl = sh + 0x2222;
            uint32_t a0 = prmt(sv[0].x, sv[0].y, sh), a1 = prmt(sv[1].x, sv[1].y, sh), a2 = prmt(sv[0].x, sv[0].y, sl), a3 = prmt(sv[1].x, sv[1].y, sl);
            TWAIT(21, mbar_wait(BAR(B_T1), 0));
            wg_wait<0>();
            mbar_arrive_remote_if(wre + 24, l01);
            asm volatile("setmaxnreg.inc.sync.aligned.u32 232;\n and.b32 %0, %4, %8; and.b32 %1, %5, %8; and.b32 %2, %6, %8; and.b32 %3, %7, %8;"
                         : "=r"(ax[0]), "=r"(ax[1]), "=r"(ax[2]), "=r"(ax[3]) : "r"(a0), "r"(a1), "r"(a2), "r"(a3), "r"(zm) : "memory");
            wg_fence();
            WG<256>::rs<1>(acc1, ax[0], ax[1], ax[2], ax[3], dlo(sb + TAB1, 0), dhi(48, 0), 1);
            WG<128>::rs<1>(acc2, ax[0], ax[1], ax[2], ax[3], dlo(sb + TAB2, 0), dhi(48, 0), 0);
            wg_commit();
        }
        char* hdst = SC(hh, (tile * 24 + js * 3) * 16384 + warp * 1024 + rr * 64 + ((q ^ (rr >> 1)) << 4));
        GSTAMPIF(warp == 0, 26);
        uint32_t hq[48];
        const uint32_t tm = (lane & 7) == (w & 1) * 4;
        auto release2 = [&](int it) {
            mbar_arrive_remote_if(wre + 8 * ((it + 3) & 3), l01 && it < 7);
            mbar_arrive_if(BAR(B_HS - 7) + 8 * it, l0 && it >= 7);
            mbar_arrive_remote_if(g2e + 8 * (it - G2R), l01 && it >= G2R && it < G2R + 6);
        };
        auto pass2 = [&](int it, auto&& epi) {
            TWAIT(70 + it, mbar_wait(BAR(B_WF) + (it & 3) * 8, ((it >> 2) & 1) ^ 1));
            STAMPI(warp == 0, 60 + it);
            const uint32_t da = dlo(sb + wg * 4096, 16) + it * 1024, db = dlo(sb + WR, 8192) + (it & 3) * 1024;
            wg_fence();
            static_for<0, 4>([&](auto KS) {
                WG<128>::ss<0, 1>(acc2, da + (KS.value >> 1) * 512 + (KS.value & 1) * 2, dhi(512, 2), db + KS.value * 128, dhi(1024, 1), 1);
                if constexpr (KS.value == 3) wg_commit();
                if constexpr (KS.value == 0 && (ER & 2)) { wg_commit(); wg_wait<1>(); if (it) release2(it); }
                epi(KS);
            });
            if (!(ER & 2)) { wg_wait<1>(); if (it) release2(it); }
        };
        pass2(0, [](auto) {});
        pin<128>(acc1);
        constexpr int NE = (epi_slot(15) >> 2) + 2;
        static_for<1, NE>([&](auto IT) {
            pass2(IT.value, [&](auto KS) {
                static_for<0, 16>([&](auto E) {
                    if constexpr (epi_slot(E.value) == 4 * IT.value + KS.value - 4) {
                        sched_bar();
                        ffn_epi<15 - E.value>(acc1, acc1 + 64, hq, hdst, tm, epoch);
                        if constexpr ((E.value & 7) == 7) { __syncwarp(); mbar_arrive_if(BAR(B_HD + (E.value >> 3)), l0); }
                        sched_bar();
                    }
                });
            });
        });
        _Pragma("unroll 1") for (int it = NE; it < 10; it++) pass2(it, [](auto) {});
        {
            float acc[80];
            static_for<0, 3>([&](auto IT) {
                constexpr int it = IT.value;
                TWAIT(35 + it, mbar_wait(BAR(B_G2F + it), 0));
                STAMPI(warp == 0 && it == 0, 70);
                const uint32_t db = dlo(sb + G2B + it * 20480, 2048);
                #pragma unroll
                for (int i = 0; i < 16; i++) asm volatile("" : "+r"(hq[16 * it + i]) :: "memory");
                wg_fence();
                static_for<0, 4>([&](auto KS) {
                    constexpr int ks = KS.value, sl = 4 * it + ks;
                    const uint32_t* o = hq + 16 * it + 8 * (ks >> 1) + 2 * (ks & 1);
                    WG<160>::rs<1>(acc, o[0], o[4], o[1], o[5], db + (ks >> 1) * 640 + (ks & 1) * 64, dhi(512, 2), it != 0 || ks != 0);
                    if constexpr (sl == 0 || ks == 3) wg_commit();
                    if constexpr (it > 0 && ks == 0 && (ER & 4)) { wg_commit(); wg_wait<1>(); mbar_arrive_remote_if(g2e + 8 * (it ? it - 1 : 0), l01); }
                    if constexpr (sl == 0) {
                        wg_wait<1>();
                        pin<64>(acc2);
                        mbar_arrive_if(BAR(B_S0), l0);
                        static_for<(G2R > 4 ? 10 - G2R : 6), 6>([&](auto G) { mbar_arrive_remote_if(g2e + 8 * G.value, l01); });
                    }
                    if constexpr (sl < 8 / Q2) {
                        sched_bar();
                        static_for<0, Q2>([&](auto J) { ffn_epi<7 - Q2 * sl - J.value>(acc2, acc2 + 32, hq + 32, hdst + 32768, tm, epoch); });
                        if constexpr (sl == 8 / Q2 - 1) { __syncwarp(); mbar_arrive_if(BAR(B_HD + 2), l0); }
                        sched_bar();
                    }
                    if constexpr (sl == 0) wg_fence();
                });
                if (it && !(ER & 4)) {
                    wg_wait<1>();
                    mbar_arrive_remote_if(g2e + 8 * (it ? it - 1 : 0), l01);
                }
            });
            mbar_wait(BAR(B_GB), 0);
            uint4 gw[5];
            #pragma unroll
            for (int i = 0; i < 5; i++) gw[i] = lds128(sb + GBT + q * 80 + i * 16);
            const uint32_t da = dlo(sb + G2A + wg * 4096, 16), db = dlo(sb + G2B, 2048);
            _Pragma("unroll 1") for (int it = 3; it < 12 - NST; it++) {
                const int g = it >= 6 ? it - 6 : it, ga = it >= 5 ? it - 5 : it + 1;
                TWAIT(35 + it, mbar_wait(BAR(B_G2F + g), it >= 6));
                TWAIT(77 + it, mbar_wait(BAR(B_AF - 3 + it), 1));
                STAMPI(warp == 0 && (it == 3 || it == 6), 70 + (it >> 2) + 1);
                wg_fence();
                #pragma unroll
                for (int ks = 0; ks < 4; ks++) {
                    WG<160>::ss<0, 1>(acc, da + ga * 1024 + (ks >> 1) * 512 + (ks & 1) * 2, dhi(512, 2), db + g * 1280 + (ks >> 1) * 640 + (ks & 1) * 64, dhi(512, 2), 1);
                    if (ks == 3 || (ks == 0 && (ER & 4))) wg_commit();
                    if (ks == ((ER & 4) ? 0 : 3)) {
                        wg_wait<1>();
                        mbar_arrive_remote_if(g2e + 8 * (it - 1), l01 && it < 7);
                        mbar_arrive_if(BAR(B_HS - 4) + 8 * it, l0 && it >= 4 && it < 7);
                    }
                }
            }
            mbar_wait(BAR(B_G2F + 6 - NST), 1);
            mbar_wait(BAR(B_AF + 9 - NST), 1);
            if (wg) TWAIT(47, bar_sync(7, 256));
            STAMPI(warp == 0, 73);
            wg_fence();
            static_for<48 - 4 * NST, 48>([&](auto K) {
                constexpr int it = K.value >> 2, ks = K.value & 3;
                WG<160>::ss<0, 1>(acc, da + (it == 11 ? 0 : it - 5) * 1024 + (ks >> 1) * 512 + (ks & 1) * 2, dhi(512, 2), db + (it - 6) * 1280 + (ks >> 1) * 640 + (ks & 1) * 64, dhi(512, 2), 1);
                if constexpr (it < 11 && ks == 1) TWAIT(36 + it, mbar_wait(BAR(B_G2F + it - 5), 1));
                if constexpr (it < 11 && ks == 2) TWAIT(78 + it, mbar_wait(BAR(B_AF + it - 2), 1));
                if constexpr (K.value == 39) wg_commit();
                if constexpr (K.value == 46) { if (!wg) bar_arrive(7, 256); }
            });
            wg_commit();
            wg_wait<1>();
            bar_sync(5 + wg, 128);
            uint32_t osts[2];
            const uint32_t orow = (lane & 15) * 160 + (lane >> 4) * 16;
            osts[0] = sb + G2A + (1 + w) * 16384 + wg * 4096; osts[1] = osts[0] + 8192;
            wg_wait<0>();
            pin<80>(acc);
            STAMPIF(w == 0, 27 + wg);
            GSTAMPIF(warp == 4, 29);
            #pragma unroll
            for (int hf = 0; hf < 2; hf++) {
                #pragma unroll
                for (int i = 5 * hf; i < 5 * hf + 5; i++) {
                    uint32_t o[4];
                    #pragma unroll
                    for (int j = 0; j < 4; j++) { const int n = 4 * i + j; const float rq = (j & 1) ? rq1 : rq0; o[j] = hmul2(pack2(acc[2 * n] * rq, acc[2 * n + 1] * rq), (&gw[n >> 3].x)[(n >> 1) & 3]); }
                    asm volatile("stmatrix.sync.aligned.m8n8.x4.shared.b16 [%0], {%1,%2,%3,%4};" :: "r"(osts[hf] + orow + (i % 5) * 32), "r"(o[0]), "r"(o[1]), "r"(o[2]), "r"(o[3]) : "memory");
                }
                fence_async_smem();
                __syncwarp();
                if (elect()) { fence_async_glob(); tma2d_red(&M.out, osts[hf], dq * 160 + 80 * hf, 128 * tile + 16 * warp); }
            }
            STAMPIF(warp == 4, 31);
            if (elect()) asm volatile("cp.async.bulk.commit_group;\n cp.async.bulk.wait_group.read 0;" ::: "memory");
            STAMPIF(warp == 4, 33);
            GSTAMPIF(warp == 4, 34);
        }
    } else {
        const int hw = warp & 3, wv = hw & 1;
        if (elect()) {
            if (warp & 2) {
                if (warp & 1) { _Pragma("unroll") for (int i = B_UD; i < NBARS; i++) mbar_init(BAR(i), bar_count(i)); }
                else { _Pragma("unroll") for (int i = B_WF; i < B_UD; i++) mbar_init(BAR(i), bar_count(i)); }
            } else { _Pragma("unroll") for (int i = 0; i < 20; i++) mbar_init(BAR(i) + wv * 160, 1); }
            asm volatile("fence.mbarrier_init.release.cluster;" ::: "memory");
            fence_async_smem();
        }
        __syncwarp();
        asm volatile("barrier.cluster.arrive.relaxed.aligned;" ::: "memory");
        const uint32_t t1 = clk0 + D_1 + ((((b * 37) & 127) * G_ST) >> 7);
        if (hw == 0) {
            bar_arrive(0, 384);
            if (lane < 15 && lane != B_KV) mbar_expect(BAR(lane), lane >= B_KV && lane < B_Q ? 9216 : 4096);
            __syncwarp();
            if (elect()) { wait_until(t1); bulk_g2s(sb + 16, P.ssm + b * 4096, 4096, BAR(B_H)); }
            __syncwarp();
            bar_sync(3, 128);
        } else { bar_sync(0, 384); bar_arrive(3, 128); }
        FFN_ROLE;
        const int kh = js >> 2, ft = tile * 8 + js;
        const int oz = __shfl_sync(~0u, tid >> 9, lane);
        epoch = ldg_rlx32(CNT(C_Z + tile, 6 + oz));
        if (hw == 0) {
            if (elect()) {
                auto x_fetch = [&](int r) {
                    if (!mbar_test(BAR(B_KV + r), 0)) { mbar_wait(BAR(B_KV + r), 0); pause(D_PK); }
                    poll_cnt(CNT(C_KV + 2 * r + (b >> 6), 0), (epoch | 127) + 1);
                    fence_async_glob();
                    if (r >= 2) mbar_wait(BAR(B_MD - 2 + r), 0);
                    mbar_expect(BAR(B_X + (r & 1)), 4096);
                    bulk_g2s(sb + XB + (r & 1) * XP, SC(kvT, (b + 128 * r) * 4096), 4096, BAR(B_X + (r & 1)));
                    STAMPIF(r < 2, 5 + r);
                };
                static_for<1, NORD>([&](auto I) {
                    constexpr char kind = ord_kind(I.value); constexpr int n = ord_index(I.value);
                    if constexpr (kind == 'k' && n >= 3) mbar_wait(BAR(B_TD + n - 3), 0);
                    if constexpr (kind != '_' && kind != 'x') wait_until(t1 + ord_slot(I.value) * G_U - (ord_slot(I.value) < NFAST ? ord_slot(I.value) : NFAST) * G_F);
                    if constexpr (kind == 'k') { tma4d(sb + st_kv(n), &M.k, n * 128 + rank * 64, cl * 4 - 1, BAR(B_KV + n)); tma4d(sb + st_kv(n) + 5120, &M.v, n * 128 + rank * 64, cl * 4, BAR(B_KV + n)); }
                    if constexpr (kind == 'q') tma3d(sb + ST_Q + n * 4096, &M.q, ft * 16, n * 4, BAR(B_Q + n));
                    if constexpr (kind == 'h') bulk_g2s(sb + eslot(n) + 16, P.ssm + (b + 128 * n) * 4096, 4096, BAR(B_H + n));
                    if constexpr (kind == 'w') pf_l2(((n & 1) ? P.Wu : P.Wg) + (b + 128 * (n >> 1)) * 3072, 3072);
                    if constexpr (kind == 'm') { _Pragma("unroll") for (int s = 0; s < 5; s++) if (s != 3) pf_tma3d(&M.wp, n * 128, b * 5, s); }
                    if constexpr (kind == 'x') x_fetch(n);
                });
                _Pragma("unroll 1") for (int r = ord_count('x'); r < 5; r++) x_fetch(r);
            }
        } else if (hw == 2 && elect()) { pf_map(&M.k); pf_map(&M.v); pf_map(&M.q); if (ord_count('m')) pf_map(&M.wp); }
        __syncwarp();
        epoch = (__shfl_sync(~0u, epoch, 0) >> 7) + 1;
        const uint32_t target = epoch << 7, par = epoch & 1;
        const char* pa = lane < 8 ? CNT(C_Y, 0) : SC(abc, (lane & 7) * 128 + 12);
        const uint32_t want = lane < 8 ? target : epoch;
        auto y_poll = [&](int r) {
            if (!mbar_test(BAR(B_RD + r), 0)) { mbar_wait(BAR(B_RD + r), 0); pause(D_PY); }
            _Pragma("unroll 1") for (int it = 0; it < 20000 && __any_sync(~0u, (int)(ldg_rlx32(pa) - want) < 0); it++) {}
        };
        auto y_request = [&](int r) {
            if (elect()) {
                fence_async_glob();
                mbar_expect(BAR(B_Y + (r & 1)), 5120);
                tma5d(sb + ST_Y + (r & 1) * 4096, &M.y, 2032 - 16 * ft, 4 * r, BAR(B_Y + (r & 1)));
                bulk_g2s(sb + ST_Y + 8192 + (r & 1) * 1024, SC(abc, r * 1024), 1024, BAR(B_Y + (r & 1)));
            }
            STAMPIF(r < 2, 48 + r);
            pa += lane < 8 ? 4096 : 1024;
        };
        if (hw == 1) {
            if (elect()) { pf_map(&M.y); pf_map(&M.wp); }
            mbar_wait(BAR(B_TD + 2), 0);
            wait_until(clk0 + D_M);
            _Pragma("unroll 1") for (int r = 0; r < 2; r++) {
                y_poll(r); y_request(r);
                if (MPF && elect()) {
                    _Pragma("unroll 1") for (int s = 0; s < (r ? 5 : 8); s++) pf_tma3d(&M.wp, r ? s * 128 : 384 + (s >> 2) * 128, b * 5, r ? 3 : (s & 3) + ((s & 3) == 3));
                }
            }
        }
        if (hw >= 2) {
            pa += lane < 8 ? 8192 : 2048;
            {
                uint32_t aQ = sb + ST_Q + wv * 2048 + (lane & 15) * 64 + (((lane >> 1) + (lane >> 4)) & 3) * 16;
                float sq[4] = {0.f, 0.f, 0.f, 0.f};
                _Pragma("unroll 1") for (int rq = 0; rq < 5; rq++) {
                    mbar_wait(BAR(B_Q + rq), 0);
                    STAMPIF(wv && rq == 4, 44);
                    uint4 v[4];
                    #pragma unroll
                    for (int u = 0; u < 4; u++) v[u] = lds128((aQ ^ ((u & 1) << 5)) + (u >> 1) * 1024);
                    sched_bar();
                    #pragma unroll
                    for (int j = 0; j < 16; j++) acc_stat(sq[2 * (j & 1)], sq[2 * (j & 1) + 1], (&v[(j & 1) + (j >> 3) * 2].x)[(j >> 1) & 3]);
                    aQ += 4096;
                }
                asm volatile("st.shared.v2.f32 [%0], {%1,%2};" :: "r"(sb + ST_S + (lane & 15) * 48 + wv * 16 + (lane >> 4) * 8), "f"(sq[0] + sq[2]), "f"(sq[1] + sq[3]) : "memory");
            }
            float sa[4] = {0.f, 0.f, 0.f, 0.f};
            uint32_t yl = sb + ST_Y + wv * 1024 + lane * 32 + (lane & 4) * 4, ca = sb + ST_Y + 8192 + wv * 256 + q * 16;
            const uint32_t ym = rr ? 0u : 0x00010001u;
            char* zp = SC(z, tile * 163840 + wv * 8192 + (16 * js + 15 - rr) * 64 + ((q ^ 3 ^ (rr >> 1)) << 4));
            uint32_t xs = sb + ST_Q + wv * 1024 + (15 - rr) * 64 + q * 16;
            const uint32_t tm = (lane & 7) == (~js & 1) * 4;
            const char* zc = CNT(C_Z + tile, lane & 7);
            bar_sync(4, 64);
            STAMPIF(hw == 3, 46);
            uint32_t rs[2], mr[2];
            #pragma unroll
            for (int h = 0; h < 2; h++) {
                float f[2] = {0.f, 0.f};
                #pragma unroll
                for (int i = 0; i < 2; i++) { const uint4 a = lds128(sb + ST_S + (15 - 8 * h - rr) * 48 + i * 16); f[0] += __uint_as_float(a.x) + __uint_as_float(a.z); f[1] += __uint_as_float(a.y) + __uint_as_float(a.w); }
                const float mu = f[0] * (1.f / D_), r_ = rsqrt_(fmaxf(f[1] * (1.f / D_) - mu * mu, 0.f) + 1e-5f);
                rs[h] = pack2(r_, r_); const float m_ = -mu * bflo(rs[h]); mr[h] = pack2(m_, m_);
            }
            const int un = min(2 * b + wv, 239), cg = (un * 205) >> 10, ur = un - 5 * cg;
            char* op = padd(P.out, (ft * 16 + 15 - rr) * 1280 + wv * 64 + q * 16) - 256;
            uint4 x1[4] = {};
            const char *cp_ = SC(abc, (ur * 64 + (lane & 16) + q * 4 + (rr & 3)) * 16 + 8), *sp_ = SC(mod, (ur * 64 + lane) * 8);
            auto caddr = [&](int i) { return i < 2 ? sp_ + i * 256 : cp_ + (i & 1) * 512; };
            uint2 mv[4] = {};
            uint32_t pv = 0;
            bool asked = false;
            _Pragma("unroll 1") for (int r = 0;; r++) {
                STAMPR(0);
                uint4 x[4] = {};
                const bool ask = r >= 2 && r < 5 && wv == 0;
                if (ask) { if (!__any_sync(~0u, (int)(pv - want) < 0)) { y_request(r); asked = true; } else pv = ldg_rlx32(pa); }
                if (r < 5) {
                    #pragma unroll
                    for (int i = 0; i < 4; i++) x[i] = lds128(xs + (i >> 1) * 2048 - (i & 1) * 512);
                    sched_bar();
                } else {
                    mbar_wait(BAR(B_TD), 1);
                    if (elect()) {
                        mbar_expect(BAR(B_UF), 16384);
                        #pragma unroll
                        for (int i = 0; i < 2; i++) tma2d(sb + UST + wv * 16384 + i * 8192, cg >= 24 ? &M.u2 : &M.g2, (cg >= 24 ? cg - 24 : cg) * 64, ur * 128 + i * 64, BAR(B_UF));
                    }
                    ll_wait<4>(mv, epoch, caddr);
                    #pragma unroll
                    for (int i = 0; i < 4; i++) sts32(sb + CS_TAB + wv * 512 + ((i & 1) * 8 + rr) * 32 + q * 4 + (i < 2 ? 16 : 0), mv[i].x);
                    fence_async_smem(); __syncwarp(); mbar_arrive_if(BAR(B_UF), l0);
                    STAMPIF(wv, 41);
                }
                if (r) {
                    #pragma unroll
                    for (int j = 0; j < 16; j++) acc_stat(sa[j & 2], sa[(j & 2) + 1], (&x1[(j >> 1) & 3].x)[(j & 1) + (j >> 3) * 2]);
                    #pragma unroll
                    for (int j = 0; j < 4; j++) asm volatile("" : "+f"(sa[j]) :: "memory");
                    bump<32768>(zp); bump(yl, (r & 1) ? 4096 : -4096); bump(ca, (r & 1) ? 1024 : -1024);
                }
                STAMPR(2);
                uint32_t nx[16];
                #pragma unroll
                for (int j = 0; j < 16; j++) { nx[j] = hfma2((&x[j >> 2].x)[j & 3], rs[(j >> 2) & 1], mr[(j >> 2) & 1]); asm volatile("" : "+r"(nx[j]) :: "memory"); }
                sched_bar();
                if (r) {
                    #pragma unroll
                    for (int i = 0; i < 4; i++) stg128(op + (i >> 1) * 128 - (i & 1) * 10240, x1[i].x, x1[i].y, x1[i].z, x1[i].w);
                }
                if (r == 5) break;
                if (ask && !asked) { if (__any_sync(~0u, (int)(pv - want) < 0)) y_poll(r); y_request(r); }
                asked = false;
                mbar_wait(BAR(B_Y + (r & 1)), (r >> 1) & 1);
                if (wv == 0 && r) { mbar_wait(BAR(B_YE + (~r & 1)), (r - 1) >> 1 & 1); pv = ldg_rlx32(pa); }
                if (r == 4) { _Pragma("unroll") for (int i = 0; i < 4; i++) mv[i] = ldg_rlx64(caddr(i)); }
                STAMPIF(wv == 0 && r == 0, 47);
                STAMPR(5);
                uint4 cc[8];
                uint32_t y[4][4];
                _Pragma("unroll 1") for (int it = 0; it < 20000; it++) {
                    uint32_t all = ~0u, any = 0;
                    #pragma unroll
                    for (int i = 0; i < 4; i++) ldsm4t(y[i], (yl ^ ((i & 1) << 4)) + (i >> 1) * 2048);
                    #pragma unroll
                    for (int i = 0; i < 8; i++) cc[i] = lds128(ca + (i >> 2) * 512 + (i & 3) * 64);
                    #pragma unroll
                    for (int j = 0; j < 16; j++) { all &= y[j >> 2][j & 3]; any |= y[j >> 2][j & 3]; }
                    if (!__any_sync(~0u, ((par ? ~all : any) & ym) != 0)) break;
                    VALIF(true, 89, 1);
                    const char* yp = SC(yT, (r * 128 + wv * 32 + (lane & 6) * 4 + (lane >> 3) * 2 + (lane & 1)) * 4096 + (254 - 2 * ft) * 16);
                    #pragma unroll
                    for (int i = 0; i < 4; i++) cp16((yl ^ ((i & 1) << 4)) + (i >> 1) * 2048, yp + (i & 1) * 16 + (i >> 1) * 262144);
                    asm volatile("cp.async.wait_all;" ::: "memory");
                    __syncwarp();
                }
                STAMPR(6);
                bump<256>(op); bump(xs, 4096);
                if (ZE) red_if(zc, 8, lane == r);
                #pragma unroll
                for (int j = 0; j < 16; j++) {
                    (&x1[j >> 2].x)[j & 3] = hfma2(hfma2(nx[j], cc[(j >> 3) * 4 + (j & 3)].x, cc[(j >> 3) * 4 + (j & 3)].y), y[j >> 2][j & 3], (&x[j >> 2].x)[j & 3]);
                    y[j >> 2][j & 3] = hmul2((&x1[j >> 2].x)[j & 3], cc[(j >> 3) * 4 + (j & 3)].z);
                    if ((j & 3) == (~j >> 2 & 1)) y[j >> 2][j & 3] = (y[j >> 2][j & 3] & ~tm) | (par & tm);
                    asm volatile("" : "+r"(y[j >> 2][j & 3]) :: "memory");
                }
                sched_bar();
                #pragma unroll
                for (int i = 0; i < 4; i++) asm volatile("st.relaxed.gpu.global.v4.b32 [%0], {%1,%2,%3,%4};" :: "l"(zp + (i >> 1) * 16384 - (i & 1) * 512), "r"(y[i][0]), "r"(y[i][1]), "r"(y[i][2]), "r"(y[i][3]) : "memory");
                if (!ZE) red_if(zc, 8, lane == r);
                mbar_arrive_if(r == 4 ? BAR(B_TD) : BAR(B_YE + (r & 1)), lane <= (r == 4));
                mbar_arrive_if(BAR(B_H + r), tid == 352);
                STAMPIF(wv, 75 + r);
                STAMPR(7);
            }
            const float e0 = ((q & 2) ? sa[2] : sa[0]) + __shfl_xor_sync(~0u, (q & 2) ? sa[0] : sa[2], 2), e1 = ((q & 2) ? sa[3] : sa[1]) + __shfl_xor_sync(~0u, (q & 2) ? sa[1] : sa[3], 2);
            float e = ((q & 1) ? e1 : e0) + __shfl_xor_sync(~0u, (q & 1) ? e0 : e1, 1);
            if (wv) sts32(sb + TAB2 + lane * 4, __float_as_uint(e));
            bar_sync(4, 64);
            if (wv) {
                if (l0) asm volatile("fence.release.gpu;\n red.relaxed.gpu.global.add.u32 [%0], 16;" :: "l"(CNT(C_Z + tile, 6)) : "memory");
                __syncwarp();
            } else {
                uint32_t oth; asm volatile("ld.shared.b32 %0, [%1];" : "=r"(oth) : "r"(sb + TAB2 + lane * 4) : "memory");
                e += __uint_as_float(oth);
                const float mu = e * (1.f / D_), ve = fmaxf(__shfl_down_sync(~0u, e, 1) * (1.f / D_) - mu * mu, 0.f) + 1e-5f, r_ = rsqrt_(ve);
                if (!(q & 1)) stg_rlx128(SC(st2, (ft * 16 + 15 - rr - 4 * q) * 16), split2(-mu), split2(ve * r_), __float_as_uint(r_ * r_), epoch);
            }
            if (!wv && elect()) pf_l2(P.Wd + b * 15360, 15360);
            mbar_wait(BAR(B_UD), 0);
            pause(D_UT);
            const char* up = SC(ut, (wv * 1536 + js * 192 + 2 * lane) * 8);
            uint4 v[15];
            _Pragma("unroll 1") for (int it = 0; it < 20000; it++) {
                uint32_t bad = 0;
                #pragma unroll
                for (int i = 0; i < 15; i++) v[i] = ldg_rlx2x64(up + (i / 3) * 24576 + (i % 3) * 512);
                #pragma unroll
                for (int i = 0; i < 15; i++) bad |= (v[i].x ^ epoch) | (v[i].z ^ epoch);
                if (!__any_sync(~0u, (bad & 7) != 0)) break;
            }
            #pragma unroll
            for (int n = 0; n < 3; n++) {
                float f[4];
                #pragma unroll
                for (int j = 0; j < 4; j++) f[j] = (__uint_as_float((&v[n].x)[j]) + __uint_as_float((&v[3 + n].x)[j])) + (__uint_as_float((&v[6 + n].x)[j]) + __uint_as_float((&v[9 + n].x)[j])) + __uint_as_float((&v[12 + n].x)[j]);
                const uint32_t ta = sb + TAB1 + ((n == 2 ? 32 + wv * 8 : n * 8 + wv * 16) + rr) * 48 + q * 4, th2 = pack2(f[1], f[3]);
                sts32(ta, pack2(f[0], f[2])); sts32(ta + 16, th2); sts32(ta + 32, pack2(f[1] - bflo(th2), f[3] - bfhi(th2)));
            }
            if (lane < 20) sts32(sb + TAB1 + 48 * 48 + lane * 4, 0);
            fence_async_smem();
            __syncwarp();
            mbar_arrive_if(BAR(B_T1), l0);
            STAMPIF(hw == 3, 43);
        }
        asm volatile("setmaxnreg.dec.sync.aligned.u32 40;");
        const uint32_t ep2 = __shfl_sync(~0u, epoch, 0), tg2 = ep2 << 7;
        const char* hfl = CNT(C_HH + tile * 2 + kh, 0);
        auto hh_src = [&](int j) { const int c = (j * 11) >> 5, m = j - 3 * c; return SC(hh, (tile * 24 + (kh * 4 + m + (m >= dq)) * 3 + (c ^ (c < 2))) * 16384); };
        if (hw == 0) {
            if (elect()) {
                const CUtensorMap *m1 = rank ? &M.u1 : &M.g1, *m2 = rank ? &M.u2 : &M.g2;
                const char* pw = P.Wg + (b + 128 * (NWP >> 1)) * 3072;
                const long long dw = P.Wu - P.Wg;
                pf_map(m1);
                _Pragma("unroll 1") for (int n = 0; n < 20; n += 2) {
                    #pragma unroll
                    for (int h = 0; h < 2; h++) {
                        const uint32_t so = (n & 2) + h;
                        mbar_wait(BAR(B_WE) + so * 8, (n >> 2) & 1);
                        mbar_expect(BAR(B_WF) + so * 8, 16384);
                        tma3d_mc(sb + WR + rank * 8192 + so * 16384, m1, (n + h) * 32, js * 3, BAR(B_WF) + so * 8);
                        if (n >= WP0 && n < WP0 + 10 - NWP) pf_l2(pw + h * dw, 3072);
                    }
                    if (n >= WP0) pw += 128 * 3072;
                }
                _Pragma("unroll 1") for (int n = 0; n < 10; n++) {
                    const uint32_t so = n & 3;
                    mbar_wait(BAR(B_WE) + so * 8, ((n >> 2) & 1) ^ 1);
                    mbar_expect(BAR(B_WF) + so * 8, 16384);
                    tma2d_mc(sb + WR + rank * 8192 + so * 16384, m2, js * 192 + 128, n * 64, BAR(B_WF) + so * 8);
                }
                _Pragma("unroll 1") for (int j = 0; j < 9; j++) {
                    const int c = (j * 11) >> 5;
                    const char* src = hh_src(j);
                    mbar_expect(BAR(B_AL + j), 16384);
                    if (j == 3 * c) { mbar_wait(BAR(B_HD + c), 0); poll_cnt(hfl + c * 4, tg2); fence_async_glob(); STAMPIF(c != 1, c ? 32 : 38); }
                    mbar_wait(c == 1 ? BAR(B_S0) : BAR(B_HS + j - 3 * c), c == 2);
                    bulk_g2s(sb + (j < 2 ? j + 12 : j < 8 ? j + 6 : 8) * 16384, src, 16384, BAR(B_AL + j));
                }
            }
        } else if (wv) {
            if (hw == 3) {
                const char* gp = SC(mod, (320 + dq * 80 + lane) * 8);
                auto gaddr = [&](int i) { return gp + i * 192; };
                uint2 gv[3];
                #pragma unroll
                for (int i = 0; i < 3; i++) gv[i] = ldg_rlx64(gaddr(i));
                ll_wait<3>(gv, ep2, gaddr);
                poll_cnt(CNT(C_Z + tile, 6), tg2);
                fence_acq();
                mbar_wait(BAR(B_HD), 0);
                red_if(hfl + lane * 4, 32, l0);
                STAMP(36);
                #pragma unroll
                for (int n = 0; n < 3; n++) sts32(sb + GBT + q * 80 + (rr + 6 * n) * 4, gv[n].x);
                __syncwarp();
                mbar_arrive_if(BAR(B_GB), l0);
                mbar_wait(BAR(B_HD + 1), 0);
                red_if(hfl + lane * 4, 32, lane == 1);
                mbar_wait(BAR(B_HD + 2), 0);
                red_if(hfl + lane * 4, 32, lane == 2);
                STAMP(40);
            } else {
                if (lane < 10) mbar_expect(BAR(B_AL + lane), 16384);
                if (elect()) { pf_map(&M.g2); pf_map(&M.u2); }
                const char *zc = CNT(C_Z + tile, lane & 7), *zp = SC(z, tile * 163840);
                uint32_t rtp = 0, zv = tg2 - 1, al = BAR(B_AL), dst = sb;
                const uint32_t vo = lane * 128 + (lane & 3) * 16 + (lane & 8) * 8 + (lane & 4);
                int zr = 0;
                _Pragma("unroll 1") for (int i = 0; i < 19; i++) {
                    if (zr < 5) {
                        const uint32_t fre = BAR(zr == 4 ? B_UD : zr ? B_RD + 3 + (zr > 1) : B_RD);
                        bool go = (__ballot_sync(~0u, (int)(zv - tg2) >= 0) >> zr) & 1;
                        if (2 * zr <= i) {
                            mbar_wait(fre, 0);
                            if (!go) {
                                if (!mbar_test(BAR(B_H + zr), 1)) { mbar_wait(BAR(B_H + zr), 1); pause(D_PZ); }
                                poll_cnt(CNT(C_Z + tile, zr), tg2);
                            }
                            go = true;
                        } else go = go && mbar_test(fre, 0);
                        if (go) {
                            if (elect()) {
                                fence_async_glob();
                                bulk_g2s(sb + zr * 32768, zp, 16384, BAR(B_AL + 2 * zr));
                                bulk_g2s(sb + zr * 32768 + 16384, zp + 16384, 16384, BAR(B_AL + 2 * zr + 1));
                            }
                            STAMP(80 + zr);
                            zr++; zp += 32768;
                        }
                    }
                    mbar_wait(al, i >= 10);
                    _Pragma("unroll 1") for (int rt = 0; rt < 2000; rt++) {
                        uint32_t v[4];
                        #pragma unroll
                        for (int k = 0; k < 4; k++) asm volatile("ld.shared.b32 %0, [%1];" : "=r"(v[k]) : "r"(dst + vo + k * 4096) : "memory");
                        if (!__any_sync(~0u, ((v[0] ^ ep2) | (v[1] ^ ep2) | (v[2] ^ ep2) | (v[3] ^ ep2)) & 1)) break;
                        int i_ = i; asm volatile("" : "+r"(i_));
                        VALIF(true, 87 + (i >= 10), 1);
                        if (elect()) { mbar_expect(BAR(B_RT), 16384); bulk_g2s(dst, i_ < 10 ? SC(z, (tile * 10 + i_) * 16384) : hh_src(i_ - 10), 16384, BAR(B_RT)); }
                        mbar_wait(BAR(B_RT), rtp);
                        rtp ^= 1;
                    }
                    mbar_arrive_if(al - 8 * (B_AL - B_AF), l0);
                    if (zr < 5) zv = ldg_rlx32(zc);
                    al += i == 9 ? -72 : 8; dst += i == 9 ? 49152 : i == 11 || i == 17 ? -81920 : 16384;
                    STAMPIF(i == 0 || i == 10 || i == 16, i == 10 ? 37 : i ? 74 : 42);
                }
            }
        } else if (elect()) {
            pf_map(&M.wn); pf_map(&M.wd); pf_map(&M.out);
            int g = 0, c = 0, m = -3;
            _Pragma("unroll 1") for (int n = 0; n < 12; n++) {
                const uint32_t st = sb + G2B + g * 20480 + rank * 10240, f = BAR(B_G2F + g);
                mbar_wait(BAR(B_G2E + g), n >= 6);
                mbar_expect(f, 20480);
                if (m < 0) tma3d_mc(st, &M.wn, (js * 3 + n) * 64 + rank * 32, dq * 5, f);
                else tma5d_mc(st, &M.wd, ((kh * 4 + m + (m >= dq)) * 3 + (c ^ (c < 2))) * 8 + rank * 4, dq * 5, f);
                g = g == 5 ? 0 : g + 1;
                if (++m == 3) { m = 0; c++; }
            }
        }
    }
}

typedef CUresult (*EncodeFn)(CUtensorMap*, CUtensorMapDataType, cuuint32_t, void*, const cuuint64_t*, const cuuint64_t*, const cuuint32_t*, const cuuint32_t*,
                             CUtensorMapInterleave, CUtensorMapSwizzle, CUtensorMapL2promotion, CUtensorMapFloatOOBfill);
void enc(EncodeFn fn, CUtensorMap* m, const void* ptr, int rank, const cuuint64_t* dims, const cuuint64_t* strides, const cuuint32_t* box, CUtensorMapSwizzle sw,
         CUtensorMapL2promotion pr = CU_TENSOR_MAP_L2_PROMOTION_L2_128B) {
    cuuint32_t es[5] = {1, 1, 1, 1, 1};
    fn(m, CU_TENSOR_MAP_DATA_TYPE_BFLOAT16, rank, (void*)ptr, dims, strides, box, es, CU_TENSOR_MAP_INTERLEAVE_NONE, sw,
       pr, CU_TENSOR_MAP_FLOAT_OOB_FILL_NONE);
}
}

extern "C" void kernel_launch(void* const* d_in, const int* in_sizes, int n_in, void* d_out, int out_size) {
    void* fnp = nullptr; cudaDriverEntryPointQueryResult st;
    cudaGetDriverEntryPoint("cuTensorMapEncodeTiled", &fnp, cudaEnableDefault, &st);
    EncodeFn fn = (EncodeFn)fnp;
    void* scr;
    cudaGetSymbolAddress(&scr, g_s);
    Maps M; Ptrs P;
    P.k = (const char*)d_in[1]; P.v = (const char*)d_in[2]; P.shift = (const char*)d_in[3]; P.ssm = (const char*)d_in[4]; P.ssmD = (const char*)d_in[5]; P.Wg = (const char*)d_in[7]; P.Wu = (const char*)d_in[8];
    P.Wd = (const char*)d_in[9]; P.c = (const char*)d_in[10]; P.out = (char*)d_out; P.scr = (char*)scr;
    { cuuint64_t d[4] = {640, 2, 256, 4}, s[3] = {1280, 8 * 1280, 2 * 1280}; cuuint32_t b1[4] = {64, 2, 5, 4}, b2[4] = {64, 2, 4, 4};
      enc(fn, &M.k, d_in[1], 4, d, s, b1, CU_TENSOR_MAP_SWIZZLE_128B); enc(fn, &M.v, d_in[2], 4, d, s, b2, CU_TENSOR_MAP_SWIZZLE_128B); }
    { cuuint64_t d[3] = {32, 2048, 20}, s[2] = {1280, 64}; cuuint32_t b1[3] = {32, 16, 4};
      enc(fn, &M.q, d_in[0], 3, d, s, b1, CU_TENSOR_MAP_SWIZZLE_NONE); }
    { cuuint64_t d[5] = {2048, 2, 4, 4, 20}, s[4] = {4096, 8 * 4096, 2 * 4096, 32 * 4096}; cuuint32_t b1[5] = {16, 2, 4, 4, 4};
      enc(fn, &M.y, (char*)scr + offsetof(Scratch, yT), 5, d, s, b1, CU_TENSOR_MAP_SWIZZLE_32B, CU_TENSOR_MAP_L2_PROMOTION_NONE); }
    { cuuint64_t d[3] = {64, 640, 24}, s[2] = {3072, 128}; cuuint32_t b1[3] = {64, 32, 2};
      enc(fn, &M.g1, P.Wg, 3, d, s, b1, CU_TENSOR_MAP_SWIZZLE_128B); enc(fn, &M.u1, P.Wu, 3, d, s, b1, CU_TENSOR_MAP_SWIZZLE_128B); }
    { cuuint64_t d[2] = {1536, 640}, s[1] = {3072}; cuuint32_t b1[2] = {64, 64};
      enc(fn, &M.g2, P.Wg, 2, d, s, b1, CU_TENSOR_MAP_SWIZZLE_128B); enc(fn, &M.u2, P.Wu, 2, d, s, b1, CU_TENSOR_MAP_SWIZZLE_128B); }
    { cuuint64_t d[5] = {32, 2, 192, 4, 20}, s[4] = {1280, 8 * 1280, 2 * 1280, 64}; cuuint32_t b1[5] = {32, 2, 4, 4, 5};
      enc(fn, &M.wd, P.Wd, 5, d, s, b1, CU_TENSOR_MAP_SWIZZLE_64B); }
    { cuuint64_t d[3] = {32, 1536, 20}, s[2] = {1280, 64}; cuuint32_t b1[3] = {32, 32, 5};
      enc(fn, &M.wn, P.Wd, 3, d, s, b1, CU_TENSOR_MAP_SWIZZLE_64B); }
    { cuuint64_t d[2] = {3840, 640}, s[1] = {7680}; cuuint32_t b1[2] = {64, 160};
      enc(fn, &M.wm, d_in[11], 2, d, s, b1, CU_TENSOR_MAP_SWIZZLE_128B); }
    { cuuint64_t d[3] = {640, 640, 6}, s[2] = {7680, 1280}; cuuint32_t b1[3] = {128, 5, 1};
      enc(fn, &M.wp, d_in[11], 3, d, s, b1, CU_TENSOR_MAP_SWIZZLE_NONE); }
    { cuuint64_t d[2] = {640, 2048}, s[1] = {1280}; cuuint32_t b1[2] = {80, 16};
      enc(fn, &M.out, d_out, 2, d, s, b1, CU_TENSOR_MAP_SWIZZLE_NONE); }
    cudaFuncSetAttribute(fused_kernel, cudaFuncAttributeMaxDynamicSharedMemorySize, SMEM_BYTES);
    fused_kernel<<<132, 384, SMEM_BYTES>>>(P, M);
}
```

```cpp
#include <cuda_runtime.h>
#include <cuda_bf16.h>
#include <cuda.h>
#include <stdint.h>
#include <stddef.h>
#include <type_traits>

namespace {

constexpr int D_ = 640;

struct Scratch {
    uint4 kvT[D_ * 256], yT[D_ * 256];
    uint4 z[16 * 10 * 1024];
    uint4 hh[16 * 24 * 1024];
    uint4 st2[2048];
    uint4 abc[320];
    uint2 mod[640];
    uint2 ut[5 * 3072];
    uint32_t cnt[64 * 1024];
};
__device__ __align__(1024) Scratch g_s;
#define SC(f, off) padd(P.scr, (uint32_t)offsetof(Scratch, f) + (off))
constexpr int C_KV = 0  , C_Y = 10  , C_Z = 16  , C_HH = 32  ;

constexpr uint32_t WR = 163840, MISC = 229376, SMEM_BYTES = 232448;
constexpr uint32_t ESLOT = 0x31650;
constexpr uint32_t XP = 4112, XB = 65536 + 18432, ST_SH = XB + 2 * XP;
constexpr uint32_t ST_Q = 131072, ST_Y = ST_Q + 20480, ST_S = ST_Y + 10240  , UST = ST_Q;
__host__ __device__ constexpr uint32_t st_kv(int r) { return r == 2 ? ST_Y : r == 1 || r == 4 ? 65536 + 9216 : 65536; }
__host__ __device__ constexpr uint32_t eslot(int r) { return ((ESLOT >> (4 * r)) & 7) << 15; }
constexpr uint32_t PP = 4352;
constexpr uint32_t BARS = MISC, TAB1 = MISC + 672, TAB2 = TAB1 + 32 * 48, CS_TAB = TAB1  , PRF = -256;
constexpr uint32_t GBT = 0, G2B = 8192, G2A = 131072;
enum { B_H = 0, B_KV = 5, B_Q = 10, B_X = 15  , B_MD = 17  , B_AF = 20, B_AL = 30, B_WF = 40, B_G2F = 44, B_GB = 50, B_RT = 51, B_Y = 52  ,
       B_WE = 54, B_G2E = 58,
       B_UD = 64, B_HD = 65  , B_S0 = 68, B_HS = 69  ,
       B_RD = 72, B_UF = 77, B_TD = 78  , B_T1 = 81, B_YE = 82  , NBARS = 84 };
__host__ __device__ constexpr uint32_t bar_count(int i) {
    return i < B_WE ? 1 : i < B_UD ? 16 : i < B_RD ? 8 : i < B_T1 ? 4 : 2;
}
#define GSTAMPIF(c, i) do {} while (0)
#define STAMPIF(c, i) do {} while (0)
#define STAMP(i) do {} while (0)
#define VALIF(c, i, v) do {} while (0)
#define STAMPI STAMPIF
#define STAMPR(i) do {} while (0)
#define TWAIT(i, stmt) stmt
#define STAMPS(k) do {} while (0)
#define QS 4
__host__ __device__ constexpr int epi_slot(int e) { return e * QS / 4; }
#define ER 7
#define MAPM 0
#define RQE 2
#define EI 1
#define Q2 4
#define G2R 5
#define YH 0
#define WP0 2
#define SEQ0 0x14124310224120ull
#define SEQ1 0x1324441123422140ull
#define NFAST 7
#define EARLYH 0
#define ZE 1
#define MPF 1
#define N_UT 13
#define NST 5
#define TN(i, v) v
#define TUNING 0
#define ORDER hkhhkxhqkxqqkqxqhwwww
#define TIMES 0, 860, 1570, 2100, 2890, 0, 3810, 0, 4520, 0, 0, 0, 6300, 0, 0, 0, 0, 8400, 0, 0, 0
#define STR2(x) #x
#define STR(x) STR2(x)
constexpr int NORD = sizeof(STR(ORDER)) - 1;
__host__ __device__ constexpr char ord_kind(int i) { return STR(ORDER)[i]; }
__host__ __device__ constexpr int ord_index(int i) { int n = ord_kind(i) == 'k'; for (int j = 0; j < i; j++) n += ord_kind(j) == ord_kind(i); return n; }
__host__ __device__ constexpr int ord_slot(int i) { int n = 0; for (int j = 0; j < i; j++) n += ord_kind(j) == 'k' ? 2 : ord_kind(j) != 'x'; return n; }
__host__ __device__ constexpr int ord_find(char c, int n) { for (int i = 0; i < NORD; i++) if (ord_kind(i) == c && ord_index(i) == n) return i; return -1; }
__host__ __device__ constexpr int ord_count(char c) { int n = 0; for (int i = 0; i < NORD; i++) n += ord_kind(i) == c; return n; }
__host__ __device__ constexpr uint32_t ord_mask(char c) { uint32_t m = 0; for (int i = 0; i < NORD; i++) m |= (uint32_t)(ord_kind(i) == c) << i; return m; }
__host__ __device__ constexpr int ord_time(int i) { constexpr int t[] = {TIMES}; return t[i]; }
constexpr int NWP = ord_count('w');
static_assert(NWP % 2 == 0 && ord_kind(0) == 'h' && ord_count('x') >= 2 && ord_count('k') == 4 && ord_count('q') == 5 && ord_count('h') == 5, "order");
#define TV0 500
#define D_1 TN(0, TV0)
#define TV1 420
#define G_U TN(1, TV1)
#define TV2 590
#define G_ST TN(2, TV2)
#define TV4 2000
#define D_SP TN(4, TV4)
#define TV5 0
#define G_F TN(5, TV5)
#define TV6 7500
#define D_M TN(6, TV6)
#define TV7 700
#define D_PK TN(7, TV7)
#define TV8 500
#define D_PY TN(8, TV8)
#define TV9 100
#define D_PZ TN(9, TV9)
#define TV10 100
#define D_H2 TN(10, TV10)
#define TV11 1400
#define D_UT TN(11, TV11)

__device__ __forceinline__ uint32_t smem_u32(const void* p) { return (uint32_t)__cvta_generic_to_shared(p); }
__device__ __forceinline__ void mbar_init(uint32_t bar, uint32_t cnt) { asm volatile("mbarrier.init.shared::cta.b64 [%0], %1;" :: "r"(bar), "r"(cnt) : "memory"); }
__device__ __forceinline__ void mbar_expect(uint32_t bar, uint32_t bytes) { asm volatile("mbarrier.arrive.expect_tx.shared::cta.b64 _, [%0], %1;" :: "r"(bar), "r"(bytes) : "memory"); }
__device__ __forceinline__ void mbar_arrive_if(uint32_t bar, bool p) { asm volatile("{ .reg .pred p; setp.ne.b32 p, %1, 0; @p mbarrier.arrive.shared::cta.b64 _, [%0]; }" :: "r"(bar), "r"((int)p) : "memory"); }
__device__ __forceinline__ void mbar_arrive_remote_if(uint32_t bar, bool p) { asm volatile("{ .reg .pred p; setp.ne.b32 p, %1, 0; @p mbarrier.arrive.shared::cluster.b64 _, [%0]; }" :: "r"(bar), "r"((int)p) : "memory"); }
#define WAIT_LOOP(op) "{\n .reg .pred p, q; .reg .u32 c; mov.u32 c, 0;\n LAB_WAIT:\n " op " p, [%0], %1;\n @p bra LAB_DONE;\n add.u32 c, c, 1; setp.lt.u32 q, c, 16384;\n @q bra LAB_WAIT;\n LAB_DONE:\n }"
__device__ __forceinline__ void mbar_wait(uint32_t bar, uint32_t parity) { asm volatile(WAIT_LOOP("mbarrier.try_wait.parity.shared::cta.b64") :: "r"(bar), "r"(parity) : "memory"); }
__device__ __forceinline__ bool mbar_test(uint32_t bar, uint32_t parity) {
    uint32_t ok; asm volatile("{ .reg .pred p; mbarrier.test_wait.parity.shared::cta.b64 p, [%1], %2; selp.u32 %0, 1, 0, p; }" : "=r"(ok) : "r"(bar), "r"(parity) : "memory"); return ok;
}
__device__ __forceinline__ uint32_t clock32() { uint32_t t; asm volatile("mov.u32 %0, %%clock;" : "=r"(t) :: "memory"); return t; }
__device__ __forceinline__ void wait_clock(uint32_t t0, uint32_t d) {
    asm volatile("{\n .reg .pred p; .reg .u32 t;\n LAB_CLK:\n mov.u32 t, %%clock; sub.u32 t, t, %0; setp.lt.u32 p, t, %1;\n @p bra LAB_CLK;\n }" :: "r"(t0), "r"(d) : "memory");
}
__device__ __forceinline__ bool elect() { uint32_t p; asm volatile("{ .reg .pred p; elect.sync _|p, 0xffffffff; selp.u32 %0, 1, 0, p; }" : "=r"(p)); return p; }
__device__ __forceinline__ void pf_map(const CUtensorMap* m) { asm volatile("prefetch.tensormap [%0];" :: "l"(m) : "memory"); }
__device__ __forceinline__ void bar_sync(int id, int n) { asm volatile("bar.sync %0, %1;" :: "r"(id), "r"(n) : "memory"); }
__device__ __forceinline__ bool bar_or(int id, int n, bool c) {
    uint32_t r; asm volatile("{ .reg .pred p, q; setp.ne.b32 p, %3, 0; bar.red.or.pred q, %1, %2, p; selp.u32 %0, 1, 0, q; }" : "=r"(r) : "r"(id), "r"(n), "r"((int)c) : "memory"); return r;
}
__device__ __forceinline__ void wait_until(uint32_t t1) {
    asm volatile("{\n .reg .pred p; .reg .s32 t;\n LAB_CLK:\n mov.u32 t, %%clock; sub.s32 t, t, %0; setp.lt.s32 p, t, 0;\n @p bra LAB_CLK;\n }" :: "r"(t1) : "memory");
}
__device__ __forceinline__ void pause(uint32_t d) { wait_clock(clock32(), d); }
__device__ __forceinline__ void bar_arrive(int id, int n) { asm volatile("bar.arrive %0, %1;" :: "r"(id), "r"(n) : "memory"); }
__device__ __forceinline__ void fence_async_smem() { asm volatile("fence.proxy.async.shared::cta;" ::: "memory"); }
__device__ __forceinline__ void fence_async_glob() { asm volatile("fence.proxy.async.global;" ::: "memory"); }
__device__ __forceinline__ void fence_acq() { asm volatile("fence.acquire.gpu;" ::: "memory"); }
__device__ __forceinline__ void bulk_g2s(uint32_t dst, const void* src, uint32_t bytes, uint32_t bar) {
    asm volatile("cp.async.bulk.shared::cluster.global.mbarrier::complete_tx::bytes [%0], [%1], %2, [%3];" :: "r"(dst), "l"(src), "r"(bytes), "r"(bar) : "memory");
}
__device__ __forceinline__ void pf_l2(const void* src, uint32_t bytes) { asm volatile("cp.async.bulk.prefetch.L2.global [%0], %1;" :: "l"(src), "r"(bytes) : "memory"); }
__device__ __forceinline__ void tma2d(uint32_t dst, const CUtensorMap* m, int c0, int c1, uint32_t bar) {
    asm volatile("cp.async.bulk.tensor.2d.shared::cluster.global.mbarrier::complete_tx::bytes [%0], [%1, {%3, %4}], [%2];" :: "r"(dst), "l"(m), "r"(bar), "r"(c0), "r"(c1) : "memory");
}
__device__ __forceinline__ void tma3d(uint32_t dst, const CUtensorMap* m, int c1, int c2, uint32_t bar) {
    asm volatile("cp.async.bulk.tensor.3d.shared::cluster.global.mbarrier::complete_tx::bytes [%0], [%1, {%5, %3, %4}], [%2];" :: "r"(dst), "l"(m), "r"(bar), "r"(c1), "r"(c2), "r"(0) : "memory");
}
__device__ __forceinline__ void tma4d(uint32_t dst, const CUtensorMap* m, int c0, int c2, uint32_t bar) {
    asm volatile("cp.async.bulk.tensor.4d.shared::cluster.global.mbarrier::complete_tx::bytes [%0], [%1, {%3, %5, %4, %5}], [%2];" :: "r"(dst), "l"(m), "r"(bar), "r"(c0), "r"(c2), "r"(0) : "memory");
}
__device__ __forceinline__ void tma5d(uint32_t dst, const CUtensorMap* m, int c0, int c4, uint32_t bar) {
    asm volatile("cp.async.bulk.tensor.5d.shared::cluster.global.mbarrier::complete_tx::bytes [%0], [%1, {%3, %5, %5, %5, %4}], [%2];" :: "r"(dst), "l"(m), "r"(bar), "r"(c0), "r"(c4), "r"(0) : "memory");
}
__device__ __forceinline__ void tma5d_mc(uint32_t dst, const CUtensorMap* m, int c2, int c4, uint32_t bar) {
    asm volatile("cp.async.bulk.tensor.5d.shared::cluster.global.mbarrier::complete_tx::bytes.multicast::cluster [%0], [%1, {%5, %5, %3, %5, %4}], [%2], %6;"
                 :: "r"(dst), "l"(m), "r"(bar), "r"(c2), "r"(c4), "r"(0), "h"((uint16_t)3) : "memory");
}
__device__ __forceinline__ void tma3d_mc(uint32_t dst, const CUtensorMap* m, int c1, int c2, uint32_t bar) {
    asm volatile("cp.async.bulk.tensor.3d.shared::cluster.global.mbarrier::complete_tx::bytes.multicast::cluster [%0], [%1, {%5, %3, %4}], [%2], %6;"
                 :: "r"(dst), "l"(m), "r"(bar), "r"(c1), "r"(c2), "r"(0), "h"((uint16_t)3) : "memory");
}
__device__ __forceinline__ void tma2d_mc(uint32_t dst, const CUtensorMap* m, int c0, int c1, uint32_t bar) {
    asm volatile("cp.async.bulk.tensor.2d.shared::cluster.global.mbarrier::complete_tx::bytes.multicast::cluster [%0], [%1, {%3, %4}], [%2], %5;"
                 :: "r"(dst), "l"(m), "r"(bar), "r"(c0), "r"(c1), "h"((uint16_t)3) : "memory");
}
__device__ __forceinline__ void tma3d_red(const CUtensorMap* m, uint32_t src, int c1, int c2) {
    asm volatile("cp.reduce.async.bulk.tensor.3d.global.shared::cta.add.bulk_group [%0, {%4, %2, %3}], [%1];" :: "l"(m), "r"(src), "r"(c1), "r"(c2), "r"(0) : "memory");
}
__device__ __forceinline__ void pf_tma3d(const CUtensorMap* m, int c0, int c1, int c2) { asm volatile("cp.async.bulk.prefetch.tensor.3d.L2.global [%0, {%1, %2, %3}];" :: "l"(m), "r"(c0), "r"(c1), "r"(c2) : "memory"); }
__device__ __forceinline__ void red_if(const void* c, uint32_t inc, bool p) { asm volatile("{ .reg .pred p; setp.ne.b32 p, %2, 0; @p red.relaxed.gpu.global.add.u32 [%0], %1; }" :: "l"(c), "r"(inc), "r"((int)p) : "memory"); }
__device__ __forceinline__ uint32_t ldg_rlx32(const void* p) { uint32_t v; asm volatile("ld.relaxed.gpu.global.u32 %0, [%1];" : "=r"(v) : "l"(p) : "memory"); return v; }
__device__ __forceinline__ uint32_t ldg_late(const char* p, int lane) { return ldg_rlx32(p + (lane & 1) * 4); }
__device__ __forceinline__ bool reached(uint32_t v, uint32_t target) { return __ballot_sync(~0u, (int)(v - target) >= 0) & 1; }
__device__ __forceinline__ uint2 ldg_rlx64(const void* p) { uint2 v; asm volatile("{ .reg .b64 x; ld.relaxed.gpu.global.b64 x, [%2]; mov.b64 {%0, %1}, x; }" : "=r"(v.x), "=r"(v.y) : "l"(p) : "memory"); return v; }
__device__ __forceinline__ void ldg_rlx128_if(uint4& v, const void* p, bool c) {
    asm volatile("{ .reg .b128 t; .reg .b64 x, y; .reg .pred p; setp.ne.b32 p, %5, 0; mov.b64 x, {%0, %1}; mov.b64 y, {%2, %3}; mov.b128 t, {x, y};\n"
                 " @p ld.relaxed.gpu.global.b128 t, [%4]; mov.b128 {x, y}, t; mov.b64 {%0, %1}, x; mov.b64 {%2, %3}, y; }"
                 : "+r"(v.x), "+r"(v.y), "+r"(v.z), "+r"(v.w) : "l"(p), "r"((int)c) : "memory");
}
__device__ __forceinline__ uint4 ldg_rlx2x64(const void* p) { uint4 v; asm volatile("{ .reg .b64 x, y; ld.relaxed.gpu.global.v2.b64 {x, y}, [%4]; mov.b64 {%0, %1}, x; mov.b64 {%2, %3}, y; }" : "=r"(v.x), "=r"(v.y), "=r"(v.z), "=r"(v.w) : "l"(p) : "memory"); return v; }
__device__ __forceinline__ void stg_rlx128(void* p, uint32_t x, uint32_t y, uint32_t z, uint32_t w) {
    asm volatile("{ .reg .b128 t; .reg .b64 a, b; mov.b64 a, {%1, %2}; mov.b64 b, {%3, %4}; mov.b128 t, {a, b}; st.relaxed.gpu.global.b128 [%0], t; }" :: "l"(p), "r"(x), "r"(y), "r"(z), "r"(w) : "memory");
}
__device__ __forceinline__ void stg_rlx128_if(void* p, const uint32_t* v, bool c) {
    asm volatile("{ .reg .pred p; .reg .b128 t; .reg .b64 a, b; setp.ne.b32 p, %5, 0; mov.b64 a, {%1, %2}; mov.b64 b, {%3, %4}; mov.b128 t, {a, b}; @p st.relaxed.gpu.global.b128 [%0], t; }" :: "l"(p), "r"(v[0]), "r"(v[1]), "r"(v[2]), "r"(v[3]), "r"((int)c) : "memory");
}
__device__ __forceinline__ void stg128(void* p, uint32_t x, uint32_t y, uint32_t z, uint32_t w) { asm volatile("st.global.v4.b32 [%0], {%1,%2,%3,%4};" :: "l"(p), "r"(x), "r"(y), "r"(z), "r"(w) : "memory"); }
template<int W> __device__ __forceinline__ void stg_tag(void* p, const uint32_t* o, uint32_t tm, uint32_t par) {
    const uint32_t t = (o[W] & ~tm) | (par & tm);
    asm volatile("st.relaxed.gpu.global.v4.b32 [%0], {%1,%2,%3,%4};" :: "l"(p), "r"(W ? o[0] : t), "r"(W ? t : o[1]), "r"(o[2]), "r"(o[3]) : "memory");
}
__device__ __forceinline__ void poll_cnt(const void* c, uint32_t target) {
    asm volatile("{\n .reg .pred p, q; .reg .u32 c, v; mov.u32 c, 0;\n LAB_POLL:\n ld.relaxed.gpu.global.u32 v, [%0];\n sub.u32 v, v, %1; setp.ge.s32 p, v, 0;\n @p bra LAB_PDONE;\n"
                 " add.u32 c, c, 1; setp.lt.u32 q, c, 20000;\n @q bra LAB_POLL;\n LAB_PDONE:\n }" :: "l"(c), "r"(target) : "memory");
}
template<int N, typename F> __device__ __forceinline__ void ll_wait(uint2* v, uint32_t tag, F&& addr) {
    #pragma unroll 1
    for (int it = 0; it < 20000; it++) {
        uint32_t bad = 0;
        #pragma unroll
        for (int i = 0; i < N; i++) bad |= v[i].y ^ tag;
        if (!__any_sync(~0u, bad != 0)) break;
        asm volatile("nanosleep.u32 100;");
        #pragma unroll
        for (int i = 0; i < N; i++) v[i] = ldg_rlx64(addr(i));
    }
}
__device__ __forceinline__ uint4 lds128(uint32_t a) { uint4 v; asm volatile("ld.shared.v4.b32 {%0,%1,%2,%3}, [%4];" : "=r"(v.x), "=r"(v.y), "=r"(v.z), "=r"(v.w) : "r"(a) : "memory"); return v; }
__device__ __forceinline__ uint2 lds64(uint32_t a) { uint2 v; asm volatile("ld.shared.v2.b32 {%0,%1}, [%2];" : "=r"(v.x), "=r"(v.y) : "r"(a) : "memory"); return v; }
__device__ __forceinline__ void sts128(uint32_t a, uint32_t x, uint32_t y, uint32_t z, uint32_t w) { asm volatile("st.shared.v4.b32 [%0], {%1,%2,%3,%4};" :: "r"(a), "r"(x), "r"(y), "r"(z), "r"(w) : "memory"); }
__device__ __forceinline__ void sts32(uint32_t a, uint32_t x) { asm volatile("st.shared.b32 [%0], %1;" :: "r"(a), "r"(x) : "memory"); }
__device__ __forceinline__ void ldsm4t(uint32_t* r, uint32_t a) { asm volatile("ldmatrix.sync.aligned.m8n8.x4.trans.shared.b16 {%0,%1,%2,%3}, [%4];" : "=r"(r[0]), "=r"(r[1]), "=r"(r[2]), "=r"(r[3]) : "r"(a) : "memory"); }
__device__ __forceinline__ void ldsm2t(uint32_t& r0, uint32_t& r1, uint32_t a) { asm volatile("ldmatrix.sync.aligned.m8n8.x2.trans.shared.b16 {%0,%1}, [%2];" : "=r"(r0), "=r"(r1) : "r"(a) : "memory"); }
__device__ __forceinline__ void ldsm4t_if(uint32_t* r, uint32_t a, bool c) { asm volatile("{ .reg .pred p; setp.ne.b32 p, %5, 0; @p ldmatrix.sync.aligned.m8n8.x4.trans.shared.b16 {%0,%1,%2,%3}, [%4]; }" : "+r"(r[0]), "+r"(r[1]), "+r"(r[2]), "+r"(r[3]) : "r"(a), "r"((int)c) : "memory"); }
__device__ __forceinline__ void ldsm2t_if(uint32_t* r, uint32_t a, bool c) { asm volatile("{ .reg .pred p; setp.ne.b32 p, %3, 0; @p ldmatrix.sync.aligned.m8n8.x2.trans.shared.b16 {%0,%1}, [%2]; }" : "+r"(r[0]), "+r"(r[1]) : "r"(a), "r"((int)c) : "memory"); }
__device__ __forceinline__ void lds128_if(uint4& v, uint32_t a, bool c) { asm volatile("{ .reg .pred p; setp.ne.b32 p, %5, 0; @p ld.shared.v4.b32 {%0,%1,%2,%3}, [%4]; }" : "+r"(v.x), "+r"(v.y), "+r"(v.z), "+r"(v.w) : "r"(a), "r"((int)c) : "memory"); }
__device__ __forceinline__ void cp16(uint32_t d, const void* s) { asm volatile("cp.async.cg.shared.global [%0], [%1], 16;" :: "r"(d), "l"(s) : "memory"); }
__device__ __forceinline__ char* padd(const void* p, uint32_t off) { char* r; asm("{ .reg .u64 t; cvt.u64.u32 t, %2; add.u64 %0, %1, t; }" : "=l"(r) : "l"(p), "r"(off)); return r; }
__device__ __forceinline__ uint32_t prmt(uint32_t a, uint32_t b, uint32_t s) { uint32_t r; asm("prmt.b32 %0, %1, %2, %3;" : "=r"(r) : "r"(a), "r"(b), "r"(s)); return r; }
__device__ __forceinline__ uint32_t pack2(float lo, float hi) { uint32_t r; asm("cvt.rn.bf16x2.f32 %0, %1, %2;" : "=r"(r) : "f"(hi), "f"(lo)); return r; }
__device__ __forceinline__ uint32_t pack2relu(float lo, float hi) { uint32_t r; asm("cvt.rn.relu.bf16x2.f32 %0, %1, %2;" : "=r"(r) : "f"(hi), "f"(lo)); return r; }
__device__ __forceinline__ float bflo(uint32_t w) { return __uint_as_float(w << 16); }
__device__ __forceinline__ float bfhi(uint32_t w) { return __uint_as_float(w & 0xffff0000u); }
__device__ __forceinline__ float bfround(float x) { return bflo(pack2(x, x)); }
__device__ __forceinline__ uint32_t hmul2(uint32_t a, uint32_t b) { uint32_t r; asm("mul.rn.bf16x2 %0, %1, %2;" : "=r"(r) : "r"(a), "r"(b)); return r; }
__device__ __forceinline__ uint32_t hadd2(uint32_t a, uint32_t b) { uint32_t r; asm("add.rn.bf16x2 %0, %1, %2;" : "=r"(r) : "r"(a), "r"(b)); return r; }
__device__ __forceinline__ uint32_t hfma2(uint32_t a, uint32_t b, uint32_t c) { uint32_t r; asm("fma.rn.bf16x2 %0, %1, %2, %3;" : "=r"(r) : "r"(a), "r"(b), "r"(c)); return r; }
__device__ __forceinline__ void sched_bar() { asm volatile("pmevent 1;" ::: "memory"); }
template<int H> __device__ __forceinline__ uint32_t hfma2s(uint32_t a, uint32_t w, uint32_t c) {
    uint32_t r;
    if (H) asm("{ .reg .b16 l, h; .reg .b32 t; mov.b32 {l, h}, %2; mov.b32 t, {h, h}; fma.rn.bf16x2 %0, %1, t, %3; }" : "=r"(r) : "r"(a), "r"(w), "r"(c));
    else asm("{ .reg .b16 l, h; .reg .b32 t; mov.b32 {l, h}, %2; mov.b32 t, {l, l}; fma.rn.bf16x2 %0, %1, t, %3; }" : "=r"(r) : "r"(a), "r"(w), "r"(c));
    return r;
}
__device__ __forceinline__ void bump(uint32_t& a, uint32_t d) { asm volatile("add.u32 %0, %0, %1;" : "+r"(a) : "r"(d) : "memory"); }
template<int D> __device__ __forceinline__ void bump(char*& p) { asm volatile("add.s64 %0, %0, %1;" : "+l"(p) : "n"(D) : "memory"); }
__device__ __forceinline__ void wg_fence() { asm volatile("wgmma.fence.sync.aligned;" ::: "memory"); }
__device__ __forceinline__ void wg_commit() { asm volatile("wgmma.commit_group.sync.aligned;" ::: "memory"); }
template<int N> __device__ __forceinline__ void wg_wait() { asm volatile("wgmma.wait_group.sync.aligned %0;" :: "n"(N) : "memory"); }
template<int N> __device__ __forceinline__ void pin(float* d) {
    #pragma unroll
    for (int i = 0; i < N; i++) asm volatile("" : "+f"(d[i]) :: "memory");
}
__device__ __forceinline__ uint32_t dlo(uint32_t addr, uint32_t lbo) { return ((addr & 0x3FFFF) >> 4) | ((lbo >> 4) << 16); }
__host__ __device__ constexpr uint32_t dhi(uint32_t sbo, uint32_t sw) { return (sbo >> 4) | (sw << 30); }

template<int N> struct WG;
template<> struct WG<8> { template<int TA, int TB> static __device__ __forceinline__ void ss(float* d, uint32_t alo, uint32_t ahi, uint32_t blo, uint32_t bhi, int sd) {
  asm volatile("{ .reg .pred p; .reg .b64 da, db; mov.b64 da, {%4,%5}; mov.b64 db, {%6,%7}; setp.ne.b32 p, %8, 0;\n"
    "wgmma.mma_async.sync.aligned.m64n8k16.f32.bf16.bf16 {%0,%1,%2,%3}, da, db, p, 1, 1, %9, %10; }"
    : "+f"(d[0]),"+f"(d[1]),"+f"(d[2]),"+f"(d[3])
    : "r"(alo), "r"(ahi), "r"(blo), "r"(bhi), "r"(sd), "n"(TA), "n"(TB)); }
};
template<> struct WG<16> { template<int TA, int TB> static __device__ __forceinline__ void ss(float* d, uint32_t alo, uint32_t ahi, uint32_t blo, uint32_t bhi, int sd) {
  asm volatile("{ .reg .pred p; .reg .b64 da, db; mov.b64 da, {%8,%9}; mov.b64 db, {%10,%11}; setp.ne.b32 p, %12, 0;\n"
    "wgmma.mma_async.sync.aligned.m64n16k16.f32.bf16.bf16 {%0,%1,%2,%3,%4,%5,%6,%7}, da, db, p, 1, 1, %13, %14; }"
    : "+f"(d[0]),"+f"(d[1]),"+f"(d[2]),"+f"(d[3]),"+f"(d[4]),"+f"(d[5]),"+f"(d[6]),"+f"(d[7])
    : "r"(alo), "r"(ahi), "r"(blo), "r"(bhi), "r"(sd), "n"(TA), "n"(TB)); }
};
template<> struct WG<32> { template<int TA, int TB> static __device__ __forceinline__ void ss(float* d, uint32_t alo, uint32_t ahi, uint32_t blo, uint32_t bhi, int sd) {
  asm volatile("{ .reg .pred p; .reg .b64 da, db; mov.b64 da, {%16,%17}; mov.b64 db, {%18,%19}; setp.ne.b32 p, %20, 0;\n"
    "wgmma.mma_async.sync.aligned.m64n32k16.f32.bf16.bf16 {%0,%1,%2,%3,%4,%5,%6,%7,%8,%9,%10,%11,%12,%13,%14,%15}, da, db, p, 1, 1, %21, %22; }"
    : "+f"(d[0]),"+f"(d[1]),"+f"(d[2]),"+f"(d[3]),"+f"(d[4]),"+f"(d[5]),"+f"(d[6]),"+f"(d[7]),"+f"(d[8]),"+f"(d[9]),"+f"(d[10]),"+f"(d[11]),"+f"(d[12]),"+f"(d[13]),"+f"(d[14]),"+f"(d[15])
    : "r"(alo), "r"(ahi), "r"(blo), "r"(bhi), "r"(sd), "n"(TA), "n"(TB)); }
};
template<> struct WG<48> { template<int TA, int TB> static __device__ __forceinline__ void ss(float* d, uint32_t alo, uint32_t ahi, uint32_t blo, uint32_t bhi, int sd) {
  asm volatile("{ .reg .pred p; .reg .b64 da, db; mov.b64 da, {%24,%25}; mov.b64 db, {%26,%27}; setp.ne.b32 p, %28, 0;\n"
    "wgmma.mma_async.sync.aligned.m64n48k16.f32.bf16.bf16 {%0,%1,%2,%3,%4,%5,%6,%7,%8,%9,%10,%11,%12,%13,%14,%15,%16,%17,%18,%19,%20,%21,%22,%23}, da, db, p, 1, 1, %29, %30; }"
    : "+f"(d[0]),"+f"(d[1]),"+f"(d[2]),"+f"(d[3]),"+f"(d[4]),"+f"(d[5]),"+f"(d[6]),"+f"(d[7]),"+f"(d[8]),"+f"(d[9]),"+f"(d[10]),"+f"(d[11]),"+f"(d[12]),"+f"(d[13]),"+f"(d[14]),"+f"(d[15]),"+f"(d[16]),"+f"(d[17]),"+f"(d[18]),"+f"(d[19]),"+f"(d[20]),"+f"(d[21]),"+f"(d[22]),"+f"(d[23])
    : "r"(alo), "r"(ahi), "r"(blo), "r"(bhi), "r"(sd), "n"(TA), "n"(TB)); }
};
template<> struct WG<64> { template<int TA, int TB> static __device__ __forceinline__ void ss(float* d, uint32_t alo, uint32_t ahi, uint32_t blo, uint32_t bhi, int sd) {
  asm volatile("{ .reg .pred p; .reg .b64 da, db; mov.b64 da, {%32,%33}; mov.b64 db, {%34,%35}; setp.ne.b32 p, %36, 0;\n"
    "wgmma.mma_async.sync.aligned.m64n64k16.f32.bf16.bf16 {%0,%1,%2,%3,%4,%5,%6,%7,%8,%9,%10,%11,%12,%13,%14,%15,%16,%17,%18,%19,%20,%21,%22,%23,%24,%25,%26,%27,%28,%29,%30,%31}, da, db, p, 1, 1, %37, %38; }"
    : "+f"(d[0]),"+f"(d[1]),"+f"(d[2]),"+f"(d[3]),"+f"(d[4]),"+f"(d[5]),"+f"(d[6]),"+f"(d[7]),"+f"(d[8]),"+f"(d[9]),"+f"(d[10]),"+f"(d[11]),"+f"(d[12]),"+f"(d[13]),"+f"(d[14]),"+f"(d[15]),"+f"(d[16]),"+f"(d[17]),"+f"(d[18]),"+f"(d[19]),"+f"(d[20]),"+f"(d[21]),"+f"(d[22]),"+f"(d[23]),"+f"(d[24]),"+f"(d[25]),"+f"(d[26]),"+f"(d[27]),"+f"(d[28]),"+f"(d[29]),"+f"(d[30]),"+f"(d[31])
    : "r"(alo), "r"(ahi), "r"(blo), "r"(bhi), "r"(sd), "n"(TA), "n"(TB)); }
};
template<> struct WG<80> { template<int TA, int TB> static __device__ __forceinline__ void ss(float* d, uint32_t alo, uint32_t ahi, uint32_t blo, uint32_t bhi, int sd) {
  asm volatile("{ .reg .pred p; .reg .b64 da, db; mov.b64 da, {%40,%41}; mov.b64 db, {%42,%43}; setp.ne.b32 p, %44, 0;\n"
    "wgmma.mma_async.sync.aligned.m64n80k16.f32.bf16.bf16 {%0,%1,%2,%3,%4,%5,%6,%7,%8,%9,%10,%11,%12,%13,%14,%15,%16,%17,%18,%19,%20,%21,%22,%23,%24,%25,%26,%27,%28,%29,%30,%31,%32,%33,%34,%35,%36,%37,%38,%39}, da, db, p, 1, 1, %45, %46; }"
    : "+f"(d[0]),"+f"(d[1]),"+f"(d[2]),"+f"(d[3]),"+f"(d[4]),"+f"(d[5]),"+f"(d[6]),"+f"(d[7]),"+f"(d[8]),"+f"(d[9]),"+f"(d[10]),"+f"(d[11]),"+f"(d[12]),"+f"(d[13]),"+f"(d[14]),"+f"(d[15]),"+f"(d[16]),"+f"(d[17]),"+f"(d[18]),"+f"(d[19]),"+f"(d[20]),"+f"(d[21]),"+f"(d[22]),"+f"(d[23]),"+f"(d[24]),"+f"(d[25]),"+f"(d[26]),"+f"(d[27]),"+f"(d[28]),"+f"(d[29]),"+f"(d[30]),"+f"(d[31]),"+f"(d[32]),"+f"(d[33]),"+f"(d[34]),"+f"(d[35]),"+f"(d[36]),"+f"(d[37]),"+f"(d[38]),"+f"(d[39])
    : "r"(alo), "r"(ahi), "r"(blo), "r"(bhi), "r"(sd), "n"(TA), "n"(TB)); }
};
template<> struct WG<96> { template<int TA, int TB> static __device__ __forceinline__ void ss(float* d, uint32_t alo, uint32_t ahi, uint32_t blo, uint32_t bhi, int sd) {
  asm volatile("{ .reg .pred p; .reg .b64 da, db; mov.b64 da, {%48,%49}; mov.b64 db, {%50,%51}; setp.ne.b32 p, %52, 0;\n"
    "wgmma.mma_async.sync.aligned.m64n96k16.f32.bf16.bf16 {%0,%1,%2,%3,%4,%5,%6,%7,%8,%9,%10,%11,%12,%13,%14,%15,%16,%17,%18,%19,%20,%21,%22,%23,%24,%25,%26,%27,%28,%29,%30,%31,%32,%33,%34,%35,%36,%37,%38,%39,%40,%41,%42,%43,%44,%45,%46,%47}, da, db, p, 1, 1, %53, %54; }"
    : "+f"(d[0]),"+f"(d[1]),"+f"(d[2]),"+f"(d[3]),"+f"(d[4]),"+f"(d[5]),"+f"(d[6]),"+f"(d[7]),"+f"(d[8]),"+f"(d[9]),"+f"(d[10]),"+f"(d[11]),"+f"(d[12]),"+f"(d[13]),"+f"(d[14]),"+f"(d[15]),"+f"(d[16]),"+f"(d[17]),"+f"(d[18]),"+f"(d[19]),"+f"(d[20]),"+f"(d[21]),"+f"(d[22]),"+f"(d[23]),"+f"(d[24]),"+f"(d[25]),"+f"(d[26]),"+f"(d[27]),"+f"(d[28]),"+f"(d[29]),"+f"(d[30]),"+f"(d[31]),"+f"(d[32]),"+f"(d[33]),"+f"(d[34]),"+f"(d[35]),"+f"(d[36]),"+f"(d[37]),"+f"(d[38]),"+f"(d[39]),"+f"(d[40]),"+f"(d[41]),"+f"(d[42]),"+f"(d[43]),"+f"(d[44]),"+f"(d[45]),"+f"(d[46]),"+f"(d[47])
    : "r"(alo), "r"(ahi), "r"(blo), "r"(bhi), "r"(sd), "n"(TA), "n"(TB)); }
};
template<> struct WG<112> { template<int TA, int TB> static __device__ __forceinline__ void ss(float* d, uint32_t alo, uint32_t ahi, uint32_t blo, uint32_t bhi, int sd) {
  asm volatile("{ .reg .pred p; .reg .b64 da, db; mov.b64 da, {%56,%57}; mov.b64 db, {%58,%59}; setp.ne.b32 p, %60, 0;\n"
    "wgmma.mma_async.sync.aligned.m64n112k16.f32.bf16.bf16 {%0,%1,%2,%3,%4,%5,%6,%7,%8,%9,%10,%11,%12,%13,%14,%15,%16,%17,%18,%19,%20,%21,%22,%23,%24,%25,%26,%27,%28,%29,%30,%31,%32,%33,%34,%35,%36,%37,%38,%39,%40,%41,%42,%43,%44,%45,%46,%47,%48,%49,%50,%51,%52,%53,%54,%55}, da, db, p, 1, 1, %61, %62; }"
    : "+f"(d[0]),"+f"(d[1]),"+f"(d[2]),"+f"(d[3]),"+f"(d[4]),"+f"(d[5]),"+f"(d[6]),"+f"(d[7]),"+f"(d[8]),"+f"(d[9]),"+f"(d[10]),"+f"(d[11]),"+f"(d[12]),"+f"(d[13]),"+f"(d[14]),"+f"(d[15]),"+f"(d[16]),"+f"(d[17]),"+f"(d[18]),"+f"(d[19]),"+f"(d[20]),"+f"(d[21]),"+f"(d[22]),"+f"(d[23]),"+f"(d[24]),"+f"(d[25]),"+f"(d[26]),"+f"(d[27]),"+f"(d[28]),"+f"(d[29]),"+f"(d[30]),"+f"(d[31]),"+f"(d[32]),"+f"(d[33]),"+f"(d[34]),"+f"(d[35]),"+f"(d[36]),"+f"(d[37]),"+f"(d[38]),"+f"(d[39]),"+f"(d[40]),"+f"(d[41]),"+f"(d[42]),"+f"(d[43]),"+f"(d[44]),"+f"(d[45]),"+f"(d[46]),"+f"(d[47]),"+f"(d[48]),"+f"(d[49]),"+f"(d[50]),"+f"(d[51]),"+f"(d[52]),"+f"(d[53]),"+f"(d[54]),"+f"(d[55])
    : "r"(alo), "r"(ahi), "r"(blo), "r"(bhi), "r"(sd), "n"(TA), "n"(TB)); }
};
template<> struct WG<128> { template<int TA, int TB> static __device__ __forceinline__ void ss(float* d, uint32_t alo, uint32_t ahi, uint32_t blo, uint32_t bhi, int sd) {
  asm volatile("{ .reg .pred p; .reg .b64 da, db; mov.b64 da, {%64,%65}; mov.b64 db, {%66,%67}; setp.ne.b32 p, %68, 0;\n"
    "wgmma.mma_async.sync.aligned.m64n128k16.f32.bf16.bf16 {%0,%1,%2,%3,%4,%5,%6,%7,%8,%9,%10,%11,%12,%13,%14,%15,%16,%17,%18,%19,%20,%21,%22,%23,%24,%25,%26,%27,%28,%29,%30,%31,%32,%33,%34,%35,%36,%37,%38,%39,%40,%41,%42,%43,%44,%45,%46,%47,%48,%49,%50,%51,%52,%53,%54,%55,%56,%57,%58,%59,%60,%61,%62,%63}, da, db, p, 1, 1, %69, %70; }"
    : "+f"(d[0]),"+f"(d[1]),"+f"(d[2]),"+f"(d[3]),"+f"(d[4]),"+f"(d[5]),"+f"(d[6]),"+f"(d[7]),"+f"(d[8]),"+f"(d[9]),"+f"(d[10]),"+f"(d[11]),"+f"(d[12]),"+f"(d[13]),"+f"(d[14]),"+f"(d[15]),"+f"(d[16]),"+f"(d[17]),"+f"(d[18]),"+f"(d[19]),"+f"(d[20]),"+f"(d[21]),"+f"(d[22]),"+f"(d[23]),"+f"(d[24]),"+f"(d[25]),"+f"(d[26]),"+f"(d[27]),"+f"(d[28]),"+f"(d[29]),"+f"(d[30]),"+f"(d[31]),"+f"(d[32]),"+f"(d[33]),"+f"(d[34]),"+f"(d[35]),"+f"(d[36]),"+f"(d[37]),"+f"(d[38]),"+f"(d[39]),"+f"(d[40]),"+f"(d[41]),"+f"(d[42]),"+f"(d[43]),"+f"(d[44]),"+f"(d[45]),"+f"(d[46]),"+f"(d[47]),"+f"(d[48]),"+f"(d[49]),"+f"(d[50]),"+f"(d[51]),"+f"(d[52]),"+f"(d[53]),"+f"(d[54]),"+f"(d[55]),"+f"(d[56]),"+f"(d[57]),"+f"(d[58]),"+f"(d[59]),"+f"(d[60]),"+f"(d[61]),"+f"(d[62]),"+f"(d[63])
    : "r"(alo), "r"(ahi), "r"(blo), "r"(bhi), "r"(sd), "n"(TA), "n"(TB)); }
  template<int TB> static __device__ __forceinline__ void rs(float* d, uint32_t a0, uint32_t a1, uint32_t a2, uint32_t a3, uint32_t blo, uint32_t bhi, int sd) {
  asm volatile("{ .reg .pred p; .reg .b64 db; mov.b64 db, {%68,%69}; setp.ne.b32 p, %71, 0;\n"
    "wgmma.mma_async.sync.aligned.m64n128k16.f32.bf16.bf16 {%0,%1,%2,%3,%4,%5,%6,%7,%8,%9,%10,%11,%12,%13,%14,%15,%16,%17,%18,%19,%20,%21,%22,%23,%24,%25,%26,%27,%28,%29,%30,%31,%32,%33,%34,%35,%36,%37,%38,%39,%40,%41,%42,%43,%44,%45,%46,%47,%48,%49,%50,%51,%52,%53,%54,%55,%56,%57,%58,%59,%60,%61,%62,%63}, {%64,%65,%66,%67}, db, p, 1, 1, %70; }"
    : "+f"(d[0]),"+f"(d[1]),"+f"(d[2]),"+f"(d[3]),"+f"(d[4]),"+f"(d[5]),"+f"(d[6]),"+f"(d[7]),"+f"(d[8]),"+f"(d[9]),"+f"(d[10]),"+f"(d[11]),"+f"(d[12]),"+f"(d[13]),"+f"(d[14]),"+f"(d[15]),"+f"(d[16]),"+f"(d[17]),"+f"(d[18]),"+f"(d[19]),"+f"(d[20]),"+f"(d[21]),"+f"(d[22]),"+f"(d[23]),"+f"(d[24]),"+f"(d[25]),"+f"(d[26]),"+f"(d[27]),"+f"(d[28]),"+f"(d[29]),"+f"(d[30]),"+f"(d[31]),"+f"(d[32]),"+f"(d[33]),"+f"(d[34]),"+f"(d[35]),"+f"(d[36]),"+f"(d[37]),"+f"(d[38]),"+f"(d[39]),"+f"(d[40]),"+f"(d[41]),"+f"(d[42]),"+f"(d[43]),"+f"(d[44]),"+f"(d[45]),"+f"(d[46]),"+f"(d[47]),"+f"(d[48]),"+f"(d[49]),"+f"(d[50]),"+f"(d[51]),"+f"(d[52]),"+f"(d[53]),"+f"(d[54]),"+f"(d[55]),"+f"(d[56]),"+f"(d[57]),"+f"(d[58]),"+f"(d[59]),"+f"(d[60]),"+f"(d[61]),"+f"(d[62]),"+f"(d[63])
    : "r"(a0), "r"(a1), "r"(a2), "r"(a3), "r"(blo), "r"(bhi), "n"(TB), "r"(sd)); }
};
template<> struct WG<144> { template<int TA, int TB> static __device__ __forceinline__ void ss(float* d, uint32_t alo, uint32_t ahi, uint32_t blo, uint32_t bhi, int sd) {
  asm volatile("{ .reg .pred p; .reg .b64 da, db; mov.b64 da, {%72,%73}; mov.b64 db, {%74,%75}; setp.ne.b32 p, %76, 0;\n"
    "wgmma.mma_async.sync.aligned.m64n144k16.f32.bf16.bf16 {%0,%1,%2,%3,%4,%5,%6,%7,%8,%9,%10,%11,%12,%13,%14,%15,%16,%17,%18,%19,%20,%21,%22,%23,%24,%25,%26,%27,%28,%29,%30,%31,%32,%33,%34,%35,%36,%37,%38,%39,%40,%41,%42,%43,%44,%45,%46,%47,%48,%49,%50,%51,%52,%53,%54,%55,%56,%57,%58,%59,%60,%61,%62,%63,%64,%65,%66,%67,%68,%69,%70,%71}, da, db, p, 1, 1, %77, %78; }"
    : "+f"(d[0]),"+f"(d[1]),"+f"(d[2]),"+f"(d[3]),"+f"(d[4]),"+f"(d[5]),"+f"(d[6]),"+f"(d[7]),"+f"(d[8]),"+f"(d[9]),"+f"(d[10]),"+f"(d[11]),"+f"(d[12]),"+f"(d[13]),"+f"(d[14]),"+f"(d[15]),"+f"(d[16]),"+f"(d[17]),"+f"(d[18]),"+f"(d[19]),"+f"(d[20]),"+f"(d[21]),"+f"(d[22]),"+f"(d[23]),"+f"(d[24]),"+f"(d[25]),"+f"(d[26]),"+f"(d[27]),"+f"(d[28]),"+f"(d[29]),"+f"(d[30]),"+f"(d[31]),"+f"(d[32]),"+f"(d[33]),"+f"(d[34]),"+f"(d[35]),"+f"(d[36]),"+f"(d[37]),"+f"(d[38]),"+f"(d[39]),"+f"(d[40]),"+f"(d[41]),"+f"(d[42]),"+f"(d[43]),"+f"(d[44]),"+f"(d[45]),"+f"(d[46]),"+f"(d[47]),"+f"(d[48]),"+f"(d[49]),"+f"(d[50]),"+f"(d[51]),"+f"(d[52]),"+f"(d[53]),"+f"(d[54]),"+f"(d[55]),"+f"(d[56]),"+f"(d[57]),"+f"(d[58]),"+f"(d[59]),"+f"(d[60]),"+f"(d[61]),"+f"(d[62]),"+f"(d[63]),"+f"(d[64]),"+f"(d[65]),"+f"(d[66]),"+f"(d[67]),"+f"(d[68]),"+f"(d[69]),"+f"(d[70]),"+f"(d[71])
    : "r"(alo), "r"(ahi), "r"(blo), "r"(bhi), "r"(sd), "n"(TA), "n"(TB)); }
};
template<> struct WG<160> { template<int TA, int TB> static __device__ __forceinline__ void ss(float* d, uint32_t alo, uint32_t ahi, uint32_t blo, uint32_t bhi, int sd) {
  asm volatile("{ .reg .pred p; .reg .b64 da, db; mov.b64 da, {%80,%81}; mov.b64 db, {%82,%83}; setp.ne.b32 p, %84, 0;\n"
    "wgmma.mma_async.sync.aligned.m64n160k16.f32.bf16.bf16 {%0,%1,%2,%3,%4,%5,%6,%7,%8,%9,%10,%11,%12,%13,%14,%15,%16,%17,%18,%19,%20,%21,%22,%23,%24,%25,%26,%27,%28,%29,%30,%31,%32,%33,%34,%35,%36,%37,%38,%39,%40,%41,%42,%43,%44,%45,%46,%47,%48,%49,%50,%51,%52,%53,%54,%55,%56,%57,%58,%59,%60,%61,%62,%63,%64,%65,%66,%67,%68,%69,%70,%71,%72,%73,%74,%75,%76,%77,%78,%79}, da, db, p, 1, 1, %85, %86; }"
    : "+f"(d[0]),"+f"(d[1]),"+f"(d[2]),"+f"(d[3]),"+f"(d[4]),"+f"(d[5]),"+f"(d[6]),"+f"(d[7]),"+f"(d[8]),"+f"(d[9]),"+f"(d[10]),"+f"(d[11]),"+f"(d[12]),"+f"(d[13]),"+f"(d[14]),"+f"(d[15]),"+f"(d[16]),"+f"(d[17]),"+f"(d[18]),"+f"(d[19]),"+f"(d[20]),"+f"(d[21]),"+f"(d[22]),"+f"(d[23]),"+f"(d[24]),"+f"(d[25]),"+f"(d[26]),"+f"(d[27]),"+f"(d[28]),"+f"(d[29]),"+f"(d[30]),"+f"(d[31]),"+f"(d[32]),"+f"(d[33]),"+f"(d[34]),"+f"(d[35]),"+f"(d[36]),"+f"(d[37]),"+f"(d[38]),"+f"(d[39]),"+f"(d[40]),"+f"(d[41]),"+f"(d[42]),"+f"(d[43]),"+f"(d[44]),"+f"(d[45]),"+f"(d[46]),"+f"(d[47]),"+f"(d[48]),"+f"(d[49]),"+f"(d[50]),"+f"(d[51]),"+f"(d[52]),"+f"(d[53]),"+f"(d[54]),"+f"(d[55]),"+f"(d[56]),"+f"(d[57]),"+f"(d[58]),"+f"(d[59]),"+f"(d[60]),"+f"(d[61]),"+f"(d[62]),"+f"(d[63]),"+f"(d[64]),"+f"(d[65]),"+f"(d[66]),"+f"(d[67]),"+f"(d[68]),"+f"(d[69]),"+f"(d[70]),"+f"(d[71]),"+f"(d[72]),"+f"(d[73]),"+f"(d[74]),"+f"(d[75]),"+f"(d[76]),"+f"(d[77]),"+f"(d[78]),"+f"(d[79])
    : "r"(alo), "r"(ahi), "r"(blo), "r"(bhi), "r"(sd), "n"(TA), "n"(TB)); }
  template<int TB> static __device__ __forceinline__ void rs(float* d, uint32_t a0, uint32_t a1, uint32_t a2, uint32_t a3, uint32_t blo, uint32_t bhi, int sd) {
  asm volatile("{ .reg .pred p; .reg .b64 db; mov.b64 db, {%84,%85}; setp.ne.b32 p, %87, 0;\n"
    "wgmma.mma_async.sync.aligned.m64n160k16.f32.bf16.bf16 {%0,%1,%2,%3,%4,%5,%6,%7,%8,%9,%10,%11,%12,%13,%14,%15,%16,%17,%18,%19,%20,%21,%22,%23,%24,%25,%26,%27,%28,%29,%30,%31,%32,%33,%34,%35,%36,%37,%38,%39,%40,%41,%42,%43,%44,%45,%46,%47,%48,%49,%50,%51,%52,%53,%54,%55,%56,%57,%58,%59,%60,%61,%62,%63,%64,%65,%66,%67,%68,%69,%70,%71,%72,%73,%74,%75,%76,%77,%78,%79}, {%80,%81,%82,%83}, db, p, 1, 1, %86; }"
    : "+f"(d[0]),"+f"(d[1]),"+f"(d[2]),"+f"(d[3]),"+f"(d[4]),"+f"(d[5]),"+f"(d[6]),"+f"(d[7]),"+f"(d[8]),"+f"(d[9]),"+f"(d[10]),"+f"(d[11]),"+f"(d[12]),"+f"(d[13]),"+f"(d[14]),"+f"(d[15]),"+f"(d[16]),"+f"(d[17]),"+f"(d[18]),"+f"(d[19]),"+f"(d[20]),"+f"(d[21]),"+f"(d[22]),"+f"(d[23]),"+f"(d[24]),"+f"(d[25]),"+f"(d[26]),"+f"(d[27]),"+f"(d[28]),"+f"(d[29]),"+f"(d[30]),"+f"(d[31]),"+f"(d[32]),"+f"(d[33]),"+f"(d[34]),"+f"(d[35]),"+f"(d[36]),"+f"(d[37]),"+f"(d[38]),"+f"(d[39]),"+f"(d[40]),"+f"(d[41]),"+f"(d[42]),"+f"(d[43]),"+f"(d[44]),"+f"(d[45]),"+f"(d[46]),"+f"(d[47]),"+f"(d[48]),"+f"(d[49]),"+f"(d[50]),"+f"(d[51]),"+f"(d[52]),"+f"(d[53]),"+f"(d[54]),"+f"(d[55]),"+f"(d[56]),"+f"(d[57]),"+f"(d[58]),"+f"(d[59]),"+f"(d[60]),"+f"(d[61]),"+f"(d[62]),"+f"(d[63]),"+f"(d[64]),"+f"(d[65]),"+f"(d[66]),"+f"(d[67]),"+f"(d[68]),"+f"(d[69]),"+f"(d[70]),"+f"(d[71]),"+f"(d[72]),"+f"(d[73]),"+f"(d[74]),"+f"(d[75]),"+f"(d[76]),"+f"(d[77]),"+f"(d[78]),"+f"(d[79])
    : "r"(a0), "r"(a1), "r"(a2), "r"(a3), "r"(blo), "r"(bhi), "n"(TB), "r"(sd)); }
};
template<> struct WG<176> { template<int TA, int TB> static __device__ __forceinline__ void ss(float* d, uint32_t alo, uint32_t ahi, uint32_t blo, uint32_t bhi, int sd) {
  asm volatile("{ .reg .pred p; .reg .b64 da, db; mov.b64 da, {%88,%89}; mov.b64 db, {%90,%91}; setp.ne.b32 p, %92, 0;\n"
    "wgmma.mma_async.sync.aligned.m64n176k16.f32.bf16.bf16 {%0,%1,%2,%3,%4,%5,%6,%7,%8,%9,%10,%11,%12,%13,%14,%15,%16,%17,%18,%19,%20,%21,%22,%23,%24,%25,%26,%27,%28,%29,%30,%31,%32,%33,%34,%35,%36,%37,%38,%39,%40,%41,%42,%43,%44,%45,%46,%47,%48,%49,%50,%51,%52,%53,%54,%55,%56,%57,%58,%59,%60,%61,%62,%63,%64,%65,%66,%67,%68,%69,%70,%71,%72,%73,%74,%75,%76,%77,%78,%79,%80,%81,%82,%83,%84,%85,%86,%87}, da, db, p, 1, 1, %93, %94; }"
    : "+f"(d[0]),"+f"(d[1]),"+f"(d[2]),"+f"(d[3]),"+f"(d[4]),"+f"(d[5]),"+f"(d[6]),"+f"(d[7]),"+f"(d[8]),"+f"(d[9]),"+f"(d[10]),"+f"(d[11]),"+f"(d[12]),"+f"(d[13]),"+f"(d[14]),"+f"(d[15]),"+f"(d[16]),"+f"(d[17]),"+f"(d[18]),"+f"(d[19]),"+f"(d[20]),"+f"(d[21]),"+f"(d[22]),"+f"(d[23]),"+f"(d[24]),"+f"(d[25]),"+f"(d[26]),"+f"(d[27]),"+f"(d[28]),"+f"(d[29]),"+f"(d[30]),"+f"(d[31]),"+f"(d[32]),"+f"(d[33]),"+f"(d[34]),"+f"(d[35]),"+f"(d[36]),"+f"(d[37]),"+f"(d[38]),"+f"(d[39]),"+f"(d[40]),"+f"(d[41]),"+f"(d[42]),"+f"(d[43]),"+f"(d[44]),"+f"(d[45]),"+f"(d[46]),"+f"(d[47]),"+f"(d[48]),"+f"(d[49]),"+f"(d[50]),"+f"(d[51]),"+f"(d[52]),"+f"(d[53]),"+f"(d[54]),"+f"(d[55]),"+f"(d[56]),"+f"(d[57]),"+f"(d[58]),"+f"(d[59]),"+f"(d[60]),"+f"(d[61]),"+f"(d[62]),"+f"(d[63]),"+f"(d[64]),"+f"(d[65]),"+f"(d[66]),"+f"(d[67]),"+f"(d[68]),"+f"(d[69]),"+f"(d[70]),"+f"(d[71]),"+f"(d[72]),"+f"(d[73]),"+f"(d[74]),"+f"(d[75]),"+f"(d[76]),"+f"(d[77]),"+f"(d[78]),"+f"(d[79]),"+f"(d[80]),"+f"(d[81]),"+f"(d[82]),"+f"(d[83]),"+f"(d[84]),"+f"(d[85]),"+f"(d[86]),"+f"(d[87])
    : "r"(alo), "r"(ahi), "r"(blo), "r"(bhi), "r"(sd), "n"(TA), "n"(TB)); }
};
template<> struct WG<192> { template<int TA, int TB> static __device__ __forceinline__ void ss(float* d, uint32_t alo, uint32_t ahi, uint32_t blo, uint32_t bhi, int sd) {
  asm volatile("{ .reg .pred p; .reg .b64 da, db; mov.b64 da, {%96,%97}; mov.b64 db, {%98,%99}; setp.ne.b32 p, %100, 0;\n"
    "wgmma.mma_async.sync.aligned.m64n192k16.f32.bf16.bf16 {%0,%1,%2,%3,%4,%5,%6,%7,%8,%9,%10,%11,%12,%13,%14,%15,%16,%17,%18,%19,%20,%21,%22,%23,%24,%25,%26,%27,%28,%29,%30,%31,%32,%33,%34,%35,%36,%37,%38,%39,%40,%41,%42,%43,%44,%45,%46,%47,%48,%49,%50,%51,%52,%53,%54,%55,%56,%57,%58,%59,%60,%61,%62,%63,%64,%65,%66,%67,%68,%69,%70,%71,%72,%73,%74,%75,%76,%77,%78,%79,%80,%81,%82,%83,%84,%85,%86,%87,%88,%89,%90,%91,%92,%93,%94,%95}, da, db, p, 1, 1, %101, %102; }"
    : "+f"(d[0]),"+f"(d[1]),"+f"(d[2]),"+f"(d[3]),"+f"(d[4]),"+f"(d[5]),"+f"(d[6]),"+f"(d[7]),"+f"(d[8]),"+f"(d[9]),"+f"(d[10]),"+f"(d[11]),"+f"(d[12]),"+f"(d[13]),"+f"(d[14]),"+f"(d[15]),"+f"(d[16]),"+f"(d[17]),"+f"(d[18]),"+f"(d[19]),"+f"(d[20]),"+f"(d[21]),"+f"(d[22]),"+f"(d[23]),"+f"(d[24]),"+f"(d[25]),"+f"(d[26]),"+f"(d[27]),"+f"(d[28]),"+f"(d[29]),"+f"(d[30]),"+f"(d[31]),"+f"(d[32]),"+f"(d[33]),"+f"(d[34]),"+f"(d[35]),"+f"(d[36]),"+f"(d[37]),"+f"(d[38]),"+f"(d[39]),"+f"(d[40]),"+f"(d[41]),"+f"(d[42]),"+f"(d[43]),"+f"(d[44]),"+f"(d[45]),"+f"(d[46]),"+f"(d[47]),"+f"(d[48]),"+f"(d[49]),"+f"(d[50]),"+f"(d[51]),"+f"(d[52]),"+f"(d[53]),"+f"(d[54]),"+f"(d[55]),"+f"(d[56]),"+f"(d[57]),"+f"(d[58]),"+f"(d[59]),"+f"(d[60]),"+f"(d[61]),"+f"(d[62]),"+f"(d[63]),"+f"(d[64]),"+f"(d[65]),"+f"(d[66]),"+f"(d[67]),"+f"(d[68]),"+f"(d[69]),"+f"(d[70]),"+f"(d[71]),"+f"(d[72]),"+f"(d[73]),"+f"(d[74]),"+f"(d[75]),"+f"(d[76]),"+f"(d[77]),"+f"(d[78]),"+f"(d[79]),"+f"(d[80]),"+f"(d[81]),"+f"(d[82]),"+f"(d[83]),"+f"(d[84]),"+f"(d[85]),"+f"(d[86]),"+f"(d[87]),"+f"(d[88]),"+f"(d[89]),"+f"(d[90]),"+f"(d[91]),"+f"(d[92]),"+f"(d[93]),"+f"(d[94]),"+f"(d[95])
    : "r"(alo), "r"(ahi), "r"(blo), "r"(bhi), "r"(sd), "n"(TA), "n"(TB)); }
};
template<> struct WG<208> { template<int TA, int TB> static __device__ __forceinline__ void ss(float* d, uint32_t alo, uint32_t ahi, uint32_t blo, uint32_t bhi, int sd) {
  asm volatile("{ .reg .pred p; .reg .b64 da, db; mov.b64 da, {%104,%105}; mov.b64 db, {%106,%107}; setp.ne.b32 p, %108, 0;\n"
    "wgmma.mma_async.sync.aligned.m64n208k16.f32.bf16.bf16 {%0,%1,%2,%3,%4,%5,%6,%7,%8,%9,%10,%11,%12,%13,%14,%15,%16,%17,%18,%19,%20,%21,%22,%23,%24,%25,%26,%27,%28,%29,%30,%31,%32,%33,%34,%35,%36,%37,%38,%39,%40,%41,%42,%43,%44,%45,%46,%47,%48,%49,%50,%51,%52,%53,%54,%55,%56,%57,%58,%59,%60,%61,%62,%63,%64,%65,%66,%67,%68,%69,%70,%71,%72,%73,%74,%75,%76,%77,%78,%79,%80,%81,%82,%83,%84,%85,%86,%87,%88,%89,%90,%91,%92,%93,%94,%95,%96,%97,%98,%99,%100,%101,%102,%103}, da, db, p, 1, 1, %109, %110; }"
    : "+f"(d[0]),"+f"(d[1]),"+f"(d[2]),"+f"(d[3]),"+f"(d[4]),"+f"(d[5]),"+f"(d[6]),"+f"(d[7]),"+f"(d[8]),"+f"(d[9]),"+f"(d[10]),"+f"(d[11]),"+f"(d[12]),"+f"(d[13]),"+f"(d[14]),"+f"(d[15]),"+f"(d[16]),"+f"(d[17]),"+f"(d[18]),"+f"(d[19]),"+f"(d[20]),"+f"(d[21]),"+f"(d[22]),"+f"(d[23]),"+f"(d[24]),"+f"(d[25]),"+f"(d[26]),"+f"(d[27]),"+f"(d[28]),"+f"(d[29]),"+f"(d[30]),"+f"(d[31]),"+f"(d[32]),"+f"(d[33]),"+f"(d[34]),"+f"(d[35]),"+f"(d[36]),"+f"(d[37]),"+f"(d[38]),"+f"(d[39]),"+f"(d[40]),"+f"(d[41]),"+f"(d[42]),"+f"(d[43]),"+f"(d[44]),"+f"(d[45]),"+f"(d[46]),"+f"(d[47]),"+f"(d[48]),"+f"(d[49]),"+f"(d[50]),"+f"(d[51]),"+f"(d[52]),"+f"(d[53]),"+f"(d[54]),"+f"(d[55]),"+f"(d[56]),"+f"(d[57]),"+f"(d[58]),"+f"(d[59]),"+f"(d[60]),"+f"(d[61]),"+f"(d[62]),"+f"(d[63]),"+f"(d[64]),"+f"(d[65]),"+f"(d[66]),"+f"(d[67]),"+f"(d[68]),"+f"(d[69]),"+f"(d[70]),"+f"(d[71]),"+f"(d[72]),"+f"(d[73]),"+f"(d[74]),"+f"(d[75]),"+f"(d[76]),"+f"(d[77]),"+f"(d[78]),"+f"(d[79]),"+f"(d[80]),"+f"(d[81]),"+f"(d[82]),"+f"(d[83]),"+f"(d[84]),"+f"(d[85]),"+f"(d[86]),"+f"(d[87]),"+f"(d[88]),"+f"(d[89]),"+f"(d[90]),"+f"(d[91]),"+f"(d[92]),"+f"(d[93]),"+f"(d[94]),"+f"(d[95]),"+f"(d[96]),"+f"(d[97]),"+f"(d[98]),"+f"(d[99]),"+f"(d[100]),"+f"(d[101]),"+f"(d[102]),"+f"(d[103])
    : "r"(alo), "r"(ahi), "r"(blo), "r"(bhi), "r"(sd), "n"(TA), "n"(TB)); }
};
template<> struct WG<224> { template<int TA, int TB> static __device__ __forceinline__ void ss(float* d, uint32_t alo, uint32_t ahi, uint32_t blo, uint32_t bhi, int sd) {
  asm volatile("{ .reg .pred p; .reg .b64 da, db; mov.b64 da, {%112,%113}; mov.b64 db, {%114,%115}; setp.ne.b32 p, %116, 0;\n"
    "wgmma.mma_async.sync.aligned.m64n224k16.f32.bf16.bf16 {%0,%1,%2,%3,%4,%5,%6,%7,%8,%9,%10,%11,%12,%13,%14,%15,%16,%17,%18,%19,%20,%21,%22,%23,%24,%25,%26,%27,%28,%29,%30,%31,%32,%33,%34,%35,%36,%37,%38,%39,%40,%41,%42,%43,%44,%45,%46,%47,%48,%49,%50,%51,%52,%53,%54,%55,%56,%57,%58,%59,%60,%61,%62,%63,%64,%65,%66,%67,%68,%69,%70,%71,%72,%73,%74,%75,%76,%77,%78,%79,%80,%81,%82,%83,%84,%85,%86,%87,%88,%89,%90,%91,%92,%93,%94,%95,%96,%97,%98,%99,%100,%101,%102,%103,%104,%105,%106,%107,%108,%109,%110,%111}, da, db, p, 1, 1, %117, %118; }"
    : "+f"(d[0]),"+f"(d[1]),"+f"(d[2]),"+f"(d[3]),"+f"(d[4]),"+f"(d[5]),"+f"(d[6]),"+f"(d[7]),"+f"(d[8]),"+f"(d[9]),"+f"(d[10]),"+f"(d[11]),"+f"(d[12]),"+f"(d[13]),"+f"(d[14]),"+f"(d[15]),"+f"(d[16]),"+f"(d[17]),"+f"(d[18]),"+f"(d[19]),"+f"(d[20]),"+f"(d[21]),"+f"(d[22]),"+f"(d[23]),"+f"(d[24]),"+f"(d[25]),"+f"(d[26]),"+f"(d[27]),"+f"(d[28]),"+f"(d[29]),"+f"(d[30]),"+f"(d[31]),"+f"(d[32]),"+f"(d[33]),"+f"(d[34]),"+f"(d[35]),"+f"(d[36]),"+f"(d[37]),"+f"(d[38]),"+f"(d[39]),"+f"(d[40]),"+f"(d[41]),"+f"(d[42]),"+f"(d[43]),"+f"(d[44]),"+f"(d[45]),"+f"(d[46]),"+f"(d[47]),"+f"(d[48]),"+f"(d[49]),"+f"(d[50]),"+f"(d[51]),"+f"(d[52]),"+f"(d[53]),"+f"(d[54]),"+f"(d[55]),"+f"(d[56]),"+f"(d[57]),"+f"(d[58]),"+f"(d[59]),"+f"(d[60]),"+f"(d[61]),"+f"(d[62]),"+f"(d[63]),"+f"(d[64]),"+f"(d[65]),"+f"(d[66]),"+f"(d[67]),"+f"(d[68]),"+f"(d[69]),"+f"(d[70]),"+f"(d[71]),"+f"(d[72]),"+f"(d[73]),"+f"(d[74]),"+f"(d[75]),"+f"(d[76]),"+f"(d[77]),"+f"(d[78]),"+f"(d[79]),"+f"(d[80]),"+f"(d[81]),"+f"(d[82]),"+f"(d[83]),"+f"(d[84]),"+f"(d[85]),"+f"(d[86]),"+f"(d[87]),"+f"(d[88]),"+f"(d[89]),"+f"(d[90]),"+f"(d[91]),"+f"(d[92]),"+f"(d[93]),"+f"(d[94]),"+f"(d[95]),"+f"(d[96]),"+f"(d[97]),"+f"(d[98]),"+f"(d[99]),"+f"(d[100]),"+f"(d[101]),"+f"(d[102]),"+f"(d[103]),"+f"(d[104]),"+f"(d[105]),"+f"(d[106]),"+f"(d[107]),"+f"(d[108]),"+f"(d[109]),"+f"(d[110]),"+f"(d[111])
    : "r"(alo), "r"(ahi), "r"(blo), "r"(bhi), "r"(sd), "n"(TA), "n"(TB)); }
};
template<> struct WG<240> { template<int TA, int TB> static __device__ __forceinline__ void ss(float* d, uint32_t alo, uint32_t ahi, uint32_t blo, uint32_t bhi, int sd) {
  asm volatile("{ .reg .pred p; .reg .b64 da, db; mov.b64 da, {%120,%121}; mov.b64 db, {%122,%123}; setp.ne.b32 p, %124, 0;\n"
    "wgmma.mma_async.sync.aligned.m64n240k16.f32.bf16.bf16 {%0,%1,%2,%3,%4,%5,%6,%7,%8,%9,%10,%11,%12,%13,%14,%15,%16,%17,%18,%19,%20,%21,%22,%23,%24,%25,%26,%27,%28,%29,%30,%31,%32,%33,%34,%35,%36,%37,%38,%39,%40,%41,%42,%43,%44,%45,%46,%47,%48,%49,%50,%51,%52,%53,%54,%55,%56,%57,%58,%59,%60,%61,%62,%63,%64,%65,%66,%67,%68,%69,%70,%71,%72,%73,%74,%75,%76,%77,%78,%79,%80,%81,%82,%83,%84,%85,%86,%87,%88,%89,%90,%91,%92,%93,%94,%95,%96,%97,%98,%99,%100,%101,%102,%103,%104,%105,%106,%107,%108,%109,%110,%111,%112,%113,%114,%115,%116,%117,%118,%119}, da, db, p, 1, 1, %125, %126; }"
    : "+f"(d[0]),"+f"(d[1]),"+f"(d[2]),"+f"(d[3]),"+f"(d[4]),"+f"(d[5]),"+f"(d[6]),"+f"(d[7]),"+f"(d[8]),"+f"(d[9]),"+f"(d[10]),"+f"(d[11]),"+f"(d[12]),"+f"(d[13]),"+f"(d[14]),"+f"(d[15]),"+f"(d[16]),"+f"(d[17]),"+f"(d[18]),"+f"(d[19]),"+f"(d[20]),"+f"(d[21]),"+f"(d[22]),"+f"(d[23]),"+f"(d[24]),"+f"(d[25]),"+f"(d[26]),"+f"(d[27]),"+f"(d[28]),"+f"(d[29]),"+f"(d[30]),"+f"(d[31]),"+f"(d[32]),"+f"(d[33]),"+f"(d[34]),"+f"(d[35]),"+f"(d[36]),"+f"(d[37]),"+f"(d[38]),"+f"(d[39]),"+f"(d[40]),"+f"(d[41]),"+f"(d[42]),"+f"(d[43]),"+f"(d[44]),"+f"(d[45]),"+f"(d[46]),"+f"(d[47]),"+f"(d[48]),"+f"(d[49]),"+f"(d[50]),"+f"(d[51]),"+f"(d[52]),"+f"(d[53]),"+f"(d[54]),"+f"(d[55]),"+f"(d[56]),"+f"(d[57]),"+f"(d[58]),"+f"(d[59]),"+f"(d[60]),"+f"(d[61]),"+f"(d[62]),"+f"(d[63]),"+f"(d[64]),"+f"(d[65]),"+f"(d[66]),"+f"(d[67]),"+f"(d[68]),"+f"(d[69]),"+f"(d[70]),"+f"(d[71]),"+f"(d[72]),"+f"(d[73]),"+f"(d[74]),"+f"(d[75]),"+f"(d[76]),"+f"(d[77]),"+f"(d[78]),"+f"(d[79]),"+f"(d[80]),"+f"(d[81]),"+f"(d[82]),"+f"(d[83]),"+f"(d[84]),"+f"(d[85]),"+f"(d[86]),"+f"(d[87]),"+f"(d[88]),"+f"(d[89]),"+f"(d[90]),"+f"(d[91]),"+f"(d[92]),"+f"(d[93]),"+f"(d[94]),"+f"(d[95]),"+f"(d[96]),"+f"(d[97]),"+f"(d[98]),"+f"(d[99]),"+f"(d[100]),"+f"(d[101]),"+f"(d[102]),"+f"(d[103]),"+f"(d[104]),"+f"(d[105]),"+f"(d[106]),"+f"(d[107]),"+f"(d[108]),"+f"(d[109]),"+f"(d[110]),"+f"(d[111]),"+f"(d[112]),"+f"(d[113]),"+f"(d[114]),"+f"(d[115]),"+f"(d[116]),"+f"(d[117]),"+f"(d[118]),"+f"(d[119])
    : "r"(alo), "r"(ahi), "r"(blo), "r"(bhi), "r"(sd), "n"(TA), "n"(TB)); }
};
template<> struct WG<256> { template<int TA, int TB> static __device__ __forceinline__ void ss(float* d, uint32_t alo, uint32_t ahi, uint32_t blo, uint32_t bhi, int sd) {
  asm volatile("{ .reg .pred p; .reg .b64 da, db; mov.b64 da, {%128,%129}; mov.b64 db, {%130,%131}; setp.ne.b32 p, %132, 0;\n"
    "wgmma.mma_async.sync.aligned.m64n256k16.f32.bf16.bf16 {%0,%1,%2,%3,%4,%5,%6,%7,%8,%9,%10,%11,%12,%13,%14,%15,%16,%17,%18,%19,%20,%21,%22,%23,%24,%25,%26,%27,%28,%29,%30,%31,%32,%33,%34,%35,%36,%37,%38,%39,%40,%41,%42,%43,%44,%45,%46,%47,%48,%49,%50,%51,%52,%53,%54,%55,%56,%57,%58,%59,%60,%61,%62,%63,%64,%65,%66,%67,%68,%69,%70,%71,%72,%73,%74,%75,%76,%77,%78,%79,%80,%81,%82,%83,%84,%85,%86,%87,%88,%89,%90,%91,%92,%93,%94,%95,%96,%97,%98,%99,%100,%101,%102,%103,%104,%105,%106,%107,%108,%109,%110,%111,%112,%113,%114,%115,%116,%117,%118,%119,%120,%121,%122,%123,%124,%125,%126,%127}, da, db, p, 1, 1, %133, %134; }"
    : "+f"(d[0]),"+f"(d[1]),"+f"(d[2]),"+f"(d[3]),"+f"(d[4]),"+f"(d[5]),"+f"(d[6]),"+f"(d[7]),"+f"(d[8]),"+f"(d[9]),"+f"(d[10]),"+f"(d[11]),"+f"(d[12]),"+f"(d[13]),"+f"(d[14]),"+f"(d[15]),"+f"(d[16]),"+f"(d[17]),"+f"(d[18]),"+f"(d[19]),"+f"(d[20]),"+f"(d[21]),"+f"(d[22]),"+f"(d[23]),"+f"(d[24]),"+f"(d[25]),"+f"(d[26]),"+f"(d[27]),"+f"(d[28]),"+f"(d[29]),"+f"(d[30]),"+f"(d[31]),"+f"(d[32]),"+f"(d[33]),"+f"(d[34]),"+f"(d[35]),"+f"(d[36]),"+f"(d[37]),"+f"(d[38]),"+f"(d[39]),"+f"(d[40]),"+f"(d[41]),"+f"(d[42]),"+f"(d[43]),"+f"(d[44]),"+f"(d[45]),"+f"(d[46]),"+f"(d[47]),"+f"(d[48]),"+f"(d[49]),"+f"(d[50]),"+f"(d[51]),"+f"(d[52]),"+f"(d[53]),"+f"(d[54]),"+f"(d[55]),"+f"(d[56]),"+f"(d[57]),"+f"(d[58]),"+f"(d[59]),"+f"(d[60]),"+f"(d[61]),"+f"(d[62]),"+f"(d[63]),"+f"(d[64]),"+f"(d[65]),"+f"(d[66]),"+f"(d[67]),"+f"(d[68]),"+f"(d[69]),"+f"(d[70]),"+f"(d[71]),"+f"(d[72]),"+f"(d[73]),"+f"(d[74]),"+f"(d[75]),"+f"(d[76]),"+f"(d[77]),"+f"(d[78]),"+f"(d[79]),"+f"(d[80]),"+f"(d[81]),"+f"(d[82]),"+f"(d[83]),"+f"(d[84]),"+f"(d[85]),"+f"(d[86]),"+f"(d[87]),"+f"(d[88]),"+f"(d[89]),"+f"(d[90]),"+f"(d[91]),"+f"(d[92]),"+f"(d[93]),"+f"(d[94]),"+f"(d[95]),"+f"(d[96]),"+f"(d[97]),"+f"(d[98]),"+f"(d[99]),"+f"(d[100]),"+f"(d[101]),"+f"(d[102]),"+f"(d[103]),"+f"(d[104]),"+f"(d[105]),"+f"(d[106]),"+f"(d[107]),"+f"(d[108]),"+f"(d[109]),"+f"(d[110]),"+f"(d[111]),"+f"(d[112]),"+f"(d[113]),"+f"(d[114]),"+f"(d[115]),"+f"(d[116]),"+f"(d[117]),"+f"(d[118]),"+f"(d[119]),"+f"(d[120]),"+f"(d[121]),"+f"(d[122]),"+f"(d[123]),"+f"(d[124]),"+f"(d[125]),"+f"(d[126]),"+f"(d[127])
    : "r"(alo), "r"(ahi), "r"(blo), "r"(bhi), "r"(sd), "n"(TA), "n"(TB)); }
  template<int TB> static __device__ __forceinline__ void rs(float* d, uint32_t a0, uint32_t a1, uint32_t a2, uint32_t a3, uint32_t blo, uint32_t bhi, int sd) {
  asm volatile("{ .reg .pred p; .reg .b64 db; mov.b64 db, {%132,%133}; setp.ne.b32 p, %135, 0;\n"
    "wgmma.mma_async.sync.aligned.m64n256k16.f32.bf16.bf16 {%0,%1,%2,%3,%4,%5,%6,%7,%8,%9,%10,%11,%12,%13,%14,%15,%16,%17,%18,%19,%20,%21,%22,%23,%24,%25,%26,%27,%28,%29,%30,%31,%32,%33,%34,%35,%36,%37,%38,%39,%40,%41,%42,%43,%44,%45,%46,%47,%48,%49,%50,%51,%52,%53,%54,%55,%56,%57,%58,%59,%60,%61,%62,%63,%64,%65,%66,%67,%68,%69,%70,%71,%72,%73,%74,%75,%76,%77,%78,%79,%80,%81,%82,%83,%84,%85,%86,%87,%88,%89,%90,%91,%92,%93,%94,%95,%96,%97,%98,%99,%100,%101,%102,%103,%104,%105,%106,%107,%108,%109,%110,%111,%112,%113,%114,%115,%116,%117,%118,%119,%120,%121,%122,%123,%124,%125,%126,%127}, {%128,%129,%130,%131}, db, p, 1, 1, %134; }"
    : "+f"(d[0]),"+f"(d[1]),"+f"(d[2]),"+f"(d[3]),"+f"(d[4]),"+f"(d[5]),"+f"(d[6]),"+f"(d[7]),"+f"(d[8]),"+f"(d[9]),"+f"(d[10]),"+f"(d[11]),"+f"(d[12]),"+f"(d[13]),"+f"(d[14]),"+f"(d[15]),"+f"(d[16]),"+f"(d[17]),"+f"(d[18]),"+f"(d[19]),"+f"(d[20]),"+f"(d[21]),"+f"(d[22]),"+f"(d[23]),"+f"(d[24]),"+f"(d[25]),"+f"(d[26]),"+f"(d[27]),"+f"(d[28]),"+f"(d[29]),"+f"(d[30]),"+f"(d[31]),"+f"(d[32]),"+f"(d[33]),"+f"(d[34]),"+f"(d[35]),"+f"(d[36]),"+f"(d[37]),"+f"(d[38]),"+f"(d[39]),"+f"(d[40]),"+f"(d[41]),"+f"(d[42]),"+f"(d[43]),"+f"(d[44]),"+f"(d[45]),"+f"(d[46]),"+f"(d[47]),"+f"(d[48]),"+f"(d[49]),"+f"(d[50]),"+f"(d[51]),"+f"(d[52]),"+f"(d[53]),"+f"(d[54]),"+f"(d[55]),"+f"(d[56]),"+f"(d[57]),"+f"(d[58]),"+f"(d[59]),"+f"(d[60]),"+f"(d[61]),"+f"(d[62]),"+f"(d[63]),"+f"(d[64]),"+f"(d[65]),"+f"(d[66]),"+f"(d[67]),"+f"(d[68]),"+f"(d[69]),"+f"(d[70]),"+f"(d[71]),"+f"(d[72]),"+f"(d[73]),"+f"(d[74]),"+f"(d[75]),"+f"(d[76]),"+f"(d[77]),"+f"(d[78]),"+f"(d[79]),"+f"(d[80]),"+f"(d[81]),"+f"(d[82]),"+f"(d[83]),"+f"(d[84]),"+f"(d[85]),"+f"(d[86]),"+f"(d[87]),"+f"(d[88]),"+f"(d[89]),"+f"(d[90]),"+f"(d[91]),"+f"(d[92]),"+f"(d[93]),"+f"(d[94]),"+f"(d[95]),"+f"(d[96]),"+f"(d[97]),"+f"(d[98]),"+f"(d[99]),"+f"(d[100]),"+f"(d[101]),"+f"(d[102]),"+f"(d[103]),"+f"(d[104]),"+f"(d[105]),"+f"(d[106]),"+f"(d[107]),"+f"(d[108]),"+f"(d[109]),"+f"(d[110]),"+f"(d[111]),"+f"(d[112]),"+f"(d[113]),"+f"(d[114]),"+f"(d[115]),"+f"(d[116]),"+f"(d[117]),"+f"(d[118]),"+f"(d[119]),"+f"(d[120]),"+f"(d[121]),"+f"(d[122]),"+f"(d[123]),"+f"(d[124]),"+f"(d[125]),"+f"(d[126]),"+f"(d[127])
    : "r"(a0), "r"(a1), "r"(a2), "r"(a3), "r"(blo), "r"(bhi), "n"(TB), "r"(sd)); }
};

template<int T> struct Conv {
    static __device__ __forceinline__ void run(float* acc, uint32_t da, uint32_t db) {
        WG<256 - 16 * T>::template ss<0, 0>(acc, da + (T >> 2) * 512 + (T & 3) * 2, dhi(1024, 1), db + T * 16, dhi(128, 0), T != 0);
        Conv<T + 1>::run(acc, da, db);
    }
};
template<> struct Conv<16> { static __device__ __forceinline__ void run(float*, uint32_t, uint32_t) {} };

template<int Q> __device__ __forceinline__ void ffn_epi(const float* g, const float* u, uint32_t* hq, char* dst, uint32_t tm, uint32_t par, float rq0, float rq1) {
    constexpr int U = Q >> 2, i = 4 * Q;
    uint32_t* o = hq + 8 * U;
    o[Q & 3] = hmul2(pack2relu(g[i], g[i + 1]), RQE == 1 ? pack2(u[i] * rq0, u[i + 1] * rq0) : pack2(u[i], u[i + 1]));
    o[4 + (Q & 3)] = hmul2(pack2relu(g[i + 2], g[i + 3]), RQE == 1 ? pack2(u[i + 2] * rq1, u[i + 3] * rq1) : pack2(u[i + 2], u[i + 3]));
    asm volatile("" : "+r"(o[Q & 3]), "+r"(o[4 + (Q & 3)]) :: "memory");
    if ((Q & 3) == 0) {
        stg_tag<0>(dst + U * 8192, o, tm, par);
        stg_tag<1>(dst + U * 8192 + 512, o + 4, tm, par);
    }
}
__device__ __forceinline__ uint32_t tagged(float x, uint32_t tag) { return (__float_as_uint(x) & ~7u) | (tag & 7u); }
__device__ __forceinline__ uint32_t split2(float x) { const float h = bfround(x); return pack2(h, x - h); }
__device__ __forceinline__ float rsqrt_(float x) { float r; asm("rsqrt.approx.ftz.f32 %0, %1;" : "=f"(r) : "f"(x)); return r; }
__device__ __forceinline__ void acc_stat(float& s, float& q, uint32_t w) { const float a = bflo(w), c = bfhi(w); s += a; q = fmaf(a, a, q); s += c; q = fmaf(c, c, q); }
template<int I, int N, typename F> __device__ __forceinline__ void static_for(F&& f) {
    if constexpr (I < N) { f(std::integral_constant<int, I>{}); static_for<I + 1, N>(f); }
}

__device__ __forceinline__ int mod_col(int i, int s) {
    const int g = 4 * i + s - 40;
    return i < 10 ? ((s & 1) ? 1280 + 1280 * (i & 1) : 640 * (i & 1)) + (i >> 1) * 128 + (s >> 1) * 64 : (g < 10 ? 1920 : 2560) + g * 64;
}
__device__ __forceinline__ uint32_t silu2(uint32_t w) {
    const float a0 = bflo(w), a1 = bfhi(w);
    return pack2(__fdividef(a0, 1.f + __expf(-a0)), __fdividef(a1, 1.f + __expf(-a1)));
}

struct Maps { CUtensorMap k, v, q, y, g1, u1, g2, u2, wd, wn, wm, wp, out; };
struct Ptrs { const char *k, *v, *shift, *ssm, *ssmD; char *scr, *out; const char *c, *Wg, *Wu, *Wd;
};

__global__ void __cluster_dims__(2, 1, 1) __launch_bounds__(384, 1)
fused_kernel(const __grid_constant__ Ptrs P, const __grid_constant__ Maps M) {
    extern __shared__ __align__(1024) char smraw[];
    const uint32_t clk0 = clock32();
    const uint32_t sb = smem_u32(smraw);
    const int tid = threadIdx.x, b = blockIdx.x;
    #define BAR(i) (sb + BARS + 8 * (i))
    if (tid < 256 && b < 128) {
        const uint32_t rv = tid >> 3, c = (tid ^ rv) & 7, rk = rv + 2 + 2 * (rv >> 3);
        const uint32_t go = ((b >> 1) * 32 + (rv & 6) * 4 + 2 * (rv >> 3) + (rv & 1)) * 1280 + (b & 1) * 128 + c * 16;
        cp16(sb + st_kv(0) + 5120 + tid * 16, padd(P.v, go));
        cp16(sb + st_kv(0) + rk * 128 + (((c ^ rk) & 7) << 4), padd(P.k, go));
        sched_bar();
        if ((rv & 22) == 16)
            asm volatile("cp.async.cg.shared.global [%0], [%1], 16, %2;" :: "r"(sb + st_kv(0) + (rk - 2) * 128 + (((c ^ (rk - 2)) & 7) << 4)), "l"(padd(P.k, b < 2 ? go : go - 10240)), "r"(b < 2 ? 0 : 16) : "memory");
        if (tid < 160) cp16(sb + ST_SH + tid * 16, padd(P.shift, (tid >> 5) * 512 + (b & 1) * 512 + tid * 16));
        asm volatile("cp.async.commit_group;" ::: "memory");
    }
    const int warp = __shfl_sync(~0u, tid >> 5, 0), lane = tid & 31;
    const int rank = b & 1, cl = b >> 1;
    #define FFN_ROLE int cl_ = cl; asm volatile("pmevent 1;" : "+r"(cl_)); const int cu = cl_ - 36, cv = (cu * 37) >> 8, \
        gp_ = cl_ < 4 ? 0 : cl_ < 36 ? (cl_ - 4) & 7 : 1 + cu - 7 * cv, gi_ = cl_ < 4 ? 4 + cl_ : cl_ < 36 ? (cl_ - 4) >> 3 : 4 + cv, \
        grp = MAPM == 0 ? gp_ : MAPM == 1 ? (gp_ & 6) + (gi_ >> 2) : MAPM == 2 ? (gp_ & 6) + (gi_ & 1) : MAPM == 3 ? (gp_ & 4) + (gi_ & 3) : gi_, \
        js = MAPM == 0 ? gi_ : MAPM == 1 ? 4 * (gp_ & 1) + (gi_ & 3) : MAPM == 2 ? 4 * (gp_ & 1) + (gi_ >> 1) : MAPM == 3 ? 2 * (gp_ & 3) + (gi_ >> 2) : gp_, tile = 2 * grp + rank, dq = js & 3
    #define CNT(l, w) SC(cnt, (l) * 4096 + (w) * 4)
    uint32_t epoch = 0;

    if (b >= 128) {
        if (warp == 11) {
            if (elect()) {
                _Pragma("unroll") for (int i = 0; i < 25; i++) mbar_init(BAR(i), i < 10 || i >= 20 ? 1 : 4);
                asm volatile("fence.mbarrier_init.release.cluster;" ::: "memory");
                fence_async_smem();
                pf_map(&M.wm);
            }
            __syncwarp();
            asm volatile("barrier.cluster.arrive.relaxed.aligned;" ::: "memory");
            bar_arrive(0, 384);
        } else {
            epoch = ldg_late(CNT(C_Z, 6), lane);
            if (tid < 320) sts32(sb + 204800 + tid * 4, silu2(__ldg((const uint32_t*)P.c + tid)));
            fence_async_smem();
            __syncwarp();
            asm volatile("barrier.cluster.arrive.relaxed.aligned;\n barrier.cluster.wait.aligned;" ::: "memory");
            bar_sync(0, 384);
            STAMPIF(warp == 0, 7);
        }
        if (warp == 11) {
            if (elect()) {
                wait_clock(clk0, D_SP);
                int s0 = 0, ph0 = 1;
                _Pragma("unroll 1") for (int i = 0; i < 15; i++) {
                    const int col = mod_col(i, b - 128);
                    int s = s0, ph = ph0;
                    _Pragma("unroll 1") for (int j = 0; j < 4; j++) {
                        const int sl = (i & 1) * 5 + s;
                        mbar_wait(BAR(10 + sl), ph);
                        mbar_expect(BAR(sl), 20480);
                        tma2d(sb + sl * 20480, &M.wm, col, j * 160, BAR(sl));
                        if (++s == 5) { s = 0; ph ^= 1; }
                    }
                    if (i & 1) { s0 = s; ph0 = ph; }
                }
            }
        } else if (warp == 9 && !rank) {
            epoch = (__shfl_sync(~0u, epoch, 0) >> 7) + 1;
            _Pragma("unroll 1") for (int r = 0; r < 5; r++) {
                if (lane == 0) mbar_expect(BAR(20 + r), 512);
                mbar_wait(BAR(20 + r), 0);
                uint32_t v[4];
                #pragma unroll
                for (int k = 0; k < 4; k++) asm volatile("ld.shared.b32 %0, [%1];" : "=r"(v[k]) : "r"(sb + 206336 + r * 512 + k * 128 + (lane & 16) * 4 + (lane & 3) * 16 + (lane & 12)) : "memory");
                stg_rlx128(SC(abc, (r * 64 + (b - 128) * 16 + lane) * 16), hmul2(v[2], hadd2(v[1], 0x3f803f80u)), hmul2(v[2], v[0]), hadd2(v[3], 0x3f803f80u), epoch);
                STAMP(1 + r);
            }
        } else if (warp < 8) {
            const int wg = warp >> 2;
            epoch = (__shfl_sync(~0u, epoch, 0) >> 7) + 1;
            int s = 0, ph = 0;
            _Pragma("unroll 1") for (int i = wg; i < 15; i += 2) {
                float ac5[20];
                uint32_t prev = 0;
                _Pragma("unroll 1") for (int j = 0; j < 4; j++) {
                    const int sl = wg * 5 + s;
                    mbar_wait(BAR(sl), ph);
                    wg_fence();
                    const uint32_t da = dlo(sb + sl * 20480, 16), db = dlo(sb + 204800 + j * 320, 16);
                    #pragma unroll
                    for (int ks = 0; ks < 10; ks++) WG<8>::ss<1, 0>(ac5 + 4 * (ks % 5), da + ks * 128, dhi(1024, 1), db + ks * 2, dhi(128, 0), ks >= 5 || j != 0);
                    wg_commit();
                    wg_wait<1>();
                    mbar_arrive_if(prev, lane == 0 && j);
                    prev = BAR(10 + sl);
                    if (++s == 5) { s = 0; ph ^= 1; }
                }
                wg_wait<0>();
                pin<20>(ac5);
                mbar_arrive_if(prev, lane == 0);
                const float acc[3] = {ac5[0] + ac5[4] + ac5[8] + ac5[12] + ac5[16], 0.f, ac5[2] + ac5[6] + ac5[10] + ac5[14] + ac5[18]};
                const uint32_t m0 = pack2(acc[0], __shfl_down_sync(~0u, acc[0], 4)), m1 = pack2(acc[2], __shfl_down_sync(~0u, acc[2], 4));
                if (i < 10) {
                    if ((lane & 7) == 0)
                        asm volatile("{ .reg .u32 a, m; mapa.shared::cluster.u32 a, %0, 0; mapa.shared::cluster.u32 m, %1, 0; \n"
                                     " st.async.shared::cluster.mbarrier::complete_tx::bytes.b32 [a], %2, [m]; st.async.shared::cluster.mbarrier::complete_tx::bytes.b32 [a+16], %3, [m]; }"
                                     :: "r"(sb + 206336 + (i >> 1) * 512 + rank * 256 + warp * 32 + (lane >> 3) * 4), "r"(BAR(20 + (i >> 1))), "r"(m0), "r"(m1) : "memory");
                } else if ((lane & 7) == 0) {
                    char* mp = SC(mod, ((4 * i + b - 168) * 64 + (warp & 3) * 16 + (lane >> 2)) * 4);
                    asm volatile("{ .reg .b64 x; mov.b64 x, {%1, %3}; st.relaxed.gpu.global.b64 [%0], x; mov.b64 x, {%2, %3}; st.relaxed.gpu.global.b64 [%0+32], x; }" :: "l"(mp), "r"(m0), "r"(m1), "r"(epoch) : "memory");
                }
                STAMPIF(warp == 0 && i == 12, 6); STAMPIF(warp == 0 && i == 0, 8);
            }
        }
        return;
    }

    const bool l0 = lane == 0;
    const int q = lane & 3, rr = lane >> 2;

    if (warp < 8) {
        const int wg = warp >> 2, w = warp & 3, t = tid & 127;
        if (t < 5) sts128(wg ? sb + XB + (t & 1) * XP + 4096 : sb + eslot(t), 0, 0, 0, 0);
        bar_sync(0, 384);
        asm volatile("barrier.cluster.arrive.relaxed.aligned;" ::: "memory");
        STAMPIF(warp == 0, 1);
        uint32_t dv = 0;
        if (t < 5) asm volatile("ld.global.nc.u16 %0, [%1];" : "=r"(dv) : "l"(padd(P.ssmD, (b + 128 * t) * 2)));
        FFN_ROLE;
        epoch = ldg_late(CNT(C_Z + tile, 6), lane);
        asm volatile("cp.async.wait_group 0;" ::: "memory");
        bar_sync(2, 256);
        mbar_arrive_if(BAR(B_KV), tid == 0);
        epoch = (__shfl_sync(~0u, epoch, 0) >> 7) + 1;
        asm volatile("barrier.cluster.wait.aligned;" ::: "memory");
        uint32_t g2e;
        asm("mapa.shared::cluster.u32 %0, %1, %2;" : "=r"(g2e) : "r"(BAR(B_G2E)), "r"(rank ^ (lane & 1)));
        const bool l01 = lane < 2;
        const uint32_t wre = g2e - 8 * (B_G2E - B_WE);
        {
            const uint32_t par = epoch & 1, xa = sb + XB + wg * XP;
            const char* gp = SC(kvT, (b + 128 * wg) * 4096 + t * 16);
            if (wg) bar_arrive(1, 256);
            auto krow = [&](int o) { const int tk = 39 - 8 * ((lane & 7) >> 1) - o, ro = (tk & 1) + 2 * (tk >> 3) + 10 * ((tk >> 1) & 3); return sb + ro * 128 + (((ro & 7) ^ (2 * w)) << 4); };
            const int o0 = 2 * (lane >> 3) + (lane & 1);
            const int tv = 31 - 8 * ((lane & 7) >> 1) - o0, rv = (tv & 1) + 2 * (tv >> 3) + 8 * ((tv >> 1) & 3);
            uint32_t aE = krow(o0), aH = krow(8 + (o0 & 3)), aV = sb + 5120 + rv * 128 + (((rv & 7) ^ (2 * w)) << 4);
            uint32_t tdo = (rank * 64 + w * 16 + rr) * 4096 + (252 - 4 * cl + q) * 16;
            asm volatile("" : "+r"(aE), "+r"(aH), "+r"(aV), "+r"(tdo));
            _Pragma("unroll 1") for (unsigned long long steps = wg ? SEQ1 : SEQ0; steps; steps >>= 8) {
                const int r = steps & 7;
                STAMPS(0);
                if (steps & 0x40) {
                    const uint32_t so = st_kv(r);
                    const char *dst = SC(kvT, tdo + r * 524288), *hc = CNT(C_KV + 2 * r + rank, t);
                    mbar_wait(BAR(B_KV + r), 0);
                    STAMPIF(w == 1 && (r & 3) == 0, 35 + r); STAMPS(1);
                    red_if(hc, 2, t == 0 && ((EARLYH >> r) & 1));
                    uint2 sw[2]; uint32_t ke[2][6], vv[2][4], o[2][4];
                    #pragma unroll
                    for (int u = 0; u < 2; u++) {
                        sw[u] = lds64(sb + ST_SH + r * 512 + w * 128 + rr * 8 + u * 64);
                        ldsm4t(ke[u], (aE ^ (u << 4)) + so); ldsm2t(ke[u][4], ke[u][5], (aH ^ (u << 4)) + so); ldsm4t(vv[u], (aV ^ (u << 4)) + so);
                    }
                    sched_bar();
                    #pragma unroll
                    for (int u = 0; u < 2; u++) {
                        uint32_t ko[5];
                        #pragma unroll
                        for (int j = 0; j < 5; j++) ko[j] = prmt(ke[u][j], ke[u][j + 1], 0x5432);
                        #pragma unroll
                        for (int j = 0; j < 4; j++) o[u][j] = hmul2(hfma2s<0>(ke[u][j], sw[u].x, hfma2s<1>(ko[j], sw[u].x, hfma2s<0>(ke[u][j + 1], sw[u].y, hfma2s<1>(ko[j + 1], sw[u].y, 0x80008000u)))), vv[u][j]);
                        o[u][0] = (o[u][0] & ~1u) | par;
                    }
                    asm volatile("{ .reg .pred h; setp.ne.b32 h, %10, 0; pmevent 1;\n @h red.relaxed.gpu.global.add.u32 [%9], 2;\n"
                                 " st.relaxed.gpu.global.v4.b32 [%0], {%1,%2,%3,%4}; st.relaxed.gpu.global.v4.b32 [%0+32768], {%5,%6,%7,%8}; }"
                                 :: "l"(dst), "r"(o[0][0]), "r"(o[0][1]), "r"(o[0][2]), "r"(o[0][3]), "r"(o[1][0]), "r"(o[1][1]), "r"(o[1][2]), "r"(o[1][3]),
                                    "l"(hc), "r"((int)(t == 0 && !((EARLYH >> r) & 1))) : "memory");
                    mbar_arrive_if(BAR(B_TD + r), l0 && r < 3);
                    STAMPIF(w == 1 && (r & 3) == 0, r ? 3 : 45);
                    continue;
                }
                const uint32_t eb = sb + eslot(r);
                if (steps & 0x20) {
                    const int ew = (t >> 1) & 3, et = (ew + (t >> 3)) & 3, eh = (t >> 5) & 1;
                    const uint32_t ha = eb + ((t & 64) + 16 * et + 8 * eh + 2 * ew + (t & 1)) * 16;
                    const uint32_t ea = eb + (t & 64) * 128 + (2 * ew + eh) * 1024 + ((2 * et + (t & 1)) << 4);
                    mbar_wait(BAR(B_H + r), 0);
                    STAMPIF(warp == 1 && r == 0, 2); STAMPS(1);
                    uint4 hv4[4];
                    #pragma unroll
                    for (int i = 0; i < 4; i++) hv4[i] = lds128(ha + (i >> 1) * 2048 + (i & 1) * 16);
                    if (w == 0) { const uint32_t dr = __shfl_sync(~0u, dv, r); if (l0) hv4[1].x = hadd2(hv4[1].x, dr); }
                    bar_sync(5 + wg, 128);
                    #pragma unroll
                    for (int h = 0; h < 2; h++) {
                        const uint32_t* w8 = &hv4[2 * h].x;
                        #pragma unroll
                        for (int row = 0; row < 8; row++) {
                            uint32_t o[4];
                            #pragma unroll
                            for (int i = 0; i < 4; i++) o[i] = (row & 1) ? prmt(w8[(7 - row) / 2 + i], w8[(7 - row) / 2 + i + 1], 0x5432) : w8[(8 - row) / 2 + i];
                            sts128((ea ^ (row << 4)) + row * 128 + h * 16384, o[0], o[1], o[2], o[3]);
                        }
                    }
                    if (!(steps & 0x2000)) fence_async_smem();
                    STAMPIF(w == 0, wg ? 30 : 4);
                    continue;
                }
                float acc[128];
                mbar_wait(BAR(B_X + wg), (r >> 1) & 1); STAMPS(1);
                STAMPIF(w == 0, 10 + r);
                bar_sync(1 + wg, 256);
                GSTAMPIF(w == 0 && r == 0, 7); STAMPS(2);
                _Pragma("unroll 1") for (int rep = 0;; rep++) {
                    wg_fence();
                    Conv<0>::run(acc, dlo(eb, 16), dlo(xa, 16));
                    wg_commit();
                    if (r < 4 && !rep) bar_arrive(2 - wg, 256);
                    uint32_t t0;
                    asm volatile("ld.shared.b32 %0, [%1];" : "=r"(t0) : "r"(xa + w * 512 + (lane >> 4) * 2048 + (lane & 15) * 32 + (lane & 4) * 4) : "memory");
                    wg_wait<0>();
                    pin<128>(acc);
                    STAMPIF(w == 0, 15 + r);
                    if (!bar_or(5 + wg, 128, (t0 ^ par) & 1) || rep) break;
                    VALIF(true, 90, 1);
                    _Pragma("unroll 1") for (int h = 0; h < 2; h++) {
                        uint4 kx = {0, 0, 0, 0};
                        _Pragma("unroll 1") for (int it = 0; it < 20000; it++) {
                            ldg_rlx128_if(kx, gp + h * 2048, true);
                            if (!__any_sync(~0u, (kx.x ^ par) & 1)) break;
                        }
                        sts128(xa + t * 16 + h * 2048, kx.x, kx.y, kx.z, kx.w);
                    }
                    fence_async_smem();
                    bar_sync(5 + wg, 128);
                }
                gp += 2 * 524288;
                mbar_arrive_if(BAR(B_MD + r), t == 0 && r < 3);
                const uint32_t pw = eb + w * PP + lane * 16;
                #pragma unroll
                for (int g = 0; g < 8; g++) {
                    uint32_t o[4];
                    #pragma unroll
                    for (int l = 0; l < 4; l++) { const int i = 4 * g + l;
                        o[l] = i < 31 ? pack2(acc[4 * i] + acc[4 * i + 6], acc[4 * i + 1] + acc[4 * i + 7]) : pack2(acc[4 * i], acc[4 * i + 1]); }
                    asm volatile("stmatrix.sync.aligned.m8n8.x4.trans.shared.b16 [%0], {%1,%2,%3,%4};" :: "r"(pw + g * 512), "r"(o[0]), "r"(o[1]), "r"(o[2]), "r"(o[3]) : "memory");
                    if (g & 1) sched_bar();
                }
                if (lane < 6) sts128(pw + 4096, 0, 0, 0, 0);
                bar_sync(5 + wg, 128);
                if (YH < 0) red_if(CNT(C_Y + r, t), 1, t == 0);
                char* yp = (char*)gp + (offsetof(Scratch, yT) - 2 * 524288);
                #pragma unroll
                for (int h = 0; h < 2; h++) {
                    uint4 p[4];
                    #pragma unroll
                    for (int k = 0; k < 4; k++) p[k] = lds128(eb + (t + 128 * h) * 16 + k * (PP + 32));
                    uint32_t y[4];
                    #pragma unroll
                    for (int j = 0; j < 4; j++) y[j] = hadd2((&p[0].x)[j], hadd2((&p[1].x)[j], hadd2((&p[2].x)[j], (&p[3].x)[j])));
                    stg_rlx128(yp + h * 2048, (y[0] & ~1u) | par, y[1], y[2], y[3]);
                    if (h == YH) red_if(CNT(C_Y + r, t), 1, t == 0);
                }
                __syncwarp();
                mbar_arrive_if(BAR(B_RD + r), l0);
                mbar_arrive_remote_if(wre + 16 * (r - 1) + (lane & 4) * 2, lane < 8 && (r == 1 || r == 2));
                STAMPIF(w == 0, 20 + r);
            }
        }
        float acc1[128];
        uint4 sv[2] = {};
        const char* s2p = SC(st2, (tile * 128 + wg * 64 + w * 16 + rr) * 16);
        auto pass1 = [&](int n0, int n1, auto&& top, auto&& mid) {
            _Pragma("unroll 1") for (int n = n0; n < n1; n++) {
                top();
                const uint32_t da = dlo(sb + wg * 4096, 16) + n * 512, db = dlo(sb + WR, 4096) + (n & 3) * 1024;
                TWAIT((n & 1) ? 91 : 10 + (n >> 1), mbar_wait(BAR(B_AF) + (n >> 1) * 8, 0));
                TWAIT(50 + n, mbar_wait(BAR(B_WF) + (n & 3) * 8, (n >> 2) & 1));
                GSTAMPIF(n == 0 && warp == 0, 8);
                STAMPIF(n == 0 && warp == 4, 9);
                STAMPI(warp == 0 && !(n & 1), 50 + (n >> 1));
                wg_fence();
                WG<256>::ss<0, 1>(acc1, da, dhi(512, 2), db, dhi(1024, 1), n0 ? 1 : n);
                if (ER & 1) {
                    wg_commit();
                    wg_wait<1>();
                    mbar_arrive_remote_if(wre + ((n + 3) & 3) * 8, l01 && n > 0);
                }
                WG<256>::ss<0, 1>(acc1, da + 2, dhi(512, 2), db + 128, dhi(1024, 1), 1);
                wg_commit();
                if (!(ER & 1)) {
                    wg_wait<1>();
                    mbar_arrive_remote_if(wre + ((n + 3) & 3) * 8, l01 && n > 0);
                }
                mid(n);
            }
        };
        pass1(0, N_UT, []() {}, [](int) {});
        {
            float au[8];
            const int un = min(2 * b + wg, 239), cg = (un * 205) >> 10;
            char* up = SC(ut, ((un - 5 * cg) * 3072 + cg * 64 + w * 16 + rr) * 8);
            pass1(N_UT, N_UT + 1, [&]() {
                TWAIT(20, mbar_wait(BAR(B_UF), 0));
                const uint32_t ua = dlo(sb + UST + wg * 16384, 16), ub = dlo(sb + CS_TAB + wg * 512, 32);
                wg_fence();
                #pragma unroll
                for (int ks = 0; ks < 8; ks++) WG<8>::ss<1, 0>(au + 4 * (ks & 1), ua + ks * 128, dhi(1024, 1), ub + ks * 4, dhi(128, 0), ks >= 2);
                wg_commit();
            }, [&](int) {
                pin<8>(au);
                asm volatile("{ .reg .pred p; .reg .b64 x; setp.eq.b32 p, %5, 0; mov.b64 x, {%1, %2}; @p st.relaxed.gpu.global.b64 [%0], x; mov.b64 x, {%3, %4}; @p st.relaxed.gpu.global.b64 [%0+64], x; }"
                             :: "l"(up), "r"(tagged(au[0] + au[4], epoch)), "f"(au[1] + au[5]), "r"(tagged(au[2] + au[6], epoch)), "f"(au[3] + au[7]), "r"(q | (b >= 120)) : "memory");
                mbar_arrive_if(BAR(B_UD), l0);
                STAMPIF(warp == 0, 25);
            });
        }
        pass1(N_UT + 1, 20, []() {}, [&](int n) { ldg_rlx128_if(sv[0], s2p, n == 16); ldg_rlx128_if(sv[1], s2p + 128, n == 16); });
        _Pragma("unroll 1") for (int it = 0; it < 20000 && __any_sync(~0u, sv[0].w != epoch || sv[1].w != epoch); it++) { ldg_rlx128_if(sv[0], s2p, true); ldg_rlx128_if(sv[1], s2p + 128, true); }
        float acc2[64];
        const float rq0 = __uint_as_float(sv[0].z), rq1 = __uint_as_float(sv[1].z);
        {
            uint32_t ax[4];
            const uint32_t zm = q == 0 ? ~0u : q == 1 ? 0xffffu : 0u, sh = q ? 0x5454 : 0x5410, sl = sh + 0x2222;
            uint32_t a0 = prmt(sv[0].x, sv[0].y, sh), a1 = prmt(sv[1].x, sv[1].y, sh), a2 = prmt(sv[0].x, sv[0].y, sl), a3 = prmt(sv[1].x, sv[1].y, sl);
            TWAIT(21, mbar_wait(BAR(B_T1), 0));
            wg_wait<0>();
            mbar_arrive_remote_if(wre + 24, l01);
            asm volatile("setmaxnreg.inc.sync.aligned.u32 232;\n and.b32 %0, %4, %8; and.b32 %1, %5, %8; and.b32 %2, %6, %8; and.b32 %3, %7, %8;"
                         : "=r"(ax[0]), "=r"(ax[1]), "=r"(ax[2]), "=r"(ax[3]) : "r"(a0), "r"(a1), "r"(a2), "r"(a3), "r"(zm) : "memory");
            wg_fence();
            WG<256>::rs<1>(acc1, ax[0], ax[1], ax[2], ax[3], dlo(sb + TAB1, 0), dhi(48, 0), 1);
            WG<128>::rs<1>(acc2, ax[0], ax[1], ax[2], ax[3], dlo(sb + TAB2, 0), dhi(48, 0), 0);
            wg_commit();
        }
        char* hdst = SC(hh, (tile * 24 + js * 3) * 16384 + warp * 1024 + rr * 64 + ((q ^ (rr >> 1)) << 4));
        GSTAMPIF(warp == 0, 26);
        uint32_t hq[48];
        const uint32_t tm = (lane & 7) == (w & 1) * 4;
        auto release2 = [&](int it) {
            mbar_arrive_remote_if(wre + 8 * ((it + 3) & 3), l01 && it < 7);
            mbar_arrive_if(BAR(B_HS - 7) + 8 * it, l0 && it >= 7);
            mbar_arrive_remote_if(g2e + 8 * (it - G2R), l01 && it >= G2R && it < G2R + 6);
        };
        auto pass2 = [&](int it, auto&& epi) {
            TWAIT(70 + it, mbar_wait(BAR(B_WF) + (it & 3) * 8, ((it >> 2) & 1) ^ 1));
            STAMPI(warp == 0, 60 + it);
            const uint32_t da = dlo(sb + wg * 4096, 16) + it * 1024, db = dlo(sb + WR, 8192) + (it & 3) * 1024;
            wg_fence();
            static_for<0, 4>([&](auto KS) {
                WG<128>::ss<0, 1>(acc2, da + (KS.value >> 1) * 512 + (KS.value & 1) * 2, dhi(512, 2), db + KS.value * 128, dhi(1024, 1), 1);
                if constexpr (KS.value == 3) wg_commit();
                if constexpr (KS.value == 0 && (ER & 2)) { wg_commit(); wg_wait<1>(); if (it) release2(it); }
                epi(KS);
            });
            if (!(ER & 2)) { wg_wait<1>(); if (it) release2(it); }
        };
        pass2(0, [](auto) {});
        pin<128>(acc1);
        constexpr int NE = (epi_slot(15) >> 2) + 2;
        static_for<1, NE>([&](auto IT) {
            pass2(IT.value, [&](auto KS) {
                static_for<0, 16>([&](auto E) {
                    if constexpr (epi_slot(E.value) == 4 * IT.value + KS.value - 4) {
                        sched_bar();
                        ffn_epi<15 - E.value>(acc1, acc1 + 64, hq, hdst, tm, epoch, rq0, rq1);
                        if constexpr ((E.value & 7) == 7) { __syncwarp(); mbar_arrive_if(BAR(B_HD + (E.value >> 3)), l0); }
                        sched_bar();
                    }
                });
            });
        });
        _Pragma("unroll 1") for (int it = NE; it < 10; it++) pass2(it, [](auto) {});
        {
            float acc[80];
            static_for<0, 3>([&](auto IT) {
                constexpr int it = IT.value;
                TWAIT(35 + it, mbar_wait(BAR(B_G2F + it), 0));
                STAMPI(warp == 0 && it == 0, 70);
                const uint32_t db = dlo(sb + G2B + it * 20480, 2048);
                #pragma unroll
                for (int i = 0; i < 16; i++) asm volatile("" : "+r"(hq[16 * it + i]) :: "memory");
                wg_fence();
                static_for<0, 4>([&](auto KS) {
                    constexpr int ks = KS.value, sl = 4 * it + ks;
                    const uint32_t* o = hq + 16 * it + 8 * (ks >> 1) + 2 * (ks & 1);
                    WG<160>::rs<1>(acc, o[0], o[4], o[1], o[5], db + (ks >> 1) * 640 + (ks & 1) * 64, dhi(512, 2), it != 0 || ks != 0);
                    if constexpr (sl == 0 || ks == 3) wg_commit();
                    if constexpr (it > 0 && ks == 0 && (ER & 4)) { wg_commit(); wg_wait<1>(); mbar_arrive_remote_if(g2e + 8 * (it ? it - 1 : 0), l01); }
                    if constexpr (sl == 0) {
                        wg_wait<1>();
                        pin<64>(acc2);
                        mbar_arrive_if(BAR(B_S0), l0);
                        static_for<(G2R > 4 ? 10 - G2R : 6), 6>([&](auto G) { mbar_arrive_remote_if(g2e + 8 * G.value, l01); });
                    }
                    if constexpr (sl < 8 / Q2) {
                        sched_bar();
                        static_for<0, Q2>([&](auto J) { ffn_epi<7 - Q2 * sl - J.value>(acc2, acc2 + 32, hq + 32, hdst + 32768, tm, epoch, rq0, rq1); });
                        if constexpr (sl == 8 / Q2 - 1) { __syncwarp(); mbar_arrive_if(BAR(B_HD + 2), l0); }
                        sched_bar();
                    }
                    if constexpr (sl == 0) wg_fence();
                });
                if (it && !(ER & 4)) {
                    wg_wait<1>();
                    mbar_arrive_remote_if(g2e + 8 * (it ? it - 1 : 0), l01);
                }
            });
            mbar_wait(BAR(B_GB), 0);
            fence_async_glob();
            uint4 gw[5];
            #pragma unroll
            for (int i = 0; i < 5; i++) gw[i] = lds128(sb + GBT + q * 80 + i * 16);
            const uint32_t da = dlo(sb + G2A + wg * 4096, 16), db = dlo(sb + G2B, 2048);
            _Pragma("unroll 1") for (int it = 3; it < 12 - NST; it++) {
                const int g = it >= 6 ? it - 6 : it, ga = it >= 5 ? it - 5 : it + 1;
                TWAIT(35 + it, mbar_wait(BAR(B_G2F + g), it >= 6));
                TWAIT(77 + it, mbar_wait(BAR(B_AF - 3 + it), 1));
                STAMPI(warp == 0 && (it == 3 || it == 6), 70 + (it >> 2) + 1);
                wg_fence();
                #pragma unroll
                for (int ks = 0; ks < 4; ks++) {
                    WG<160>::ss<0, 1>(acc, da + ga * 1024 + (ks >> 1) * 512 + (ks & 1) * 2, dhi(512, 2), db + g * 1280 + (ks >> 1) * 640 + (ks & 1) * 64, dhi(512, 2), 1);
                    if (ks == 3 || (ks == 0 && (ER & 4))) wg_commit();
                    if (ks == ((ER & 4) ? 0 : 3)) {
                        wg_wait<1>();
                        mbar_arrive_remote_if(g2e + 8 * (it - 1), l01 && it < 7);
                        mbar_arrive_if(BAR(B_HS - 4) + 8 * it, l0 && it >= 4 && it < 7);
                    }
                }
            }
            mbar_wait(BAR(B_G2F + 6 - NST), 1);
            mbar_wait(BAR(B_AF + 9 - NST), 1);
            if (wg) TWAIT(47, bar_sync(7, 256));
            STAMPI(warp == 0, 73);
            float gf[80];
            wg_fence();
            static_for<48 - 4 * NST, 48>([&](auto K) {
                constexpr int it = K.value >> 2, ks = K.value & 3;
                WG<160>::ss<0, 1>(acc, da + (it == 11 ? 0 : it - 5) * 1024 + (ks >> 1) * 512 + (ks & 1) * 2, dhi(512, 2), db + (it - 6) * 1280 + (ks >> 1) * 640 + (ks & 1) * 64, dhi(512, 2), 1);
                if constexpr (it < 11 && ks == 1) TWAIT(36 + it, mbar_wait(BAR(B_G2F + it - 5), 1));
                if constexpr (it < 11 && ks == 2) TWAIT(78 + it, mbar_wait(BAR(B_AF + it - 2), 1));
                if constexpr (RQE == 2 && K.value >= 28 && K.value < 47) {
                    sched_bar();
                    #pragma unroll
                    for (int j = K.value - 28; j < (K.value == 46 ? 20 : K.value - 27); j++) {
                        const float lo = bflo((&gw[j >> 2].x)[j & 3]), hi = bfhi((&gw[j >> 2].x)[j & 3]);
                        gf[4 * j] = lo * rq0; gf[4 * j + 1] = hi * rq0; gf[4 * j + 2] = lo * rq1; gf[4 * j + 3] = hi * rq1;
                        pin<4>(gf + 4 * j);
                    }
                    sched_bar();
                }
                if constexpr (K.value == 39) wg_commit();
                if constexpr (K.value == 46) { if (!wg) bar_arrive(7, 256); }
            });
            wg_commit();
            wg_wait<1>();
            bar_sync(5 + wg, 128);
            uint32_t osts[2];
            const uint32_t orow = (lane & 7) * 336 + (lane >> 3) * 16;
            osts[0] = sb + G2A + (1 + w) * 16384 + wg * 4096; osts[1] = osts[0] + 8192;
            wg_wait<0>();
            pin<80>(acc);
            STAMPIF(w == 0, 27 + wg);
            GSTAMPIF(warp == 4, 29);
            #pragma unroll
            for (int hf = 0; hf < 2; hf++) {
                #pragma unroll
                for (int i = 0; i < 5; i++) {
                    uint32_t o[4];
                    const float rq = hf ? rq1 : rq0;
                    #pragma unroll
                    for (int j = 0; j < 4; j++) { const int n = 16 * i + 4 * j + 2 * hf; o[j] = RQE == 2 ? pack2(acc[n] * gf[n], acc[n + 1] * gf[n + 1]) : hmul2(RQE ? pack2(acc[n], acc[n + 1]) : pack2(acc[n] * rq, acc[n + 1] * rq), (&gw[i].x)[j]); }
                    asm volatile("stmatrix.sync.aligned.m8n8.x4.shared.b16 [%0], {%1,%2,%3,%4};" :: "r"(osts[hf] + orow + i * 64), "r"(o[0]), "r"(o[1]), "r"(o[2]), "r"(o[3]) : "memory");
                    if (EI && i < 4 && (EI == 1 || (i & 1))) sched_bar();
                }
                fence_async_smem();
                __syncwarp();
                if (elect()) { tma3d_red(&M.out, osts[hf], dq, 128 * tile + 16 * warp + 8 * hf); }
                sched_bar();
            }
            STAMPIF(w == 0, wg ? 31 : 85);
            if (elect()) asm volatile("cp.async.bulk.commit_group;\n cp.async.bulk.wait_group.read 0;" ::: "memory");
            STAMPIF(w == 3, wg ? 33 : 86);
            GSTAMPIF(warp == 4, 34);
        }
    } else {
        const int hw = warp & 3, wv = hw & 1;
        if (elect()) {
            if (warp & 2) {
                if (warp & 1) { _Pragma("unroll") for (int i = B_UD; i < NBARS; i++) mbar_init(BAR(i), bar_count(i)); }
                else { _Pragma("unroll") for (int i = B_WF; i < B_UD; i++) mbar_init(BAR(i), bar_count(i)); }
            } else { _Pragma("unroll") for (int i = 0; i < 20; i++) mbar_init(BAR(i) + wv * 160, 1); }
            asm volatile("fence.mbarrier_init.release.cluster;" ::: "memory");
            fence_async_smem();
        }
        __syncwarp();
        asm volatile("barrier.cluster.arrive.relaxed.aligned;" ::: "memory");
        const uint32_t t1 = clk0 + D_1 + ((((b * 37) & 127) * G_ST) >> 7);
        if (hw == 0) {
            bar_arrive(0, 384);
            if (lane < 15 && lane != B_KV) mbar_expect(BAR(lane), lane >= B_KV && lane < B_Q ? 9216 : 4096);
            __syncwarp();
            if (elect()) { wait_until(t1); bulk_g2s(sb + 16, P.ssm + b * 4096, 4096, BAR(B_H)); }
            __syncwarp();
            bar_sync(3, 128);
        } else { bar_sync(0, 384); bar_arrive(3, 128); }
        FFN_ROLE;
        const int kh = js >> 2, ft = tile * 8 + js;
        const int oz = __shfl_sync(~0u, tid >> 9, lane);
        epoch = ldg_rlx32(CNT(C_Z + tile, 6 + oz));
        if (hw == 0) {
            if (elect()) {
                auto x_fetch = [&](int r) {
                    if (!mbar_test(BAR(B_KV + r), 0)) { mbar_wait(BAR(B_KV + r), 0); pause(D_PK); }
                    poll_cnt(CNT(C_KV + 2 * r + (b >> 6), 0), (epoch | 127) + 1);
                    fence_async_glob();
                    if (r >= 2) mbar_wait(BAR(B_MD - 2 + r), 0);
                    mbar_expect(BAR(B_X + (r & 1)), 4096);
                    bulk_g2s(sb + XB + (r & 1) * XP, SC(kvT, (b + 128 * r) * 4096), 4096, BAR(B_X + (r & 1)));
                    STAMPIF(r < 2, 5 + r);
                };
                static_for<1, NORD>([&](auto I) {
                    constexpr char kind = ord_kind(I.value); constexpr int n = ord_index(I.value);
                    if constexpr (kind == 'k' && n >= 3) mbar_wait(BAR(B_TD + n - 3), 0);
                    if constexpr (kind != '_' && kind != 'x' && (TUNING || ord_time(I.value))) wait_until(t1 + TN(16 + I.value, ord_time(I.value)));
                    if constexpr (kind == 'k') { tma4d(sb + st_kv(n), &M.k, n * 128 + rank * 64, cl * 4 - 1, BAR(B_KV + n)); tma4d(sb + st_kv(n) + 5120, &M.v, n * 128 + rank * 64, cl * 4, BAR(B_KV + n)); }
                    if constexpr (kind == 'q') tma3d(sb + ST_Q + n * 4096, &M.q, ft * 16, n * 4, BAR(B_Q + n));
                    if constexpr (kind == 'h') bulk_g2s(sb + eslot(n) + 16, P.ssm + (b + 128 * n) * 4096, 4096, BAR(B_H + n));
                    if constexpr (kind == 'w') pf_l2(((n & 1) ? P.Wu : P.Wg) + (b + 128 * (n >> 1)) * 3072, 3072);
                    if constexpr (kind == 'm') { _Pragma("unroll") for (int s = 0; s < 5; s++) if (s != 3) pf_tma3d(&M.wp, n * 128, b * 5, s); }
                    if constexpr (kind == 'x') x_fetch(n);
                });
                _Pragma("unroll 1") for (int r = ord_count('x'); r < 5; r++) x_fetch(r);
            }
        } else if (hw == 2 && elect()) { pf_map(&M.k); pf_map(&M.v); pf_map(&M.q); if (ord_count('m')) pf_map(&M.wp); }
        __syncwarp();
        epoch = (__shfl_sync(~0u, epoch, 0) >> 7) + 1;
        const uint32_t target = epoch << 7, par = epoch & 1;
        const char* pa = lane < 8 ? CNT(C_Y, 0) : SC(abc, (lane & 7) * 128 + 12);
        const uint32_t want = lane < 8 ? target : epoch;
        auto y_poll = [&](int r) {
            if (!mbar_test(BAR(B_RD + r), 0)) { mbar_wait(BAR(B_RD + r), 0); pause(D_PY); }
            _Pragma("unroll 1") for (int it = 0; it < 20000 && __any_sync(~0u, (int)(ldg_rlx32(pa) - want) < 0); it++) {}
        };
        auto y_request = [&](int r) {
            if (elect()) {
                fence_async_glob();
                mbar_expect(BAR(B_Y + (r & 1)), 5120);
                tma5d(sb + ST_Y + (r & 1) * 4096, &M.y, 2032 - 16 * ft, 4 * r, BAR(B_Y + (r & 1)));
                bulk_g2s(sb + ST_Y + 8192 + (r & 1) * 1024, SC(abc, r * 1024), 1024, BAR(B_Y + (r & 1)));
            }
            STAMPIF(r < 2, 48 + r);
            pa += lane < 8 ? 4096 : 1024;
        };
        if (hw == 1) {
            if (elect()) { pf_map(&M.y); pf_map(&M.wp); }
            mbar_wait(BAR(B_TD + 2), 0);
            wait_until(clk0 + D_M);
            _Pragma("unroll 1") for (int r = 0; r < 2; r++) {
                y_poll(r); y_request(r);
                if (MPF && elect()) {
                    _Pragma("unroll 1") for (int s = 0; s < (r ? 5 : 8); s++) pf_tma3d(&M.wp, r ? s * 128 : 384 + (s >> 2) * 128, b * 5, r ? 3 : (s & 3) + ((s & 3) == 3));
                }
            }
        }
        if (hw >= 2) {
            pa += lane < 8 ? 8192 : 2048;
            {
                uint32_t aQ = sb + ST_Q + wv * 2048 + (lane & 15) * 64 + (((lane >> 1) + (lane >> 4)) & 3) * 16;
                float sq[4] = {0.f, 0.f, 0.f, 0.f};
                _Pragma("unroll 1") for (int rq = 0; rq < 5; rq++) {
                    mbar_wait(BAR(B_Q + rq), 0);
                    STAMPIF(wv && rq == 4, 44);
                    uint4 v[4];
                    #pragma unroll
                    for (int u = 0; u < 4; u++) v[u] = lds128((aQ ^ ((u & 1) << 5)) + (u >> 1) * 1024);
                    sched_bar();
                    #pragma unroll
                    for (int j = 0; j < 16; j++) acc_stat(sq[2 * (j & 1)], sq[2 * (j & 1) + 1], (&v[(j & 1) + (j >> 3) * 2].x)[(j >> 1) & 3]);
                    aQ += 4096;
                }
                asm volatile("st.shared.v2.f32 [%0], {%1,%2};" :: "r"(sb + ST_S + (lane & 15) * 48 + wv * 16 + (lane >> 4) * 8), "f"(sq[0] + sq[2]), "f"(sq[1] + sq[3]) : "memory");
            }
            float sa[4] = {0.f, 0.f, 0.f, 0.f};
            uint32_t yl = sb + ST_Y + wv * 1024 + lane * 32 + (lane & 4) * 4, ca = sb + ST_Y + 8192 + wv * 256 + q * 16;
            const uint32_t ym = rr ? 0u : 0x00010001u;
            char* zp = SC(z, tile * 163840 + wv * 8192 + (16 * js + 15 - rr) * 64 + ((q ^ 3 ^ (rr >> 1)) << 4));
            uint32_t xs = sb + ST_Q + wv * 1024 + (15 - rr) * 64 + q * 16;
            const uint32_t tm = (lane & 7) == (~js & 1) * 4;
            const char* zc = CNT(C_Z + tile, lane & 7);
            bar_sync(4, 64);
            STAMPIF(hw == 3, 46);
            uint32_t rs[2], mr[2];
            #pragma unroll
            for (int h = 0; h < 2; h++) {
                float f[2] = {0.f, 0.f};
                #pragma unroll
                for (int i = 0; i < 2; i++) { const uint4 a = lds128(sb + ST_S + (15 - 8 * h - rr) * 48 + i * 16); f[0] += __uint_as_float(a.x) + __uint_as_float(a.z); f[1] += __uint_as_float(a.y) + __uint_as_float(a.w); }
                const float mu = f[0] * (1.f / D_), r_ = rsqrt_(fmaxf(f[1] * (1.f / D_) - mu * mu, 0.f) + 1e-5f);
                rs[h] = pack2(r_, r_); const float m_ = -mu * bflo(rs[h]); mr[h] = pack2(m_, m_);
            }
            const int un = min(2 * b + wv, 239), cg = (un * 205) >> 10, ur = un - 5 * cg;
            char* op = padd(P.out, (ft * 16 + 15 - rr) * 1280 + wv * 64 + q * 16) - 256;
            uint4 x1[4] = {};
            const char *cp_ = SC(abc, (ur * 64 + (lane & 16) + q * 4 + (rr & 3)) * 16 + 8), *sp_ = SC(mod, (ur * 64 + lane) * 8);
            auto caddr = [&](int i) { return i < 2 ? sp_ + i * 256 : cp_ + (i & 1) * 512; };
            uint2 mv[4] = {};
            uint32_t pv = 0;
            bool asked = false;
            _Pragma("unroll 1") for (int r = 0;; r++) {
                STAMPR(0);
                uint4 x[4] = {};
                const bool ask = r >= 2 && r < 5 && wv == 0;
                if (ask) { if (!__any_sync(~0u, (int)(pv - want) < 0)) { y_request(r); asked = true; } else pv = ldg_rlx32(pa); }
                if (r < 5) {
                    #pragma unroll
                    for (int i = 0; i < 4; i++) x[i] = lds128(xs + (i >> 1) * 2048 - (i & 1) * 512);
                    sched_bar();
                } else {
                    mbar_wait(BAR(B_TD), 1);
                    if (elect()) {
                        mbar_expect(BAR(B_UF), 16384);
                        #pragma unroll
                        for (int i = 0; i < 2; i++) tma2d(sb + UST + wv * 16384 + i * 8192, cg >= 24 ? &M.u2 : &M.g2, (cg >= 24 ? cg - 24 : cg) * 64, ur * 128 + i * 64, BAR(B_UF));
                    }
                    ll_wait<4>(mv, epoch, caddr);
                    #pragma unroll
                    for (int i = 0; i < 4; i++) sts32(sb + CS_TAB + wv * 512 + ((i & 1) * 8 + rr) * 32 + q * 4 + (i < 2 ? 16 : 0), mv[i].x);
                    fence_async_smem(); __syncwarp(); mbar_arrive_if(BAR(B_UF), l0);
                    STAMPIF(wv, 41);
                }
                if (r) {
                    #pragma unroll
                    for (int j = 0; j < 16; j++) acc_stat(sa[j & 2], sa[(j & 2) + 1], (&x1[(j >> 1) & 3].x)[(j & 1) + (j >> 3) * 2]);
                    #pragma unroll
                    for (int j = 0; j < 4; j++) asm volatile("" : "+f"(sa[j]) :: "memory");
                    bump<32768>(zp); bump(yl, (r & 1) ? 4096 : -4096); bump(ca, (r & 1) ? 1024 : -1024);
                }
                STAMPR(2);
                uint32_t nx[16];
                #pragma unroll
                for (int j = 0; j < 16; j++) { nx[j] = hfma2((&x[j >> 2].x)[j & 3], rs[(j >> 2) & 1], mr[(j >> 2) & 1]); asm volatile("" : "+r"(nx[j]) :: "memory"); }
                sched_bar();
                if (r) {
                    #pragma unroll
                    for (int i = 0; i < 4; i++) stg128(op + (i >> 1) * 128 - (i & 1) * 10240, x1[i].x, x1[i].y, x1[i].z, x1[i].w);
                }
                if (r == 5) break;
                if (ask && !asked) { if (__any_sync(~0u, (int)(pv - want) < 0)) y_poll(r); y_request(r); }
                asked = false;
                mbar_wait(BAR(B_Y + (r & 1)), (r >> 1) & 1);
                if (wv == 0 && r) { mbar_wait(BAR(B_YE + (~r & 1)), (r - 1) >> 1 & 1); pv = ldg_rlx32(pa); }
                if (r == 4) { _Pragma("unroll") for (int i = 0; i < 4; i++) mv[i] = ldg_rlx64(caddr(i)); }
                STAMPIF(wv == 0 && r == 0, 47);
                STAMPR(5);
                uint4 cc[8];
                uint32_t y[4][4];
                _Pragma("unroll 1") for (int it = 0; it < 20000; it++) {
                    uint32_t all = ~0u, any = 0;
                    #pragma unroll
                    for (int i = 0; i < 4; i++) ldsm4t(y[i], (yl ^ ((i & 1) << 4)) + (i >> 1) * 2048);
                    #pragma unroll
                    for (int i = 0; i < 8; i++) cc[i] = lds128(ca + (i >> 2) * 512 + (i & 3) * 64);
                    #pragma unroll
                    for (int j = 0; j < 16; j++) { all &= y[j >> 2][j & 3]; any |= y[j >> 2][j & 3]; }
                    if (!__any_sync(~0u, ((par ? ~all : any) & ym) != 0)) break;
                    VALIF(true, 89, 1);
                    const char* yp = SC(yT, (r * 128 + wv * 32 + (lane & 6) * 4 + (lane >> 3) * 2 + (lane & 1)) * 4096 + (254 - 2 * ft) * 16);
                    #pragma unroll
                    for (int i = 0; i < 4; i++) cp16((yl ^ ((i & 1) << 4)) + (i >> 1) * 2048, yp + (i & 1) * 16 + (i >> 1) * 262144);
                    asm volatile("cp.async.wait_all;" ::: "memory");
                    __syncwarp();
                }
                STAMPR(6);
                bump<256>(op); bump(xs, 4096);
                if (ZE) red_if(zc, 8, lane == r);
                #pragma unroll
                for (int j = 0; j < 16; j++) {
                    (&x1[j >> 2].x)[j & 3] = hfma2(hfma2(nx[j], cc[(j >> 3) * 4 + (j & 3)].x, cc[(j >> 3) * 4 + (j & 3)].y), y[j >> 2][j & 3], (&x[j >> 2].x)[j & 3]);
                    y[j >> 2][j & 3] = hmul2((&x1[j >> 2].x)[j & 3], cc[(j >> 3) * 4 + (j & 3)].z);
                    if ((j & 3) == (~j >> 2 & 1)) y[j >> 2][j & 3] = (y[j >> 2][j & 3] & ~tm) | (par & tm);
                    asm volatile("" : "+r"(y[j >> 2][j & 3]) :: "memory");
                }
                sched_bar();
                #pragma unroll
                for (int i = 0; i < 4; i++) asm volatile("st.relaxed.gpu.global.v4.b32 [%0], {%1,%2,%3,%4};" :: "l"(zp + (i >> 1) * 16384 - (i & 1) * 512), "r"(y[i][0]), "r"(y[i][1]), "r"(y[i][2]), "r"(y[i][3]) : "memory");
                if (!ZE) red_if(zc, 8, lane == r);
                mbar_arrive_if(r == 4 ? BAR(B_TD) : BAR(B_YE + (r & 1)), lane <= (r == 4));
                mbar_arrive_if(BAR(B_H + r), tid == 352);
                STAMPIF(wv, 75 + r);
                STAMPR(7);
            }
            const float e0 = ((q & 2) ? sa[2] : sa[0]) + __shfl_xor_sync(~0u, (q & 2) ? sa[0] : sa[2], 2), e1 = ((q & 2) ? sa[3] : sa[1]) + __shfl_xor_sync(~0u, (q & 2) ? sa[1] : sa[3], 2);
            float e = ((q & 1) ? e1 : e0) + __shfl_xor_sync(~0u, (q & 1) ? e0 : e1, 1);
            if (wv) sts32(sb + TAB2 + lane * 4, __float_as_uint(e));
            bar_sync(4, 64);
            if (wv) {
                if (l0) asm volatile("fence.release.gpu;\n red.relaxed.gpu.global.add.u32 [%0], 16;" :: "l"(CNT(C_Z + tile, 6)) : "memory");
                __syncwarp();
            } else {
                uint32_t oth; asm volatile("ld.shared.b32 %0, [%1];" : "=r"(oth) : "r"(sb + TAB2 + lane * 4) : "memory");
                e += __uint_as_float(oth);
                const float mu = e * (1.f / D_), ve = fmaxf(__shfl_down_sync(~0u, e, 1) * (1.f / D_) - mu * mu, 0.f) + 1e-5f, r_ = rsqrt_(ve);
                if (!(q & 1)) stg_rlx128(SC(st2, (ft * 16 + 15 - rr - 4 * q) * 16), split2(-mu), split2(ve * r_), __float_as_uint(r_ * r_), epoch);
            }
            if (!wv && elect()) pf_l2(P.Wd + b * 15360, 15360);
            mbar_wait(BAR(B_UD), 0);
            pause(D_UT);
            const char* up = SC(ut, (wv * 1536 + js * 192 + 2 * lane) * 8);
            uint4 v[15];
            _Pragma("unroll 1") for (int it = 0; it < 20000; it++) {
                uint32_t bad = 0;
                #pragma unroll
                for (int i = 0; i < 15; i++) v[i] = ldg_rlx2x64(up + (i / 3) * 24576 + (i % 3) * 512);
                #pragma unroll
                for (int i = 0; i < 15; i++) bad |= (v[i].x ^ epoch) | (v[i].z ^ epoch);
                if (!__any_sync(~0u, (bad & 7) != 0)) break;
            }
            #pragma unroll
            for (int n = 0; n < 3; n++) {
                float f[4];
                #pragma unroll
                for (int j = 0; j < 4; j++) f[j] = (__uint_as_float((&v[n].x)[j]) + __uint_as_float((&v[3 + n].x)[j])) + (__uint_as_float((&v[6 + n].x)[j]) + __uint_as_float((&v[9 + n].x)[j])) + __uint_as_float((&v[12 + n].x)[j]);
                const uint32_t ta = sb + TAB1 + ((n == 2 ? 32 + wv * 8 : n * 8 + wv * 16) + rr) * 48 + q * 4, th2 = pack2(f[1], f[3]);
                sts32(ta, pack2(f[0], f[2])); sts32(ta + 16, th2); sts32(ta + 32, pack2(f[1] - bflo(th2), f[3] - bfhi(th2)));
            }
            if (lane < 20) sts32(sb + TAB1 + 48 * 48 + lane * 4, 0);
            fence_async_smem();
            __syncwarp();
            mbar_arrive_if(BAR(B_T1), l0);
            STAMPIF(hw == 3, 43);
        }
        asm volatile("setmaxnreg.dec.sync.aligned.u32 40;");
        const uint32_t ep2 = __shfl_sync(~0u, epoch, 0), tg2 = ep2 << 7;
        const char* hfl = CNT(C_HH + tile * 2 + kh, 0);
        auto hh_src = [&](int j) { const int c = (j * 11) >> 5, m = j - 3 * c; return SC(hh, (tile * 24 + (kh * 4 + m + (m >= dq)) * 3 + (c ^ (c < 2))) * 16384); };
        if (hw == 0 || hw == 3) {
            if (hw == 0) {
            if (elect()) {
                const CUtensorMap *m1 = rank ? &M.u1 : &M.g1, *m2 = rank ? &M.u2 : &M.g2;
                const char* pw = P.Wg + (b + 128 * (NWP >> 1)) * 3072;
                const long long dw = P.Wu - P.Wg;
                pf_map(m1);
                _Pragma("unroll 1") for (int n = 0; n < 20; n += 2) {
                    #pragma unroll
                    for (int h = 0; h < 2; h++) {
                        const uint32_t so = (n & 2) + h;
                        mbar_wait(BAR(B_WE) + so * 8, (n >> 2) & 1);
                        mbar_expect(BAR(B_WF) + so * 8, 16384);
                        tma3d_mc(sb + WR + rank * 8192 + so * 16384, m1, (n + h) * 32, js * 3, BAR(B_WF) + so * 8);
                        if (n >= WP0 && n < WP0 + 10 - NWP) pf_l2(pw + h * dw, 3072);
                    }
                    if (n >= WP0) pw += 128 * 3072;
                }
                _Pragma("unroll 1") for (int n = 0; n < 10; n++) {
                    const uint32_t so = n & 3;
                    mbar_wait(BAR(B_WE) + so * 8, ((n >> 2) & 1) ^ 1);
                    mbar_expect(BAR(B_WF) + so * 8, 16384);
                    tma2d_mc(sb + WR + rank * 8192 + so * 16384, m2, js * 192 + 128, n * 64, BAR(B_WF) + so * 8);
                }
            }
            } else {
                const char* gp = SC(mod, (320 + dq * 80 + lane) * 8);
                auto gaddr = [&](int i) { return gp + i * 192; };
                uint2 gv[3];
                #pragma unroll
                for (int i = 0; i < 3; i++) gv[i] = ldg_rlx64(gaddr(i));
                ll_wait<3>(gv, ep2, gaddr);
                poll_cnt(CNT(C_Z + tile, 6), tg2);
                fence_acq();
                mbar_wait(BAR(B_HD), 0);
                red_if(hfl + lane * 4, 32, l0);
                STAMP(36);
                #pragma unroll
                for (int n = 0; n < 3; n++) sts32(sb + GBT + q * 80 + (rr + 6 * n) * 4, gv[n].x);
                __syncwarp();
                mbar_arrive_if(BAR(B_GB), l0);
                mbar_wait(BAR(B_HD + 1), 0);
                red_if(hfl + lane * 4, 32, lane == 1);
            }
            if (elect()) {
                _Pragma("unroll 1") for (int j = 3 - hw; j < 6 + hw; j += j == 2 ? 4 : 1) {
                    const int c = (j * 11) >> 5;
                    const char* src = hh_src(j);
                    mbar_expect(BAR(B_AL + j), 16384);
                    if (j == 3 * c) { mbar_wait(BAR(B_HD + c), 0); if (c == 2) { red_if(hfl + 8, 32, true); STAMP(40); pause(D_H2); } poll_cnt(hfl + c * 4, tg2); fence_async_glob(); STAMPIF(c != 1, c ? 32 : 38); }
                    mbar_wait(c == 1 ? BAR(B_S0) : BAR(B_HS + j - 3 * c), c == 2);
                    bulk_g2s(sb + (j < 2 ? j + 12 : j < 8 ? j + 6 : 8) * 16384, src, 16384, BAR(B_AL + j));
                }
            }
        } else if (wv) {
            {
                if (lane < 10) mbar_expect(BAR(B_AL + lane), 16384);
                if (elect()) { pf_map(&M.g2); pf_map(&M.u2); }
                const char *zc = CNT(C_Z + tile, lane & 7), *zp = SC(z, tile * 163840);
                uint32_t rtp = 0, zv = tg2 - 1, al = BAR(B_AL), dst = sb;
                const uint32_t vo = lane * 128 + (lane & 3) * 16 + (lane & 8) * 8 + (lane & 4);
                int zr = 0;
                _Pragma("unroll 1") for (int i = 0; i < 19; i++) {
                    if (zr < 5) {
                        const uint32_t fre = BAR(zr == 4 ? B_UD : zr ? B_RD + 3 + (zr > 1) : B_RD);
                        bool go = (__ballot_sync(~0u, (int)(zv - tg2) >= 0) >> zr) & 1;
                        if (2 * zr <= i) {
                            mbar_wait(fre, 0);
                            if (!go) {
                                if (!mbar_test(BAR(B_H + zr), 1)) { mbar_wait(BAR(B_H + zr), 1); pause(D_PZ); }
                                poll_cnt(CNT(C_Z + tile, zr), tg2);
                            }
                            go = true;
                        } else go = go && mbar_test(fre, 0);
                        if (go) {
                            if (elect()) {
                                fence_async_glob();
                                bulk_g2s(sb + zr * 32768, zp, 16384, BAR(B_AL + 2 * zr));
                                bulk_g2s(sb + zr * 32768 + 16384, zp + 16384, 16384, BAR(B_AL + 2 * zr + 1));
                            }
                            STAMP(80 + zr);
                            zr++; zp += 32768;
                        }
                    }
                    mbar_wait(al, i >= 10);
                    _Pragma("unroll 1") for (int rt = 0; rt < 2000; rt++) {
                        uint32_t v[4];
                        #pragma unroll
                        for (int k = 0; k < 4; k++) asm volatile("ld.shared.b32 %0, [%1];" : "=r"(v[k]) : "r"(dst + vo + k * 4096) : "memory");
                        if (!__any_sync(~0u, ((v[0] ^ ep2) | (v[1] ^ ep2) | (v[2] ^ ep2) | (v[3] ^ ep2)) & 1)) break;
                        int i_ = i; asm volatile("" : "+r"(i_));
                        VALIF(true, 87 + (i >= 10), 1);
                        if (elect()) { mbar_expect(BAR(B_RT), 16384); bulk_g2s(dst, i_ < 10 ? SC(z, (tile * 10 + i_) * 16384) : hh_src(i_ - 10), 16384, BAR(B_RT)); }
                        mbar_wait(BAR(B_RT), rtp);
                        rtp ^= 1;
                    }
                    mbar_arrive_if(al - 8 * (B_AL - B_AF), l0);
                    if (zr < 5) zv = ldg_rlx32(zc);
                    al += i == 9 ? -72 : 8; dst += i == 9 ? 49152 : i == 11 || i == 17 ? -81920 : 16384;
                    STAMPIF(i == 0 || i == 10 || i == 16, i == 10 ? 37 : i ? 74 : 42);
                }
            }
        } else if (elect()) {
            pf_map(&M.wn); pf_map(&M.wd); pf_map(&M.out);
            int g = 0, c = 0, m = -3;
            _Pragma("unroll 1") for (int n = 0; n < 12; n++) {
                const uint32_t st = sb + G2B + g * 20480 + rank * 10240, f = BAR(B_G2F + g);
                mbar_wait(BAR(B_G2E + g), n >= 6);
                mbar_expect(f, 20480);
                if (m < 0) tma3d_mc(st, &M.wn, (js * 3 + n) * 64 + rank * 32, dq * 5, f);
                else tma5d_mc(st, &M.wd, ((kh * 4 + m + (m >= dq)) * 3 + (c ^ (c < 2))) * 8 + rank * 4, dq * 5, f);
                g = g == 5 ? 0 : g + 1;
                if (++m == 3) { m = 0; c++; }
            }
        }
    }
}

typedef CUresult (*EncodeFn)(CUtensorMap*, CUtensorMapDataType, cuuint32_t, void*, const cuuint64_t*, const cuuint64_t*, const cuuint32_t*, const cuuint32_t*,
                             CUtensorMapInterleave, CUtensorMapSwizzle, CUtensorMapL2promotion, CUtensorMapFloatOOBfill);
void enc(EncodeFn fn, CUtensorMap* m, const void* ptr, int rank, const cuuint64_t* dims, const cuuint64_t* strides, const cuuint32_t* box, CUtensorMapSwizzle sw,
         CUtensorMapL2promotion pr = CU_TENSOR_MAP_L2_PROMOTION_L2_128B) {
    cuuint32_t es[5] = {1, 1, 1, 1, 1};
    fn(m, CU_TENSOR_MAP_DATA_TYPE_BFLOAT16, rank, (void*)ptr, dims, strides, box, es, CU_TENSOR_MAP_INTERLEAVE_NONE, sw,
       pr, CU_TENSOR_MAP_FLOAT_OOB_FILL_NONE);
}
}

extern "C" void kernel_launch(void* const* d_in, const int* in_sizes, int n_in, void* d_out, int out_size) {
    void* fnp = nullptr; cudaDriverEntryPointQueryResult st;
    cudaGetDriverEntryPoint("cuTensorMapEncodeTiled", &fnp, cudaEnableDefault, &st);
    EncodeFn fn = (EncodeFn)fnp;
    void* scr;
    cudaGetSymbolAddress(&scr, g_s);
    Maps M; Ptrs P;
    P.k = (const char*)d_in[1]; P.v = (const char*)d_in[2]; P.shift = (const char*)d_in[3]; P.ssm = (const char*)d_in[4]; P.ssmD = (const char*)d_in[5]; P.Wg = (const char*)d_in[7]; P.Wu = (const char*)d_in[8];
    P.Wd = (const char*)d_in[9]; P.c = (const char*)d_in[10]; P.out = (char*)d_out; P.scr = (char*)scr;
    { cuuint64_t d[4] = {640, 2, 256, 4}, s[3] = {1280, 8 * 1280, 2 * 1280}; cuuint32_t b1[4] = {64, 2, 5, 4}, b2[4] = {64, 2, 4, 4};
      enc(fn, &M.k, d_in[1], 4, d, s, b1, CU_TENSOR_MAP_SWIZZLE_128B); enc(fn, &M.v, d_in[2], 4, d, s, b2, CU_TENSOR_MAP_SWIZZLE_128B); }
    { cuuint64_t d[3] = {32, 2048, 20}, s[2] = {1280, 64}; cuuint32_t b1[3] = {32, 16, 4};
      enc(fn, &M.q, d_in[0], 3, d, s, b1, CU_TENSOR_MAP_SWIZZLE_NONE); }
    { cuuint64_t d[5] = {2048, 2, 4, 4, 20}, s[4] = {4096, 8 * 4096, 2 * 4096, 32 * 4096}; cuuint32_t b1[5] = {16, 2, 4, 4, 4};
      enc(fn, &M.y, (char*)scr + offsetof(Scratch, yT), 5, d, s, b1, CU_TENSOR_MAP_SWIZZLE_32B, CU_TENSOR_MAP_L2_PROMOTION_NONE); }
    { cuuint64_t d[3] = {64, 640, 24}, s[2] = {3072, 128}; cuuint32_t b1[3] = {64, 32, 2};
      enc(fn, &M.g1, P.Wg, 3, d, s, b1, CU_TENSOR_MAP_SWIZZLE_128B); enc(fn, &M.u1, P.Wu, 3, d, s, b1, CU_TENSOR_MAP_SWIZZLE_128B); }
    { cuuint64_t d[2] = {1536, 640}, s[1] = {3072}; cuuint32_t b1[2] = {64, 64};
      enc(fn, &M.g2, P.Wg, 2, d, s, b1, CU_TENSOR_MAP_SWIZZLE_128B); enc(fn, &M.u2, P.Wu, 2, d, s, b1, CU_TENSOR_MAP_SWIZZLE_128B); }
    { cuuint64_t d[5] = {32, 2, 192, 4, 20}, s[4] = {1280, 8 * 1280, 2 * 1280, 64}; cuuint32_t b1[5] = {32, 2, 4, 4, 5};
      enc(fn, &M.wd, P.Wd, 5, d, s, b1, CU_TENSOR_MAP_SWIZZLE_64B); }
    { cuuint64_t d[3] = {32, 1536, 20}, s[2] = {1280, 64}; cuuint32_t b1[3] = {32, 32, 5};
      enc(fn, &M.wn, P.Wd, 3, d, s, b1, CU_TENSOR_MAP_SWIZZLE_64B); }
    { cuuint64_t d[2] = {3840, 640}, s[1] = {7680}; cuuint32_t b1[2] = {64, 160};
      enc(fn, &M.wm, d_in[11], 2, d, s, b1, CU_TENSOR_MAP_SWIZZLE_128B); }
    { cuuint64_t d[3] = {640, 640, 6}, s[2] = {7680, 1280}; cuuint32_t b1[3] = {128, 5, 1};
      enc(fn, &M.wp, d_in[11], 3, d, s, b1, CU_TENSOR_MAP_SWIZZLE_NONE); }
    { cuuint64_t d[3] = {160, 4, 2048}, s[2] = {320, 1280}; cuuint32_t b1[3] = {168, 1, 8};
      enc(fn, &M.out, d_out, 3, d, s, b1, CU_TENSOR_MAP_SWIZZLE_NONE); }
    cudaFuncSetAttribute(fused_kernel, cudaFuncAttributeMaxDynamicSharedMemorySize, SMEM_BYTES);
    fused_kernel<<<132, 384, SMEM_BYTES>>>(P, M);
}
```

```cpp
#include <cuda_runtime.h>
#include <cuda_bf16.h>
#include <cuda.h>
#include <stdint.h>
#include <stddef.h>
#include <type_traits>

namespace {

constexpr int D_ = 640;

struct Scratch {
    uint4 kvT[D_ * 256], yT[D_ * 256];
    uint4 z[16 * 10 * 1024];
    uint4 hh[16 * 24 * 1024];
    uint4 st2[2048];
    uint4 abc[320];
    uint2 mod[640];
    uint2 ut[5 * 3072];
    uint32_t cnt[64 * 1024];
};
__device__ __align__(1024) Scratch g_s;
#define SC(f, off) padd(P.scr, (uint32_t)offsetof(Scratch, f) + (off))
constexpr int C_KV = 0  , C_Y = 10  , C_Z = 16  , C_HH = 32  ;

constexpr uint32_t WR = 163840, MISC = 229376, SMEM_BYTES = 232448;
constexpr uint32_t ESLOT = 0x31650;
constexpr uint32_t XP = 4112, XB = 65536 + 18432, ST_SH = XB + 2 * XP;
constexpr uint32_t ST_Q = 131072, ST_Y = ST_Q + 20480, ST_S = ST_Y + 10240  , UST = ST_Q;
__host__ __device__ constexpr uint32_t st_kv(int r) { return r == 2 ? ST_Y : r == 1 || r == 4 ? 65536 + 9216 : 65536; }
__host__ __device__ constexpr uint32_t eslot(int r) { return ((ESLOT >> (4 * r)) & 7) << 15; }
constexpr uint32_t PP = 4352;
constexpr uint32_t BARS = MISC, TAB1 = MISC + 688, TAB2 = TAB1 + 32 * 48, CS_TAB = TAB1  , PRF = -256;
constexpr uint32_t GBT = 0, G2B = 8192, G2A = 131072;
enum { B_H = 0, B_KV = 5, B_Q = 10, B_X = 15  , B_MD = 17  , B_AF = 20, B_AL = 30, B_WF = 40, B_G2F = 44, B_RT = 51, B_Y = 52  ,
       B_WE = 54, B_G2E = 58,
       B_UD = 64, B_HD = 65  , B_S0 = 68, B_HS = 69  ,
       B_RD = 72, B_UF = 77, B_TD = 78  , B_T1 = 81, B_YE = 82  , B_GB = 84, NBARS = 85 };
__host__ __device__ constexpr uint32_t bar_count(int i) {
    return i < B_WE ? 1 : i < B_UD ? 16 : i < B_RD ? 8 : i < B_T1 ? 4 : 2;
}
#define GSTAMPIF(c, i) do {} while (0)
#define STAMPIF(c, i) do {} while (0)
#define STAMP(i) do {} while (0)
#define VALIF(c, i, v) do {} while (0)
#define STAMPI STAMPIF
#define STAMPR(i) do {} while (0)
#define TWAIT(i, stmt) stmt
#define STAMPS(k) do {} while (0)
#define QS 4
__host__ __device__ constexpr int epi_slot(int e) { return e * QS / 4; }
#define ER 7
#define MAPM 0
#define RQE 2
#define EI 1
#define SBAR 1
#define FLATE 1
#define E0 1
#define Q2 4
#define G2R 5
#define YH 0
#define WP0 2
#define SEQ0 0x14124310224120ull
#define SEQ1 0x1324441123422140ull
#define NFAST 7
#define EARLYH 0
#define ZE 1
#define N_UT 13
#define NST 5
#define TN(i, v) v
#define TUNING 0
#define ORDER hkhhkxhqkxqqkqxqhwwww
#define TIMES 0, 860, 1570, 2100, 2890, 0, 3810, 0, 4520, 0, 0, 0, 6300, 0, 0, 0, 0, 8400, 0, 0, 0
#define STR2(x) #x
#define STR(x) STR2(x)
constexpr int NORD = sizeof(STR(ORDER)) - 1;
__host__ __device__ constexpr char ord_kind(int i) { return STR(ORDER)[i]; }
__host__ __device__ constexpr int ord_index(int i) { int n = ord_kind(i) == 'k'; for (int j = 0; j < i; j++) n += ord_kind(j) == ord_kind(i); return n; }
__host__ __device__ constexpr int ord_slot(int i) { int n = 0; for (int j = 0; j < i; j++) n += ord_kind(j) == 'k' ? 2 : ord_kind(j) != 'x'; return n; }
__host__ __device__ constexpr int ord_find(char c, int n) { for (int i = 0; i < NORD; i++) if (ord_kind(i) == c && ord_index(i) == n) return i; return -1; }
__host__ __device__ constexpr int ord_count(char c) { int n = 0; for (int i = 0; i < NORD; i++) n += ord_kind(i) == c; return n; }
__host__ __device__ constexpr uint32_t ord_mask(char c) { uint32_t m = 0; for (int i = 0; i < NORD; i++) m |= (uint32_t)(ord_kind(i) == c) << i; return m; }
__host__ __device__ constexpr int ord_time(int i) { constexpr int t[] = {TIMES}; return t[i]; }
constexpr int NWP = ord_count('w');
static_assert(NWP % 2 == 0 && ord_kind(0) == 'h' && ord_count('x') >= 2 && ord_count('k') == 4 && ord_count('q') == 5 && ord_count('h') == 5, "order");
#define TV0 500
#define D_1 TN(0, TV0)
#define TV1 420
#define G_U TN(1, TV1)
#define TV2 590
#define G_ST TN(2, TV2)
#define TV4 2000
#define D_SP TN(4, TV4)
#define TV5 0
#define G_F TN(5, TV5)
#define TV6 7500
#define D_M TN(6, TV6)
#define TV7 700
#define D_PK TN(7, TV7)
#define TV8 500
#define D_PY TN(8, TV8)
#define TV9 100
#define D_PZ TN(9, TV9)
#define TV10 100
#define D_H2 TN(10, TV10)
#define TV11 1400
#define D_UT TN(11, TV11)

__device__ __forceinline__ uint32_t smem_u32(const void* p) { return (uint32_t)__cvta_generic_to_shared(p); }
__device__ __forceinline__ void mbar_init(uint32_t bar, uint32_t cnt) { asm volatile("mbarrier.init.shared::cta.b64 [%0], %1;" :: "r"(bar), "r"(cnt) : "memory"); }
__device__ __forceinline__ void mbar_expect(uint32_t bar, uint32_t bytes) { asm volatile("mbarrier.arrive.expect_tx.shared::cta.b64 _, [%0], %1;" :: "r"(bar), "r"(bytes) : "memory"); }
__device__ __forceinline__ void mbar_arrive_if(uint32_t bar, bool p) { asm volatile("{ .reg .pred p; setp.ne.b32 p, %1, 0; @p mbarrier.arrive.shared::cta.b64 _, [%0]; }" :: "r"(bar), "r"((int)p) : "memory"); }
__device__ __forceinline__ void mbar_arrive_remote_if(uint32_t bar, bool p) { asm volatile("{ .reg .pred p; setp.ne.b32 p, %1, 0; @p mbarrier.arrive.shared::cluster.b64 _, [%0]; }" :: "r"(bar), "r"((int)p) : "memory"); }
#define WAIT_LOOP(op) "{\n .reg .pred p, q; .reg .u32 c; mov.u32 c, 0;\n LAB_WAIT:\n " op " p, [%0], %1;\n @p bra LAB_DONE;\n add.u32 c, c, 1; setp.lt.u32 q, c, 16384;\n @q bra LAB_WAIT;\n LAB_DONE:\n }"
__device__ __forceinline__ void mbar_wait(uint32_t bar, uint32_t parity) { asm volatile(WAIT_LOOP("mbarrier.try_wait.parity.shared::cta.b64") :: "r"(bar), "r"(parity) : "memory"); }
__device__ __forceinline__ bool mbar_test(uint32_t bar, uint32_t parity) {
    uint32_t ok; asm volatile("{ .reg .pred p; mbarrier.test_wait.parity.shared::cta.b64 p, [%1], %2; selp.u32 %0, 1, 0, p; }" : "=r"(ok) : "r"(bar), "r"(parity) : "memory"); return ok;
}
__device__ __forceinline__ uint32_t clock32() { uint32_t t; asm volatile("mov.u32 %0, %%clock;" : "=r"(t) :: "memory"); return t; }
__device__ __forceinline__ void wait_clock(uint32_t t0, uint32_t d) {
    asm volatile("{\n .reg .pred p; .reg .u32 t;\n LAB_CLK:\n mov.u32 t, %%clock; sub.u32 t, t, %0; setp.lt.u32 p, t, %1;\n @p bra LAB_CLK;\n }" :: "r"(t0), "r"(d) : "memory");
}
__device__ __forceinline__ bool elect() { uint32_t p; asm volatile("{ .reg .pred p; elect.sync _|p, 0xffffffff; selp.u32 %0, 1, 0, p; }" : "=r"(p)); return p; }
__device__ __forceinline__ void pf_map(const CUtensorMap* m) { asm volatile("prefetch.tensormap [%0];" :: "l"(m) : "memory"); }
__device__ __forceinline__ void bar_sync(int id, int n) { asm volatile("bar.sync %0, %1;" :: "r"(id), "r"(n) : "memory"); }
__device__ __forceinline__ bool bar_or(int id, int n, bool c) {
    uint32_t r; asm volatile("{ .reg .pred p, q; setp.ne.b32 p, %3, 0; bar.red.or.pred q, %1, %2, p; selp.u32 %0, 1, 0, q; }" : "=r"(r) : "r"(id), "r"(n), "r"((int)c) : "memory"); return r;
}
__device__ __forceinline__ void wait_until(uint32_t t1) {
    asm volatile("{\n .reg .pred p; .reg .s32 t;\n LAB_CLK:\n mov.u32 t, %%clock; sub.s32 t, t, %0; setp.lt.s32 p, t, 0;\n @p bra LAB_CLK;\n }" :: "r"(t1) : "memory");
}
__device__ __forceinline__ void pause(uint32_t d) { wait_clock(clock32(), d); }
__device__ __forceinline__ void bar_arrive(int id, int n) { asm volatile("bar.arrive %0, %1;" :: "r"(id), "r"(n) : "memory"); }
__device__ __forceinline__ void fence_async_smem() { asm volatile("fence.proxy.async.shared::cta;" ::: "memory"); }
__device__ __forceinline__ void fence_async_glob() { asm volatile("fence.proxy.async.global;" ::: "memory"); }
__device__ __forceinline__ void fence_acq() { asm volatile("fence.acquire.gpu;" ::: "memory"); }
__device__ __forceinline__ void bulk_g2s(uint32_t dst, const void* src, uint32_t bytes, uint32_t bar) {
    asm volatile("cp.async.bulk.shared::cluster.global.mbarrier::complete_tx::bytes [%0], [%1], %2, [%3];" :: "r"(dst), "l"(src), "r"(bytes), "r"(bar) : "memory");
}
__device__ __forceinline__ void pf_l2(const void* src, uint32_t bytes) { asm volatile("cp.async.bulk.prefetch.L2.global [%0], %1;" :: "l"(src), "r"(bytes) : "memory"); }
__device__ __forceinline__ void tma2d(uint32_t dst, const CUtensorMap* m, int c0, int c1, uint32_t bar) {
    asm volatile("cp.async.bulk.tensor.2d.shared::cluster.global.mbarrier::complete_tx::bytes [%0], [%1, {%3, %4}], [%2];" :: "r"(dst), "l"(m), "r"(bar), "r"(c0), "r"(c1) : "memory");
}
__device__ __forceinline__ void tma3d(uint32_t dst, const CUtensorMap* m, int c1, int c2, uint32_t bar) {
    asm volatile("cp.async.bulk.tensor.3d.shared::cluster.global.mbarrier::complete_tx::bytes [%0], [%1, {%5, %3, %4}], [%2];" :: "r"(dst), "l"(m), "r"(bar), "r"(c1), "r"(c2), "r"(0) : "memory");
}
__device__ __forceinline__ void tma4d(uint32_t dst, const CUtensorMap* m, int c0, int c2, uint32_t bar) {
    asm volatile("cp.async.bulk.tensor.4d.shared::cluster.global.mbarrier::complete_tx::bytes [%0], [%1, {%3, %5, %4, %5}], [%2];" :: "r"(dst), "l"(m), "r"(bar), "r"(c0), "r"(c2), "r"(0) : "memory");
}
__device__ __forceinline__ void tma5d(uint32_t dst, const CUtensorMap* m, int c0, int c4, uint32_t bar) {
    asm volatile("cp.async.bulk.tensor.5d.shared::cluster.global.mbarrier::complete_tx::bytes [%0], [%1, {%3, %5, %5, %5, %4}], [%2];" :: "r"(dst), "l"(m), "r"(bar), "r"(c0), "r"(c4), "r"(0) : "memory");
}
__device__ __forceinline__ void tma5d_mc(uint32_t dst, const CUtensorMap* m, int c2, int c4, uint32_t bar) {
    asm volatile("cp.async.bulk.tensor.5d.shared::cluster.global.mbarrier::complete_tx::bytes.multicast::cluster [%0], [%1, {%5, %5, %3, %5, %4}], [%2], %6;"
                 :: "r"(dst), "l"(m), "r"(bar), "r"(c2), "r"(c4), "r"(0), "h"((uint16_t)3) : "memory");
}
__device__ __forceinline__ void tma3d_mc(uint32_t dst, const CUtensorMap* m, int c1, int c2, uint32_t bar) {
    asm volatile("cp.async.bulk.tensor.3d.shared::cluster.global.mbarrier::complete_tx::bytes.multicast::cluster [%0], [%1, {%5, %3, %4}], [%2], %6;"
                 :: "r"(dst), "l"(m), "r"(bar), "r"(c1), "r"(c2), "r"(0), "h"((uint16_t)3) : "memory");
}
__device__ __forceinline__ void tma2d_mc(uint32_t dst, const CUtensorMap* m, int c0, int c1, uint32_t bar) {
    asm volatile("cp.async.bulk.tensor.2d.shared::cluster.global.mbarrier::complete_tx::bytes.multicast::cluster [%0], [%1, {%3, %4}], [%2], %5;"
                 :: "r"(dst), "l"(m), "r"(bar), "r"(c0), "r"(c1), "h"((uint16_t)3) : "memory");
}
__device__ __forceinline__ void tma3d_red(const CUtensorMap* m, uint32_t src, int c1, int c2) {
    asm volatile("cp.reduce.async.bulk.tensor.3d.global.shared::cta.add.bulk_group [%0, {%4, %2, %3}], [%1];" :: "l"(m), "r"(src), "r"(c1), "r"(c2), "r"(0) : "memory");
}
__device__ __forceinline__ void red_if(const void* c, uint32_t inc, bool p) { asm volatile("{ .reg .pred p; setp.ne.b32 p, %2, 0; @p red.relaxed.gpu.global.add.u32 [%0], %1; }" :: "l"(c), "r"(inc), "r"((int)p) : "memory"); }
__device__ __forceinline__ uint32_t ldg_rlx32(const void* p) { uint32_t v; asm volatile("ld.relaxed.gpu.global.u32 %0, [%1];" : "=r"(v) : "l"(p) : "memory"); return v; }
__device__ __forceinline__ uint32_t ldg_late(const char* p, int lane) { return ldg_rlx32(p + (lane & 1) * 4); }
__device__ __forceinline__ bool reached(uint32_t v, uint32_t target) { return __ballot_sync(~0u, (int)(v - target) >= 0) & 1; }
__device__ __forceinline__ uint2 ldg_rlx64(const void* p) { uint2 v; asm volatile("{ .reg .b64 x; ld.relaxed.gpu.global.b64 x, [%2]; mov.b64 {%0, %1}, x; }" : "=r"(v.x), "=r"(v.y) : "l"(p) : "memory"); return v; }
__device__ __forceinline__ void ldg_rlx128_if(uint4& v, const void* p, bool c) {
    asm volatile("{ .reg .b128 t; .reg .b64 x, y; .reg .pred p; setp.ne.b32 p, %5, 0; mov.b64 x, {%0, %1}; mov.b64 y, {%2, %3}; mov.b128 t, {x, y};\n"
                 " @p ld.relaxed.gpu.global.b128 t, [%4]; mov.b128 {x, y}, t; mov.b64 {%0, %1}, x; mov.b64 {%2, %3}, y; }"
                 : "+r"(v.x), "+r"(v.y), "+r"(v.z), "+r"(v.w) : "l"(p), "r"((int)c) : "memory");
}
__device__ __forceinline__ uint4 ldg_rlx2x64(const void* p) { uint4 v; asm volatile("{ .reg .b64 x, y; ld.relaxed.gpu.global.v2.b64 {x, y}, [%4]; mov.b64 {%0, %1}, x; mov.b64 {%2, %3}, y; }" : "=r"(v.x), "=r"(v.y), "=r"(v.z), "=r"(v.w) : "l"(p) : "memory"); return v; }
__device__ __forceinline__ void stg_rlx128(void* p, uint32_t x, uint32_t y, uint32_t z, uint32_t w) {
    asm volatile("{ .reg .b128 t; .reg .b64 a, b; mov.b64 a, {%1, %2}; mov.b64 b, {%3, %4}; mov.b128 t, {a, b}; st.relaxed.gpu.global.b128 [%0], t; }" :: "l"(p), "r"(x), "r"(y), "r"(z), "r"(w) : "memory");
}
__device__ __forceinline__ void stg_rlx128_if(void* p, const uint32_t* v, bool c) {
    asm volatile("{ .reg .pred p; .reg .b128 t; .reg .b64 a, b; setp.ne.b32 p, %5, 0; mov.b64 a, {%1, %2}; mov.b64 b, {%3, %4}; mov.b128 t, {a, b}; @p st.relaxed.gpu.global.b128 [%0], t; }" :: "l"(p), "r"(v[0]), "r"(v[1]), "r"(v[2]), "r"(v[3]), "r"((int)c) : "memory");
}
__device__ __forceinline__ void stg128(void* p, uint32_t x, uint32_t y, uint32_t z, uint32_t w) { asm volatile("st.global.v4.b32 [%0], {%1,%2,%3,%4};" :: "l"(p), "r"(x), "r"(y), "r"(z), "r"(w) : "memory"); }
template<int W> __device__ __forceinline__ void stg_tag(void* p, const uint32_t* o, uint32_t tm, uint32_t par) {
    const uint32_t t = (o[W] & ~tm) | (par & tm);
    asm volatile("st.relaxed.gpu.global.v4.b32 [%0], {%1,%2,%3,%4};" :: "l"(p), "r"(W ? o[0] : t), "r"(W ? t : o[1]), "r"(o[2]), "r"(o[3]) : "memory");
}
__device__ __forceinline__ void poll_cnt(const void* c, uint32_t target) {
    asm volatile("{\n .reg .pred p, q; .reg .u32 c, v; mov.u32 c, 0;\n LAB_POLL:\n ld.relaxed.gpu.global.u32 v, [%0];\n sub.u32 v, v, %1; setp.ge.s32 p, v, 0;\n @p bra LAB_PDONE;\n"
                 " add.u32 c, c, 1; setp.lt.u32 q, c, 20000;\n @q bra LAB_POLL;\n LAB_PDONE:\n }" :: "l"(c), "r"(target) : "memory");
}
template<int N, typename F> __device__ __forceinline__ void ll_wait(uint2* v, uint32_t tag, F&& addr) {
    #pragma unroll 1
    for (int it = 0; it < 20000; it++) {
        uint32_t bad = 0;
        #pragma unroll
        for (int i = 0; i < N; i++) bad |= v[i].y ^ tag;
        if (!__any_sync(~0u, bad != 0)) break;
        asm volatile("nanosleep.u32 100;");
        #pragma unroll
        for (int i = 0; i < N; i++) v[i] = ldg_rlx64(addr(i));
    }
}
__device__ __forceinline__ uint4 lds128(uint32_t a) { uint4 v; asm volatile("ld.shared.v4.b32 {%0,%1,%2,%3}, [%4];" : "=r"(v.x), "=r"(v.y), "=r"(v.z), "=r"(v.w) : "r"(a) : "memory"); return v; }
__device__ __forceinline__ uint2 lds64(uint32_t a) { uint2 v; asm volatile("ld.shared.v2.b32 {%0,%1}, [%2];" : "=r"(v.x), "=r"(v.y) : "r"(a) : "memory"); return v; }
__device__ __forceinline__ void sts128(uint32_t a, uint32_t x, uint32_t y, uint32_t z, uint32_t w) { asm volatile("st.shared.v4.b32 [%0], {%1,%2,%3,%4};" :: "r"(a), "r"(x), "r"(y), "r"(z), "r"(w) : "memory"); }
__device__ __forceinline__ void sts32(uint32_t a, uint32_t x) { asm volatile("st.shared.b32 [%0], %1;" :: "r"(a), "r"(x) : "memory"); }
__device__ __forceinline__ void ldsm4t(uint32_t* r, uint32_t a) { asm volatile("ldmatrix.sync.aligned.m8n8.x4.trans.shared.b16 {%0,%1,%2,%3}, [%4];" : "=r"(r[0]), "=r"(r[1]), "=r"(r[2]), "=r"(r[3]) : "r"(a) : "memory"); }
__device__ __forceinline__ void ldsm2t(uint32_t& r0, uint32_t& r1, uint32_t a) { asm volatile("ldmatrix.sync.aligned.m8n8.x2.trans.shared.b16 {%0,%1}, [%2];" : "=r"(r0), "=r"(r1) : "r"(a) : "memory"); }
__device__ __forceinline__ void ldsm4t_if(uint32_t* r, uint32_t a, bool c) { asm volatile("{ .reg .pred p; setp.ne.b32 p, %5, 0; @p ldmatrix.sync.aligned.m8n8.x4.trans.shared.b16 {%0,%1,%2,%3}, [%4]; }" : "+r"(r[0]), "+r"(r[1]), "+r"(r[2]), "+r"(r[3]) : "r"(a), "r"((int)c) : "memory"); }
__device__ __forceinline__ void ldsm2t_if(uint32_t* r, uint32_t a, bool c) { asm volatile("{ .reg .pred p; setp.ne.b32 p, %3, 0; @p ldmatrix.sync.aligned.m8n8.x2.trans.shared.b16 {%0,%1}, [%2]; }" : "+r"(r[0]), "+r"(r[1]) : "r"(a), "r"((int)c) : "memory"); }
__device__ __forceinline__ void lds128_if(uint4& v, uint32_t a, bool c) { asm volatile("{ .reg .pred p; setp.ne.b32 p, %5, 0; @p ld.shared.v4.b32 {%0,%1,%2,%3}, [%4]; }" : "+r"(v.x), "+r"(v.y), "+r"(v.z), "+r"(v.w) : "r"(a), "r"((int)c) : "memory"); }
__device__ __forceinline__ void cp16(uint32_t d, const void* s) { asm volatile("cp.async.cg.shared.global [%0], [%1], 16;" :: "r"(d), "l"(s) : "memory"); }
__device__ __forceinline__ char* padd(const void* p, uint32_t off) { char* r; asm("{ .reg .u64 t; cvt.u64.u32 t, %2; add.u64 %0, %1, t; }" : "=l"(r) : "l"(p), "r"(off)); return r; }
__device__ __forceinline__ uint32_t prmt(uint32_t a, uint32_t b, uint32_t s) { uint32_t r; asm("prmt.b32 %0, %1, %2, %3;" : "=r"(r) : "r"(a), "r"(b), "r"(s)); return r; }
__device__ __forceinline__ uint32_t pack2(float lo, float hi) { uint32_t r; asm("cvt.rn.bf16x2.f32 %0, %1, %2;" : "=r"(r) : "f"(hi), "f"(lo)); return r; }
__device__ __forceinline__ uint32_t pack2relu(float lo, float hi) { uint32_t r; asm("cvt.rn.relu.bf16x2.f32 %0, %1, %2;" : "=r"(r) : "f"(hi), "f"(lo)); return r; }
__device__ __forceinline__ float bflo(uint32_t w) { return __uint_as_float(w << 16); }
__device__ __forceinline__ float bfhi(uint32_t w) { return __uint_as_float(w & 0xffff0000u); }
__device__ __forceinline__ float bfround(float x) { return bflo(pack2(x, x)); }
__device__ __forceinline__ uint32_t hmul2(uint32_t a, uint32_t b) { uint32_t r; asm("mul.rn.bf16x2 %0, %1, %2;" : "=r"(r) : "r"(a), "r"(b)); return r; }
__device__ __forceinline__ uint32_t hadd2(uint32_t a, uint32_t b) { uint32_t r; asm("add.rn.bf16x2 %0, %1, %2;" : "=r"(r) : "r"(a), "r"(b)); return r; }
__device__ __forceinline__ uint32_t hfma2(uint32_t a, uint32_t b, uint32_t c) { uint32_t r; asm("fma.rn.bf16x2 %0, %1, %2, %3;" : "=r"(r) : "r"(a), "r"(b), "r"(c)); return r; }
__device__ __forceinline__ void sched_bar() { asm volatile("pmevent 1;" ::: "memory"); }
template<int H> __device__ __forceinline__ uint32_t hfma2s(uint32_t a, uint32_t w, uint32_t c) {
    uint32_t r;
    if (H) asm("{ .reg .b16 l, h; .reg .b32 t; mov.b32 {l, h}, %2; mov.b32 t, {h, h}; fma.rn.bf16x2 %0, %1, t, %3; }" : "=r"(r) : "r"(a), "r"(w), "r"(c));
    else asm("{ .reg .b16 l, h; .reg .b32 t; mov.b32 {l, h}, %2; mov.b32 t, {l, l}; fma.rn.bf16x2 %0, %1, t, %3; }" : "=r"(r) : "r"(a), "r"(w), "r"(c));
    return r;
}
__device__ __forceinline__ void bump(uint32_t& a, uint32_t d) { asm volatile("add.u32 %0, %0, %1;" : "+r"(a) : "r"(d) : "memory"); }
template<int D> __device__ __forceinline__ void bump(char*& p) { asm volatile("add.s64 %0, %0, %1;" : "+l"(p) : "n"(D) : "memory"); }
__device__ __forceinline__ void wg_fence() { asm volatile("wgmma.fence.sync.aligned;" ::: "memory"); }
__device__ __forceinline__ void wg_commit() { asm volatile("wgmma.commit_group.sync.aligned;" ::: "memory"); }
template<int N> __device__ __forceinline__ void wg_wait() { asm volatile("wgmma.wait_group.sync.aligned %0;" :: "n"(N) : "memory"); }
template<int N> __device__ __forceinline__ void pin(float* d) {
    #pragma unroll
    for (int i = 0; i < N; i++) asm volatile("" : "+f"(d[i]) :: "memory");
}
__device__ __forceinline__ uint32_t dlo(uint32_t addr, uint32_t lbo) { return ((addr & 0x3FFFF) >> 4) | ((lbo >> 4) << 16); }
__host__ __device__ constexpr uint32_t dhi(uint32_t sbo, uint32_t sw) { return (sbo >> 4) | (sw << 30); }

template<int N> struct WG;
template<> struct WG<8> { template<int TA, int TB> static __device__ __forceinline__ void ss(float* d, uint32_t alo, uint32_t ahi, uint32_t blo, uint32_t bhi, int sd) {
  asm volatile("{ .reg .pred p; .reg .b64 da, db; mov.b64 da, {%4,%5}; mov.b64 db, {%6,%7}; setp.ne.b32 p, %8, 0;\n"
    "wgmma.mma_async.sync.aligned.m64n8k16.f32.bf16.bf16 {%0,%1,%2,%3}, da, db, p, 1, 1, %9, %10; }"
    : "+f"(d[0]),"+f"(d[1]),"+f"(d[2]),"+f"(d[3])
    : "r"(alo), "r"(ahi), "r"(blo), "r"(bhi), "r"(sd), "n"(TA), "n"(TB)); }
};
template<> struct WG<16> { template<int TA, int TB> static __device__ __forceinline__ void ss(float* d, uint32_t alo, uint32_t ahi, uint32_t blo, uint32_t bhi, int sd) {
  asm volatile("{ .reg .pred p; .reg .b64 da, db; mov.b64 da, {%8,%9}; mov.b64 db, {%10,%11}; setp.ne.b32 p, %12, 0;\n"
    "wgmma.mma_async.sync.aligned.m64n16k16.f32.bf16.bf16 {%0,%1,%2,%3,%4,%5,%6,%7}, da, db, p, 1, 1, %13, %14; }"
    : "+f"(d[0]),"+f"(d[1]),"+f"(d[2]),"+f"(d[3]),"+f"(d[4]),"+f"(d[5]),"+f"(d[6]),"+f"(d[7])
    : "r"(alo), "r"(ahi), "r"(blo), "r"(bhi), "r"(sd), "n"(TA), "n"(TB)); }
};
template<> struct WG<32> { template<int TA, int TB> static __device__ __forceinline__ void ss(float* d, uint32_t alo, uint32_t ahi, uint32_t blo, uint32_t bhi, int sd) {
  asm volatile("{ .reg .pred p; .reg .b64 da, db; mov.b64 da, {%16,%17}; mov.b64 db, {%18,%19}; setp.ne.b32 p, %20, 0;\n"
    "wgmma.mma_async.sync.aligned.m64n32k16.f32.bf16.bf16 {%0,%1,%2,%3,%4,%5,%6,%7,%8,%9,%10,%11,%12,%13,%14,%15}, da, db, p, 1, 1, %21, %22; }"
    : "+f"(d[0]),"+f"(d[1]),"+f"(d[2]),"+f"(d[3]),"+f"(d[4]),"+f"(d[5]),"+f"(d[6]),"+f"(d[7]),"+f"(d[8]),"+f"(d[9]),"+f"(d[10]),"+f"(d[11]),"+f"(d[12]),"+f"(d[13]),"+f"(d[14]),"+f"(d[15])
    : "r"(alo), "r"(ahi), "r"(blo), "r"(bhi), "r"(sd), "n"(TA), "n"(TB)); }
};
template<> struct WG<48> { template<int TA, int TB> static __device__ __forceinline__ void ss(float* d, uint32_t alo, uint32_t ahi, uint32_t blo, uint32_t bhi, int sd) {
  asm volatile("{ .reg .pred p; .reg .b64 da, db; mov.b64 da, {%24,%25}; mov.b64 db, {%26,%27}; setp.ne.b32 p, %28, 0;\n"
    "wgmma.mma_async.sync.aligned.m64n48k16.f32.bf16.bf16 {%0,%1,%2,%3,%4,%5,%6,%7,%8,%9,%10,%11,%12,%13,%14,%15,%16,%17,%18,%19,%20,%21,%22,%23}, da, db, p, 1, 1, %29, %30; }"
    : "+f"(d[0]),"+f"(d[1]),"+f"(d[2]),"+f"(d[3]),"+f"(d[4]),"+f"(d[5]),"+f"(d[6]),"+f"(d[7]),"+f"(d[8]),"+f"(d[9]),"+f"(d[10]),"+f"(d[11]),"+f"(d[12]),"+f"(d[13]),"+f"(d[14]),"+f"(d[15]),"+f"(d[16]),"+f"(d[17]),"+f"(d[18]),"+f"(d[19]),"+f"(d[20]),"+f"(d[21]),"+f"(d[22]),"+f"(d[23])
    : "r"(alo), "r"(ahi), "r"(blo), "r"(bhi), "r"(sd), "n"(TA), "n"(TB)); }
};
template<> struct WG<64> { template<int TA, int TB> static __device__ __forceinline__ void ss(float* d, uint32_t alo, uint32_t ahi, uint32_t blo, uint32_t bhi, int sd) {
  asm volatile("{ .reg .pred p; .reg .b64 da, db; mov.b64 da, {%32,%33}; mov.b64 db, {%34,%35}; setp.ne.b32 p, %36, 0;\n"
    "wgmma.mma_async.sync.aligned.m64n64k16.f32.bf16.bf16 {%0,%1,%2,%3,%4,%5,%6,%7,%8,%9,%10,%11,%12,%13,%14,%15,%16,%17,%18,%19,%20,%21,%22,%23,%24,%25,%26,%27,%28,%29,%30,%31}, da, db, p, 1, 1, %37, %38; }"
    : "+f"(d[0]),"+f"(d[1]),"+f"(d[2]),"+f"(d[3]),"+f"(d[4]),"+f"(d[5]),"+f"(d[6]),"+f"(d[7]),"+f"(d[8]),"+f"(d[9]),"+f"(d[10]),"+f"(d[11]),"+f"(d[12]),"+f"(d[13]),"+f"(d[14]),"+f"(d[15]),"+f"(d[16]),"+f"(d[17]),"+f"(d[18]),"+f"(d[19]),"+f"(d[20]),"+f"(d[21]),"+f"(d[22]),"+f"(d[23]),"+f"(d[24]),"+f"(d[25]),"+f"(d[26]),"+f"(d[27]),"+f"(d[28]),"+f"(d[29]),"+f"(d[30]),"+f"(d[31])
    : "r"(alo), "r"(ahi), "r"(blo), "r"(bhi), "r"(sd), "n"(TA), "n"(TB)); }
};
template<> struct WG<80> { template<int TA, int TB> static __device__ __forceinline__ void ss(float* d, uint32_t alo, uint32_t ahi, uint32_t blo, uint32_t bhi, int sd) {
  asm volatile("{ .reg .pred p; .reg .b64 da, db; mov.b64 da, {%40,%41}; mov.b64 db, {%42,%43}; setp.ne.b32 p, %44, 0;\n"
    "wgmma.mma_async.sync.aligned.m64n80k16.f32.bf16.bf16 {%0,%1,%2,%3,%4,%5,%6,%7,%8,%9,%10,%11,%12,%13,%14,%15,%16,%17,%18,%19,%20,%21,%22,%23,%24,%25,%26,%27,%28,%29,%30,%31,%32,%33,%34,%35,%36,%37,%38,%39}, da, db, p, 1, 1, %45, %46; }"
    : "+f"(d[0]),"+f"(d[1]),"+f"(d[2]),"+f"(d[3]),"+f"(d[4]),"+f"(d[5]),"+f"(d[6]),"+f"(d[7]),"+f"(d[8]),"+f"(d[9]),"+f"(d[10]),"+f"(d[11]),"+f"(d[12]),"+f"(d[13]),"+f"(d[14]),"+f"(d[15]),"+f"(d[16]),"+f"(d[17]),"+f"(d[18]),"+f"(d[19]),"+f"(d[20]),"+f"(d[21]),"+f"(d[22]),"+f"(d[23]),"+f"(d[24]),"+f"(d[25]),"+f"(d[26]),"+f"(d[27]),"+f"(d[28]),"+f"(d[29]),"+f"(d[30]),"+f"(d[31]),"+f"(d[32]),"+f"(d[33]),"+f"(d[34]),"+f"(d[35]),"+f"(d[36]),"+f"(d[37]),"+f"(d[38]),"+f"(d[39])
    : "r"(alo), "r"(ahi), "r"(blo), "r"(bhi), "r"(sd), "n"(TA), "n"(TB)); }
};
template<> struct WG<96> { template<int TA, int TB> static __device__ __forceinline__ void ss(float* d, uint32_t alo, uint32_t ahi, uint32_t blo, uint32_t bhi, int sd) {
  asm volatile("{ .reg .pred p; .reg .b64 da, db; mov.b64 da, {%48,%49}; mov.b64 db, {%50,%51}; setp.ne.b32 p, %52, 0;\n"
    "wgmma.mma_async.sync.aligned.m64n96k16.f32.bf16.bf16 {%0,%1,%2,%3,%4,%5,%6,%7,%8,%9,%10,%11,%12,%13,%14,%15,%16,%17,%18,%19,%20,%21,%22,%23,%24,%25,%26,%27,%28,%29,%30,%31,%32,%33,%34,%35,%36,%37,%38,%39,%40,%41,%42,%43,%44,%45,%46,%47}, da, db, p, 1, 1, %53, %54; }"
    : "+f"(d[0]),"+f"(d[1]),"+f"(d[2]),"+f"(d[3]),"+f"(d[4]),"+f"(d[5]),"+f"(d[6]),"+f"(d[7]),"+f"(d[8]),"+f"(d[9]),"+f"(d[10]),"+f"(d[11]),"+f"(d[12]),"+f"(d[13]),"+f"(d[14]),"+f"(d[15]),"+f"(d[16]),"+f"(d[17]),"+f"(d[18]),"+f"(d[19]),"+f"(d[20]),"+f"(d[21]),"+f"(d[22]),"+f"(d[23]),"+f"(d[24]),"+f"(d[25]),"+f"(d[26]),"+f"(d[27]),"+f"(d[28]),"+f"(d[29]),"+f"(d[30]),"+f"(d[31]),"+f"(d[32]),"+f"(d[33]),"+f"(d[34]),"+f"(d[35]),"+f"(d[36]),"+f"(d[37]),"+f"(d[38]),"+f"(d[39]),"+f"(d[40]),"+f"(d[41]),"+f"(d[42]),"+f"(d[43]),"+f"(d[44]),"+f"(d[45]),"+f"(d[46]),"+f"(d[47])
    : "r"(alo), "r"(ahi), "r"(blo), "r"(bhi), "r"(sd), "n"(TA), "n"(TB)); }
};
template<> struct WG<112> { template<int TA, int TB> static __device__ __forceinline__ void ss(float* d, uint32_t alo, uint32_t ahi, uint32_t blo, uint32_t bhi, int sd) {
  asm volatile("{ .reg .pred p; .reg .b64 da, db; mov.b64 da, {%56,%57}; mov.b64 db, {%58,%59}; setp.ne.b32 p, %60, 0;\n"
    "wgmma.mma_async.sync.aligned.m64n112k16.f32.bf16.bf16 {%0,%1,%2,%3,%4,%5,%6,%7,%8,%9,%10,%11,%12,%13,%14,%15,%16,%17,%18,%19,%20,%21,%22,%23,%24,%25,%26,%27,%28,%29,%30,%31,%32,%33,%34,%35,%36,%37,%38,%39,%40,%41,%42,%43,%44,%45,%46,%47,%48,%49,%50,%51,%52,%53,%54,%55}, da, db, p, 1, 1, %61, %62; }"
    : "+f"(d[0]),"+f"(d[1]),"+f"(d[2]),"+f"(d[3]),"+f"(d[4]),"+f"(d[5]),"+f"(d[6]),"+f"(d[7]),"+f"(d[8]),"+f"(d[9]),"+f"(d[10]),"+f"(d[11]),"+f"(d[12]),"+f"(d[13]),"+f"(d[14]),"+f"(d[15]),"+f"(d[16]),"+f"(d[17]),"+f"(d[18]),"+f"(d[19]),"+f"(d[20]),"+f"(d[21]),"+f"(d[22]),"+f"(d[23]),"+f"(d[24]),"+f"(d[25]),"+f"(d[26]),"+f"(d[27]),"+f"(d[28]),"+f"(d[29]),"+f"(d[30]),"+f"(d[31]),"+f"(d[32]),"+f"(d[33]),"+f"(d[34]),"+f"(d[35]),"+f"(d[36]),"+f"(d[37]),"+f"(d[38]),"+f"(d[39]),"+f"(d[40]),"+f"(d[41]),"+f"(d[42]),"+f"(d[43]),"+f"(d[44]),"+f"(d[45]),"+f"(d[46]),"+f"(d[47]),"+f"(d[48]),"+f"(d[49]),"+f"(d[50]),"+f"(d[51]),"+f"(d[52]),"+f"(d[53]),"+f"(d[54]),"+f"(d[55])
    : "r"(alo), "r"(ahi), "r"(blo), "r"(bhi), "r"(sd), "n"(TA), "n"(TB)); }
};
template<> struct WG<128> { template<int TA, int TB> static __device__ __forceinline__ void ss(float* d, uint32_t alo, uint32_t ahi, uint32_t blo, uint32_t bhi, int sd) {
  asm volatile("{ .reg .pred p; .reg .b64 da, db; mov.b64 da, {%64,%65}; mov.b64 db, {%66,%67}; setp.ne.b32 p, %68, 0;\n"
    "wgmma.mma_async.sync.aligned.m64n128k16.f32.bf16.bf16 {%0,%1,%2,%3,%4,%5,%6,%7,%8,%9,%10,%11,%12,%13,%14,%15,%16,%17,%18,%19,%20,%21,%22,%23,%24,%25,%26,%27,%28,%29,%30,%31,%32,%33,%34,%35,%36,%37,%38,%39,%40,%41,%42,%43,%44,%45,%46,%47,%48,%49,%50,%51,%52,%53,%54,%55,%56,%57,%58,%59,%60,%61,%62,%63}, da, db, p, 1, 1, %69, %70; }"
    : "+f"(d[0]),"+f"(d[1]),"+f"(d[2]),"+f"(d[3]),"+f"(d[4]),"+f"(d[5]),"+f"(d[6]),"+f"(d[7]),"+f"(d[8]),"+f"(d[9]),"+f"(d[10]),"+f"(d[11]),"+f"(d[12]),"+f"(d[13]),"+f"(d[14]),"+f"(d[15]),"+f"(d[16]),"+f"(d[17]),"+f"(d[18]),"+f"(d[19]),"+f"(d[20]),"+f"(d[21]),"+f"(d[22]),"+f"(d[23]),"+f"(d[24]),"+f"(d[25]),"+f"(d[26]),"+f"(d[27]),"+f"(d[28]),"+f"(d[29]),"+f"(d[30]),"+f"(d[31]),"+f"(d[32]),"+f"(d[33]),"+f"(d[34]),"+f"(d[35]),"+f"(d[36]),"+f"(d[37]),"+f"(d[38]),"+f"(d[39]),"+f"(d[40]),"+f"(d[41]),"+f"(d[42]),"+f"(d[43]),"+f"(d[44]),"+f"(d[45]),"+f"(d[46]),"+f"(d[47]),"+f"(d[48]),"+f"(d[49]),"+f"(d[50]),"+f"(d[51]),"+f"(d[52]),"+f"(d[53]),"+f"(d[54]),"+f"(d[55]),"+f"(d[56]),"+f"(d[57]),"+f"(d[58]),"+f"(d[59]),"+f"(d[60]),"+f"(d[61]),"+f"(d[62]),"+f"(d[63])
    : "r"(alo), "r"(ahi), "r"(blo), "r"(bhi), "r"(sd), "n"(TA), "n"(TB)); }
  template<int TB> static __device__ __forceinline__ void rs(float* d, uint32_t a0, uint32_t a1, uint32_t a2, uint32_t a3, uint32_t blo, uint32_t bhi, int sd) {
  asm volatile("{ .reg .pred p; .reg .b64 db; mov.b64 db, {%68,%69}; setp.ne.b32 p, %71, 0;\n"
    "wgmma.mma_async.sync.aligned.m64n128k16.f32.bf16.bf16 {%0,%1,%2,%3,%4,%5,%6,%7,%8,%9,%10,%11,%12,%13,%14,%15,%16,%17,%18,%19,%20,%21,%22,%23,%24,%25,%26,%27,%28,%29,%30,%31,%32,%33,%34,%35,%36,%37,%38,%39,%40,%41,%42,%43,%44,%45,%46,%47,%48,%49,%50,%51,%52,%53,%54,%55,%56,%57,%58,%59,%60,%61,%62,%63}, {%64,%65,%66,%67}, db, p, 1, 1, %70; }"
    : "+f"(d[0]),"+f"(d[1]),"+f"(d[2]),"+f"(d[3]),"+f"(d[4]),"+f"(d[5]),"+f"(d[6]),"+f"(d[7]),"+f"(d[8]),"+f"(d[9]),"+f"(d[10]),"+f"(d[11]),"+f"(d[12]),"+f"(d[13]),"+f"(d[14]),"+f"(d[15]),"+f"(d[16]),"+f"(d[17]),"+f"(d[18]),"+f"(d[19]),"+f"(d[20]),"+f"(d[21]),"+f"(d[22]),"+f"(d[23]),"+f"(d[24]),"+f"(d[25]),"+f"(d[26]),"+f"(d[27]),"+f"(d[28]),"+f"(d[29]),"+f"(d[30]),"+f"(d[31]),"+f"(d[32]),"+f"(d[33]),"+f"(d[34]),"+f"(d[35]),"+f"(d[36]),"+f"(d[37]),"+f"(d[38]),"+f"(d[39]),"+f"(d[40]),"+f"(d[41]),"+f"(d[42]),"+f"(d[43]),"+f"(d[44]),"+f"(d[45]),"+f"(d[46]),"+f"(d[47]),"+f"(d[48]),"+f"(d[49]),"+f"(d[50]),"+f"(d[51]),"+f"(d[52]),"+f"(d[53]),"+f"(d[54]),"+f"(d[55]),"+f"(d[56]),"+f"(d[57]),"+f"(d[58]),"+f"(d[59]),"+f"(d[60]),"+f"(d[61]),"+f"(d[62]),"+f"(d[63])
    : "r"(a0), "r"(a1), "r"(a2), "r"(a3), "r"(blo), "r"(bhi), "n"(TB), "r"(sd)); }
};
template<> struct WG<144> { template<int TA, int TB> static __device__ __forceinline__ void ss(float* d, uint32_t alo, uint32_t ahi, uint32_t blo, uint32_t bhi, int sd) {
  asm volatile("{ .reg .pred p; .reg .b64 da, db; mov.b64 da, {%72,%73}; mov.b64 db, {%74,%75}; setp.ne.b32 p, %76, 0;\n"
    "wgmma.mma_async.sync.aligned.m64n144k16.f32.bf16.bf16 {%0,%1,%2,%3,%4,%5,%6,%7,%8,%9,%10,%11,%12,%13,%14,%15,%16,%17,%18,%19,%20,%21,%22,%23,%24,%25,%26,%27,%28,%29,%30,%31,%32,%33,%34,%35,%36,%37,%38,%39,%40,%41,%42,%43,%44,%45,%46,%47,%48,%49,%50,%51,%52,%53,%54,%55,%56,%57,%58,%59,%60,%61,%62,%63,%64,%65,%66,%67,%68,%69,%70,%71}, da, db, p, 1, 1, %77, %78; }"
    : "+f"(d[0]),"+f"(d[1]),"+f"(d[2]),"+f"(d[3]),"+f"(d[4]),"+f"(d[5]),"+f"(d[6]),"+f"(d[7]),"+f"(d[8]),"+f"(d[9]),"+f"(d[10]),"+f"(d[11]),"+f"(d[12]),"+f"(d[13]),"+f"(d[14]),"+f"(d[15]),"+f"(d[16]),"+f"(d[17]),"+f"(d[18]),"+f"(d[19]),"+f"(d[20]),"+f"(d[21]),"+f"(d[22]),"+f"(d[23]),"+f"(d[24]),"+f"(d[25]),"+f"(d[26]),"+f"(d[27]),"+f"(d[28]),"+f"(d[29]),"+f"(d[30]),"+f"(d[31]),"+f"(d[32]),"+f"(d[33]),"+f"(d[34]),"+f"(d[35]),"+f"(d[36]),"+f"(d[37]),"+f"(d[38]),"+f"(d[39]),"+f"(d[40]),"+f"(d[41]),"+f"(d[42]),"+f"(d[43]),"+f"(d[44]),"+f"(d[45]),"+f"(d[46]),"+f"(d[47]),"+f"(d[48]),"+f"(d[49]),"+f"(d[50]),"+f"(d[51]),"+f"(d[52]),"+f"(d[53]),"+f"(d[54]),"+f"(d[55]),"+f"(d[56]),"+f"(d[57]),"+f"(d[58]),"+f"(d[59]),"+f"(d[60]),"+f"(d[61]),"+f"(d[62]),"+f"(d[63]),"+f"(d[64]),"+f"(d[65]),"+f"(d[66]),"+f"(d[67]),"+f"(d[68]),"+f"(d[69]),"+f"(d[70]),"+f"(d[71])
    : "r"(alo), "r"(ahi), "r"(blo), "r"(bhi), "r"(sd), "n"(TA), "n"(TB)); }
};
template<> struct WG<160> { template<int TA, int TB> static __device__ __forceinline__ void ss(float* d, uint32_t alo, uint32_t ahi, uint32_t blo, uint32_t bhi, int sd) {
  asm volatile("{ .reg .pred p; .reg .b64 da, db; mov.b64 da, {%80,%81}; mov.b64 db, {%82,%83}; setp.ne.b32 p, %84, 0;\n"
    "wgmma.mma_async.sync.aligned.m64n160k16.f32.bf16.bf16 {%0,%1,%2,%3,%4,%5,%6,%7,%8,%9,%10,%11,%12,%13,%14,%15,%16,%17,%18,%19,%20,%21,%22,%23,%24,%25,%26,%27,%28,%29,%30,%31,%32,%33,%34,%35,%36,%37,%38,%39,%40,%41,%42,%43,%44,%45,%46,%47,%48,%49,%50,%51,%52,%53,%54,%55,%56,%57,%58,%59,%60,%61,%62,%63,%64,%65,%66,%67,%68,%69,%70,%71,%72,%73,%74,%75,%76,%77,%78,%79}, da, db, p, 1, 1, %85, %86; }"
    : "+f"(d[0]),"+f"(d[1]),"+f"(d[2]),"+f"(d[3]),"+f"(d[4]),"+f"(d[5]),"+f"(d[6]),"+f"(d[7]),"+f"(d[8]),"+f"(d[9]),"+f"(d[10]),"+f"(d[11]),"+f"(d[12]),"+f"(d[13]),"+f"(d[14]),"+f"(d[15]),"+f"(d[16]),"+f"(d[17]),"+f"(d[18]),"+f"(d[19]),"+f"(d[20]),"+f"(d[21]),"+f"(d[22]),"+f"(d[23]),"+f"(d[24]),"+f"(d[25]),"+f"(d[26]),"+f"(d[27]),"+f"(d[28]),"+f"(d[29]),"+f"(d[30]),"+f"(d[31]),"+f"(d[32]),"+f"(d[33]),"+f"(d[34]),"+f"(d[35]),"+f"(d[36]),"+f"(d[37]),"+f"(d[38]),"+f"(d[39]),"+f"(d[40]),"+f"(d[41]),"+f"(d[42]),"+f"(d[43]),"+f"(d[44]),"+f"(d[45]),"+f"(d[46]),"+f"(d[47]),"+f"(d[48]),"+f"(d[49]),"+f"(d[50]),"+f"(d[51]),"+f"(d[52]),"+f"(d[53]),"+f"(d[54]),"+f"(d[55]),"+f"(d[56]),"+f"(d[57]),"+f"(d[58]),"+f"(d[59]),"+f"(d[60]),"+f"(d[61]),"+f"(d[62]),"+f"(d[63]),"+f"(d[64]),"+f"(d[65]),"+f"(d[66]),"+f"(d[67]),"+f"(d[68]),"+f"(d[69]),"+f"(d[70]),"+f"(d[71]),"+f"(d[72]),"+f"(d[73]),"+f"(d[74]),"+f"(d[75]),"+f"(d[76]),"+f"(d[77]),"+f"(d[78]),"+f"(d[79])
    : "r"(alo), "r"(ahi), "r"(blo), "r"(bhi), "r"(sd), "n"(TA), "n"(TB)); }
  template<int TB> static __device__ __forceinline__ void rs(float* d, uint32_t a0, uint32_t a1, uint32_t a2, uint32_t a3, uint32_t blo, uint32_t bhi, int sd) {
  asm volatile("{ .reg .pred p; .reg .b64 db; mov.b64 db, {%84,%85}; setp.ne.b32 p, %87, 0;\n"
    "wgmma.mma_async.sync.aligned.m64n160k16.f32.bf16.bf16 {%0,%1,%2,%3,%4,%5,%6,%7,%8,%9,%10,%11,%12,%13,%14,%15,%16,%17,%18,%19,%20,%21,%22,%23,%24,%25,%26,%27,%28,%29,%30,%31,%32,%33,%34,%35,%36,%37,%38,%39,%40,%41,%42,%43,%44,%45,%46,%47,%48,%49,%50,%51,%52,%53,%54,%55,%56,%57,%58,%59,%60,%61,%62,%63,%64,%65,%66,%67,%68,%69,%70,%71,%72,%73,%74,%75,%76,%77,%78,%79}, {%80,%81,%82,%83}, db, p, 1, 1, %86; }"
    : "+f"(d[0]),"+f"(d[1]),"+f"(d[2]),"+f"(d[3]),"+f"(d[4]),"+f"(d[5]),"+f"(d[6]),"+f"(d[7]),"+f"(d[8]),"+f"(d[9]),"+f"(d[10]),"+f"(d[11]),"+f"(d[12]),"+f"(d[13]),"+f"(d[14]),"+f"(d[15]),"+f"(d[16]),"+f"(d[17]),"+f"(d[18]),"+f"(d[19]),"+f"(d[20]),"+f"(d[21]),"+f"(d[22]),"+f"(d[23]),"+f"(d[24]),"+f"(d[25]),"+f"(d[26]),"+f"(d[27]),"+f"(d[28]),"+f"(d[29]),"+f"(d[30]),"+f"(d[31]),"+f"(d[32]),"+f"(d[33]),"+f"(d[34]),"+f"(d[35]),"+f"(d[36]),"+f"(d[37]),"+f"(d[38]),"+f"(d[39]),"+f"(d[40]),"+f"(d[41]),"+f"(d[42]),"+f"(d[43]),"+f"(d[44]),"+f"(d[45]),"+f"(d[46]),"+f"(d[47]),"+f"(d[48]),"+f"(d[49]),"+f"(d[50]),"+f"(d[51]),"+f"(d[52]),"+f"(d[53]),"+f"(d[54]),"+f"(d[55]),"+f"(d[56]),"+f"(d[57]),"+f"(d[58]),"+f"(d[59]),"+f"(d[60]),"+f"(d[61]),"+f"(d[62]),"+f"(d[63]),"+f"(d[64]),"+f"(d[65]),"+f"(d[66]),"+f"(d[67]),"+f"(d[68]),"+f"(d[69]),"+f"(d[70]),"+f"(d[71]),"+f"(d[72]),"+f"(d[73]),"+f"(d[74]),"+f"(d[75]),"+f"(d[76]),"+f"(d[77]),"+f"(d[78]),"+f"(d[79])
    : "r"(a0), "r"(a1), "r"(a2), "r"(a3), "r"(blo), "r"(bhi), "n"(TB), "r"(sd)); }
};
template<> struct WG<176> { template<int TA, int TB> static __device__ __forceinline__ void ss(float* d, uint32_t alo, uint32_t ahi, uint32_t blo, uint32_t bhi, int sd) {
  asm volatile("{ .reg .pred p; .reg .b64 da, db; mov.b64 da, {%88,%89}; mov.b64 db, {%90,%91}; setp.ne.b32 p, %92, 0;\n"
    "wgmma.mma_async.sync.aligned.m64n176k16.f32.bf16.bf16 {%0,%1,%2,%3,%4,%5,%6,%7,%8,%9,%10,%11,%12,%13,%14,%15,%16,%17,%18,%19,%20,%21,%22,%23,%24,%25,%26,%27,%28,%29,%30,%31,%32,%33,%34,%35,%36,%37,%38,%39,%40,%41,%42,%43,%44,%45,%46,%47,%48,%49,%50,%51,%52,%53,%54,%55,%56,%57,%58,%59,%60,%61,%62,%63,%64,%65,%66,%67,%68,%69,%70,%71,%72,%73,%74,%75,%76,%77,%78,%79,%80,%81,%82,%83,%84,%85,%86,%87}, da, db, p, 1, 1, %93, %94; }"
    : "+f"(d[0]),"+f"(d[1]),"+f"(d[2]),"+f"(d[3]),"+f"(d[4]),"+f"(d[5]),"+f"(d[6]),"+f"(d[7]),"+f"(d[8]),"+f"(d[9]),"+f"(d[10]),"+f"(d[11]),"+f"(d[12]),"+f"(d[13]),"+f"(d[14]),"+f"(d[15]),"+f"(d[16]),"+f"(d[17]),"+f"(d[18]),"+f"(d[19]),"+f"(d[20]),"+f"(d[21]),"+f"(d[22]),"+f"(d[23]),"+f"(d[24]),"+f"(d[25]),"+f"(d[26]),"+f"(d[27]),"+f"(d[28]),"+f"(d[29]),"+f"(d[30]),"+f"(d[31]),"+f"(d[32]),"+f"(d[33]),"+f"(d[34]),"+f"(d[35]),"+f"(d[36]),"+f"(d[37]),"+f"(d[38]),"+f"(d[39]),"+f"(d[40]),"+f"(d[41]),"+f"(d[42]),"+f"(d[43]),"+f"(d[44]),"+f"(d[45]),"+f"(d[46]),"+f"(d[47]),"+f"(d[48]),"+f"(d[49]),"+f"(d[50]),"+f"(d[51]),"+f"(d[52]),"+f"(d[53]),"+f"(d[54]),"+f"(d[55]),"+f"(d[56]),"+f"(d[57]),"+f"(d[58]),"+f"(d[59]),"+f"(d[60]),"+f"(d[61]),"+f"(d[62]),"+f"(d[63]),"+f"(d[64]),"+f"(d[65]),"+f"(d[66]),"+f"(d[67]),"+f"(d[68]),"+f"(d[69]),"+f"(d[70]),"+f"(d[71]),"+f"(d[72]),"+f"(d[73]),"+f"(d[74]),"+f"(d[75]),"+f"(d[76]),"+f"(d[77]),"+f"(d[78]),"+f"(d[79]),"+f"(d[80]),"+f"(d[81]),"+f"(d[82]),"+f"(d[83]),"+f"(d[84]),"+f"(d[85]),"+f"(d[86]),"+f"(d[87])
    : "r"(alo), "r"(ahi), "r"(blo), "r"(bhi), "r"(sd), "n"(TA), "n"(TB)); }
};
template<> struct WG<192> { template<int TA, int TB> static __device__ __forceinline__ void ss(float* d, uint32_t alo, uint32_t ahi, uint32_t blo, uint32_t bhi, int sd) {
  asm volatile("{ .reg .pred p; .reg .b64 da, db; mov.b64 da, {%96,%97}; mov.b64 db, {%98,%99}; setp.ne.b32 p, %100, 0;\n"
    "wgmma.mma_async.sync.aligned.m64n192k16.f32.bf16.bf16 {%0,%1,%2,%3,%4,%5,%6,%7,%8,%9,%10,%11,%12,%13,%14,%15,%16,%17,%18,%19,%20,%21,%22,%23,%24,%25,%26,%27,%28,%29,%30,%31,%32,%33,%34,%35,%36,%37,%38,%39,%40,%41,%42,%43,%44,%45,%46,%47,%48,%49,%50,%51,%52,%53,%54,%55,%56,%57,%58,%59,%60,%61,%62,%63,%64,%65,%66,%67,%68,%69,%70,%71,%72,%73,%74,%75,%76,%77,%78,%79,%80,%81,%82,%83,%84,%85,%86,%87,%88,%89,%90,%91,%92,%93,%94,%95}, da, db, p, 1, 1, %101, %102; }"
    : "+f"(d[0]),"+f"(d[1]),"+f"(d[2]),"+f"(d[3]),"+f"(d[4]),"+f"(d[5]),"+f"(d[6]),"+f"(d[7]),"+f"(d[8]),"+f"(d[9]),"+f"(d[10]),"+f"(d[11]),"+f"(d[12]),"+f"(d[13]),"+f"(d[14]),"+f"(d[15]),"+f"(d[16]),"+f"(d[17]),"+f"(d[18]),"+f"(d[19]),"+f"(d[20]),"+f"(d[21]),"+f"(d[22]),"+f"(d[23]),"+f"(d[24]),"+f"(d[25]),"+f"(d[26]),"+f"(d[27]),"+f"(d[28]),"+f"(d[29]),"+f"(d[30]),"+f"(d[31]),"+f"(d[32]),"+f"(d[33]),"+f"(d[34]),"+f"(d[35]),"+f"(d[36]),"+f"(d[37]),"+f"(d[38]),"+f"(d[39]),"+f"(d[40]),"+f"(d[41]),"+f"(d[42]),"+f"(d[43]),"+f"(d[44]),"+f"(d[45]),"+f"(d[46]),"+f"(d[47]),"+f"(d[48]),"+f"(d[49]),"+f"(d[50]),"+f"(d[51]),"+f"(d[52]),"+f"(d[53]),"+f"(d[54]),"+f"(d[55]),"+f"(d[56]),"+f"(d[57]),"+f"(d[58]),"+f"(d[59]),"+f"(d[60]),"+f"(d[61]),"+f"(d[62]),"+f"(d[63]),"+f"(d[64]),"+f"(d[65]),"+f"(d[66]),"+f"(d[67]),"+f"(d[68]),"+f"(d[69]),"+f"(d[70]),"+f"(d[71]),"+f"(d[72]),"+f"(d[73]),"+f"(d[74]),"+f"(d[75]),"+f"(d[76]),"+f"(d[77]),"+f"(d[78]),"+f"(d[79]),"+f"(d[80]),"+f"(d[81]),"+f"(d[82]),"+f"(d[83]),"+f"(d[84]),"+f"(d[85]),"+f"(d[86]),"+f"(d[87]),"+f"(d[88]),"+f"(d[89]),"+f"(d[90]),"+f"(d[91]),"+f"(d[92]),"+f"(d[93]),"+f"(d[94]),"+f"(d[95])
    : "r"(alo), "r"(ahi), "r"(blo), "r"(bhi), "r"(sd), "n"(TA), "n"(TB)); }
};
template<> struct WG<208> { template<int TA, int TB> static __device__ __forceinline__ void ss(float* d, uint32_t alo, uint32_t ahi, uint32_t blo, uint32_t bhi, int sd) {
  asm volatile("{ .reg .pred p; .reg .b64 da, db; mov.b64 da, {%104,%105}; mov.b64 db, {%106,%107}; setp.ne.b32 p, %108, 0;\n"
    "wgmma.mma_async.sync.aligned.m64n208k16.f32.bf16.bf16 {%0,%1,%2,%3,%4,%5,%6,%7,%8,%9,%10,%11,%12,%13,%14,%15,%16,%17,%18,%19,%20,%21,%22,%23,%24,%25,%26,%27,%28,%29,%30,%31,%32,%33,%34,%35,%36,%37,%38,%39,%40,%41,%42,%43,%44,%45,%46,%47,%48,%49,%50,%51,%52,%53,%54,%55,%56,%57,%58,%59,%60,%61,%62,%63,%64,%65,%66,%67,%68,%69,%70,%71,%72,%73,%74,%75,%76,%77,%78,%79,%80,%81,%82,%83,%84,%85,%86,%87,%88,%89,%90,%91,%92,%93,%94,%95,%96,%97,%98,%99,%100,%101,%102,%103}, da, db, p, 1, 1, %109, %110; }"
    : "+f"(d[0]),"+f"(d[1]),"+f"(d[2]),"+f"(d[3]),"+f"(d[4]),"+f"(d[5]),"+f"(d[6]),"+f"(d[7]),"+f"(d[8]),"+f"(d[9]),"+f"(d[10]),"+f"(d[11]),"+f"(d[12]),"+f"(d[13]),"+f"(d[14]),"+f"(d[15]),"+f"(d[16]),"+f"(d[17]),"+f"(d[18]),"+f"(d[19]),"+f"(d[20]),"+f"(d[21]),"+f"(d[22]),"+f"(d[23]),"+f"(d[24]),"+f"(d[25]),"+f"(d[26]),"+f"(d[27]),"+f"(d[28]),"+f"(d[29]),"+f"(d[30]),"+f"(d[31]),"+f"(d[32]),"+f"(d[33]),"+f"(d[34]),"+f"(d[35]),"+f"(d[36]),"+f"(d[37]),"+f"(d[38]),"+f"(d[39]),"+f"(d[40]),"+f"(d[41]),"+f"(d[42]),"+f"(d[43]),"+f"(d[44]),"+f"(d[45]),"+f"(d[46]),"+f"(d[47]),"+f"(d[48]),"+f"(d[49]),"+f"(d[50]),"+f"(d[51]),"+f"(d[52]),"+f"(d[53]),"+f"(d[54]),"+f"(d[55]),"+f"(d[56]),"+f"(d[57]),"+f"(d[58]),"+f"(d[59]),"+f"(d[60]),"+f"(d[61]),"+f"(d[62]),"+f"(d[63]),"+f"(d[64]),"+f"(d[65]),"+f"(d[66]),"+f"(d[67]),"+f"(d[68]),"+f"(d[69]),"+f"(d[70]),"+f"(d[71]),"+f"(d[72]),"+f"(d[73]),"+f"(d[74]),"+f"(d[75]),"+f"(d[76]),"+f"(d[77]),"+f"(d[78]),"+f"(d[79]),"+f"(d[80]),"+f"(d[81]),"+f"(d[82]),"+f"(d[83]),"+f"(d[84]),"+f"(d[85]),"+f"(d[86]),"+f"(d[87]),"+f"(d[88]),"+f"(d[89]),"+f"(d[90]),"+f"(d[91]),"+f"(d[92]),"+f"(d[93]),"+f"(d[94]),"+f"(d[95]),"+f"(d[96]),"+f"(d[97]),"+f"(d[98]),"+f"(d[99]),"+f"(d[100]),"+f"(d[101]),"+f"(d[102]),"+f"(d[103])
    : "r"(alo), "r"(ahi), "r"(blo), "r"(bhi), "r"(sd), "n"(TA), "n"(TB)); }
};
template<> struct WG<224> { template<int TA, int TB> static __device__ __forceinline__ void ss(float* d, uint32_t alo, uint32_t ahi, uint32_t blo, uint32_t bhi, int sd) {
  asm volatile("{ .reg .pred p; .reg .b64 da, db; mov.b64 da, {%112,%113}; mov.b64 db, {%114,%115}; setp.ne.b32 p, %116, 0;\n"
    "wgmma.mma_async.sync.aligned.m64n224k16.f32.bf16.bf16 {%0,%1,%2,%3,%4,%5,%6,%7,%8,%9,%10,%11,%12,%13,%14,%15,%16,%17,%18,%19,%20,%21,%22,%23,%24,%25,%26,%27,%28,%29,%30,%31,%32,%33,%34,%35,%36,%37,%38,%39,%40,%41,%42,%43,%44,%45,%46,%47,%48,%49,%50,%51,%52,%53,%54,%55,%56,%57,%58,%59,%60,%61,%62,%63,%64,%65,%66,%67,%68,%69,%70,%71,%72,%73,%74,%75,%76,%77,%78,%79,%80,%81,%82,%83,%84,%85,%86,%87,%88,%89,%90,%91,%92,%93,%94,%95,%96,%97,%98,%99,%100,%101,%102,%103,%104,%105,%106,%107,%108,%109,%110,%111}, da, db, p, 1, 1, %117, %118; }"
    : "+f"(d[0]),"+f"(d[1]),"+f"(d[2]),"+f"(d[3]),"+f"(d[4]),"+f"(d[5]),"+f"(d[6]),"+f"(d[7]),"+f"(d[8]),"+f"(d[9]),"+f"(d[10]),"+f"(d[11]),"+f"(d[12]),"+f"(d[13]),"+f"(d[14]),"+f"(d[15]),"+f"(d[16]),"+f"(d[17]),"+f"(d[18]),"+f"(d[19]),"+f"(d[20]),"+f"(d[21]),"+f"(d[22]),"+f"(d[23]),"+f"(d[24]),"+f"(d[25]),"+f"(d[26]),"+f"(d[27]),"+f"(d[28]),"+f"(d[29]),"+f"(d[30]),"+f"(d[31]),"+f"(d[32]),"+f"(d[33]),"+f"(d[34]),"+f"(d[35]),"+f"(d[36]),"+f"(d[37]),"+f"(d[38]),"+f"(d[39]),"+f"(d[40]),"+f"(d[41]),"+f"(d[42]),"+f"(d[43]),"+f"(d[44]),"+f"(d[45]),"+f"(d[46]),"+f"(d[47]),"+f"(d[48]),"+f"(d[49]),"+f"(d[50]),"+f"(d[51]),"+f"(d[52]),"+f"(d[53]),"+f"(d[54]),"+f"(d[55]),"+f"(d[56]),"+f"(d[57]),"+f"(d[58]),"+f"(d[59]),"+f"(d[60]),"+f"(d[61]),"+f"(d[62]),"+f"(d[63]),"+f"(d[64]),"+f"(d[65]),"+f"(d[66]),"+f"(d[67]),"+f"(d[68]),"+f"(d[69]),"+f"(d[70]),"+f"(d[71]),"+f"(d[72]),"+f"(d[73]),"+f"(d[74]),"+f"(d[75]),"+f"(d[76]),"+f"(d[77]),"+f"(d[78]),"+f"(d[79]),"+f"(d[80]),"+f"(d[81]),"+f"(d[82]),"+f"(d[83]),"+f"(d[84]),"+f"(d[85]),"+f"(d[86]),"+f"(d[87]),"+f"(d[88]),"+f"(d[89]),"+f"(d[90]),"+f"(d[91]),"+f"(d[92]),"+f"(d[93]),"+f"(d[94]),"+f"(d[95]),"+f"(d[96]),"+f"(d[97]),"+f"(d[98]),"+f"(d[99]),"+f"(d[100]),"+f"(d[101]),"+f"(d[102]),"+f"(d[103]),"+f"(d[104]),"+f"(d[105]),"+f"(d[106]),"+f"(d[107]),"+f"(d[108]),"+f"(d[109]),"+f"(d[110]),"+f"(d[111])
    : "r"(alo), "r"(ahi), "r"(blo), "r"(bhi), "r"(sd), "n"(TA), "n"(TB)); }
};
template<> struct WG<240> { template<int TA, int TB> static __device__ __forceinline__ void ss(float* d, uint32_t alo, uint32_t ahi, uint32_t blo, uint32_t bhi, int sd) {
  asm volatile("{ .reg .pred p; .reg .b64 da, db; mov.b64 da, {%120,%121}; mov.b64 db, {%122,%123}; setp.ne.b32 p, %124, 0;\n"
    "wgmma.mma_async.sync.aligned.m64n240k16.f32.bf16.bf16 {%0,%1,%2,%3,%4,%5,%6,%7,%8,%9,%10,%11,%12,%13,%14,%15,%16,%17,%18,%19,%20,%21,%22,%23,%24,%25,%26,%27,%28,%29,%30,%31,%32,%33,%34,%35,%36,%37,%38,%39,%40,%41,%42,%43,%44,%45,%46,%47,%48,%49,%50,%51,%52,%53,%54,%55,%56,%57,%58,%59,%60,%61,%62,%63,%64,%65,%66,%67,%68,%69,%70,%71,%72,%73,%74,%75,%76,%77,%78,%79,%80,%81,%82,%83,%84,%85,%86,%87,%88,%89,%90,%91,%92,%93,%94,%95,%96,%97,%98,%99,%100,%101,%102,%103,%104,%105,%106,%107,%108,%109,%110,%111,%112,%113,%114,%115,%116,%117,%118,%119}, da, db, p, 1, 1, %125, %126; }"
    : "+f"(d[0]),"+f"(d[1]),"+f"(d[2]),"+f"(d[3]),"+f"(d[4]),"+f"(d[5]),"+f"(d[6]),"+f"(d[7]),"+f"(d[8]),"+f"(d[9]),"+f"(d[10]),"+f"(d[11]),"+f"(d[12]),"+f"(d[13]),"+f"(d[14]),"+f"(d[15]),"+f"(d[16]),"+f"(d[17]),"+f"(d[18]),"+f"(d[19]),"+f"(d[20]),"+f"(d[21]),"+f"(d[22]),"+f"(d[23]),"+f"(d[24]),"+f"(d[25]),"+f"(d[26]),"+f"(d[27]),"+f"(d[28]),"+f"(d[29]),"+f"(d[30]),"+f"(d[31]),"+f"(d[32]),"+f"(d[33]),"+f"(d[34]),"+f"(d[35]),"+f"(d[36]),"+f"(d[37]),"+f"(d[38]),"+f"(d[39]),"+f"(d[40]),"+f"(d[41]),"+f"(d[42]),"+f"(d[43]),"+f"(d[44]),"+f"(d[45]),"+f"(d[46]),"+f"(d[47]),"+f"(d[48]),"+f"(d[49]),"+f"(d[50]),"+f"(d[51]),"+f"(d[52]),"+f"(d[53]),"+f"(d[54]),"+f"(d[55]),"+f"(d[56]),"+f"(d[57]),"+f"(d[58]),"+f"(d[59]),"+f"(d[60]),"+f"(d[61]),"+f"(d[62]),"+f"(d[63]),"+f"(d[64]),"+f"(d[65]),"+f"(d[66]),"+f"(d[67]),"+f"(d[68]),"+f"(d[69]),"+f"(d[70]),"+f"(d[71]),"+f"(d[72]),"+f"(d[73]),"+f"(d[74]),"+f"(d[75]),"+f"(d[76]),"+f"(d[77]),"+f"(d[78]),"+f"(d[79]),"+f"(d[80]),"+f"(d[81]),"+f"(d[82]),"+f"(d[83]),"+f"(d[84]),"+f"(d[85]),"+f"(d[86]),"+f"(d[87]),"+f"(d[88]),"+f"(d[89]),"+f"(d[90]),"+f"(d[91]),"+f"(d[92]),"+f"(d[93]),"+f"(d[94]),"+f"(d[95]),"+f"(d[96]),"+f"(d[97]),"+f"(d[98]),"+f"(d[99]),"+f"(d[100]),"+f"(d[101]),"+f"(d[102]),"+f"(d[103]),"+f"(d[104]),"+f"(d[105]),"+f"(d[106]),"+f"(d[107]),"+f"(d[108]),"+f"(d[109]),"+f"(d[110]),"+f"(d[111]),"+f"(d[112]),"+f"(d[113]),"+f"(d[114]),"+f"(d[115]),"+f"(d[116]),"+f"(d[117]),"+f"(d[118]),"+f"(d[119])
    : "r"(alo), "r"(ahi), "r"(blo), "r"(bhi), "r"(sd), "n"(TA), "n"(TB)); }
};
template<> struct WG<256> { template<int TA, int TB> static __device__ __forceinline__ void ss(float* d, uint32_t alo, uint32_t ahi, uint32_t blo, uint32_t bhi, int sd) {
  asm volatile("{ .reg .pred p; .reg .b64 da, db; mov.b64 da, {%128,%129}; mov.b64 db, {%130,%131}; setp.ne.b32 p, %132, 0;\n"
    "wgmma.mma_async.sync.aligned.m64n256k16.f32.bf16.bf16 {%0,%1,%2,%3,%4,%5,%6,%7,%8,%9,%10,%11,%12,%13,%14,%15,%16,%17,%18,%19,%20,%21,%22,%23,%24,%25,%26,%27,%28,%29,%30,%31,%32,%33,%34,%35,%36,%37,%38,%39,%40,%41,%42,%43,%44,%45,%46,%47,%48,%49,%50,%51,%52,%53,%54,%55,%56,%57,%58,%59,%60,%61,%62,%63,%64,%65,%66,%67,%68,%69,%70,%71,%72,%73,%74,%75,%76,%77,%78,%79,%80,%81,%82,%83,%84,%85,%86,%87,%88,%89,%90,%91,%92,%93,%94,%95,%96,%97,%98,%99,%100,%101,%102,%103,%104,%105,%106,%107,%108,%109,%110,%111,%112,%113,%114,%115,%116,%117,%118,%119,%120,%121,%122,%123,%124,%125,%126,%127}, da, db, p, 1, 1, %133, %134; }"
    : "+f"(d[0]),"+f"(d[1]),"+f"(d[2]),"+f"(d[3]),"+f"(d[4]),"+f"(d[5]),"+f"(d[6]),"+f"(d[7]),"+f"(d[8]),"+f"(d[9]),"+f"(d[10]),"+f"(d[11]),"+f"(d[12]),"+f"(d[13]),"+f"(d[14]),"+f"(d[15]),"+f"(d[16]),"+f"(d[17]),"+f"(d[18]),"+f"(d[19]),"+f"(d[20]),"+f"(d[21]),"+f"(d[22]),"+f"(d[23]),"+f"(d[24]),"+f"(d[25]),"+f"(d[26]),"+f"(d[27]),"+f"(d[28]),"+f"(d[29]),"+f"(d[30]),"+f"(d[31]),"+f"(d[32]),"+f"(d[33]),"+f"(d[34]),"+f"(d[35]),"+f"(d[36]),"+f"(d[37]),"+f"(d[38]),"+f"(d[39]),"+f"(d[40]),"+f"(d[41]),"+f"(d[42]),"+f"(d[43]),"+f"(d[44]),"+f"(d[45]),"+f"(d[46]),"+f"(d[47]),"+f"(d[48]),"+f"(d[49]),"+f"(d[50]),"+f"(d[51]),"+f"(d[52]),"+f"(d[53]),"+f"(d[54]),"+f"(d[55]),"+f"(d[56]),"+f"(d[57]),"+f"(d[58]),"+f"(d[59]),"+f"(d[60]),"+f"(d[61]),"+f"(d[62]),"+f"(d[63]),"+f"(d[64]),"+f"(d[65]),"+f"(d[66]),"+f"(d[67]),"+f"(d[68]),"+f"(d[69]),"+f"(d[70]),"+f"(d[71]),"+f"(d[72]),"+f"(d[73]),"+f"(d[74]),"+f"(d[75]),"+f"(d[76]),"+f"(d[77]),"+f"(d[78]),"+f"(d[79]),"+f"(d[80]),"+f"(d[81]),"+f"(d[82]),"+f"(d[83]),"+f"(d[84]),"+f"(d[85]),"+f"(d[86]),"+f"(d[87]),"+f"(d[88]),"+f"(d[89]),"+f"(d[90]),"+f"(d[91]),"+f"(d[92]),"+f"(d[93]),"+f"(d[94]),"+f"(d[95]),"+f"(d[96]),"+f"(d[97]),"+f"(d[98]),"+f"(d[99]),"+f"(d[100]),"+f"(d[101]),"+f"(d[102]),"+f"(d[103]),"+f"(d[104]),"+f"(d[105]),"+f"(d[106]),"+f"(d[107]),"+f"(d[108]),"+f"(d[109]),"+f"(d[110]),"+f"(d[111]),"+f"(d[112]),"+f"(d[113]),"+f"(d[114]),"+f"(d[115]),"+f"(d[116]),"+f"(d[117]),"+f"(d[118]),"+f"(d[119]),"+f"(d[120]),"+f"(d[121]),"+f"(d[122]),"+f"(d[123]),"+f"(d[124]),"+f"(d[125]),"+f"(d[126]),"+f"(d[127])
    : "r"(alo), "r"(ahi), "r"(blo), "r"(bhi), "r"(sd), "n"(TA), "n"(TB)); }
  template<int TB> static __device__ __forceinline__ void rs(float* d, uint32_t a0, uint32_t a1, uint32_t a2, uint32_t a3, uint32_t blo, uint32_t bhi, int sd) {
  asm volatile("{ .reg .pred p; .reg .b64 db; mov.b64 db, {%132,%133}; setp.ne.b32 p, %135, 0;\n"
    "wgmma.mma_async.sync.aligned.m64n256k16.f32.bf16.bf16 {%0,%1,%2,%3,%4,%5,%6,%7,%8,%9,%10,%11,%12,%13,%14,%15,%16,%17,%18,%19,%20,%21,%22,%23,%24,%25,%26,%27,%28,%29,%30,%31,%32,%33,%34,%35,%36,%37,%38,%39,%40,%41,%42,%43,%44,%45,%46,%47,%48,%49,%50,%51,%52,%53,%54,%55,%56,%57,%58,%59,%60,%61,%62,%63,%64,%65,%66,%67,%68,%69,%70,%71,%72,%73,%74,%75,%76,%77,%78,%79,%80,%81,%82,%83,%84,%85,%86,%87,%88,%89,%90,%91,%92,%93,%94,%95,%96,%97,%98,%99,%100,%101,%102,%103,%104,%105,%106,%107,%108,%109,%110,%111,%112,%113,%114,%115,%116,%117,%118,%119,%120,%121,%122,%123,%124,%125,%126,%127}, {%128,%129,%130,%131}, db, p, 1, 1, %134; }"
    : "+f"(d[0]),"+f"(d[1]),"+f"(d[2]),"+f"(d[3]),"+f"(d[4]),"+f"(d[5]),"+f"(d[6]),"+f"(d[7]),"+f"(d[8]),"+f"(d[9]),"+f"(d[10]),"+f"(d[11]),"+f"(d[12]),"+f"(d[13]),"+f"(d[14]),"+f"(d[15]),"+f"(d[16]),"+f"(d[17]),"+f"(d[18]),"+f"(d[19]),"+f"(d[20]),"+f"(d[21]),"+f"(d[22]),"+f"(d[23]),"+f"(d[24]),"+f"(d[25]),"+f"(d[26]),"+f"(d[27]),"+f"(d[28]),"+f"(d[29]),"+f"(d[30]),"+f"(d[31]),"+f"(d[32]),"+f"(d[33]),"+f"(d[34]),"+f"(d[35]),"+f"(d[36]),"+f"(d[37]),"+f"(d[38]),"+f"(d[39]),"+f"(d[40]),"+f"(d[41]),"+f"(d[42]),"+f"(d[43]),"+f"(d[44]),"+f"(d[45]),"+f"(d[46]),"+f"(d[47]),"+f"(d[48]),"+f"(d[49]),"+f"(d[50]),"+f"(d[51]),"+f"(d[52]),"+f"(d[53]),"+f"(d[54]),"+f"(d[55]),"+f"(d[56]),"+f"(d[57]),"+f"(d[58]),"+f"(d[59]),"+f"(d[60]),"+f"(d[61]),"+f"(d[62]),"+f"(d[63]),"+f"(d[64]),"+f"(d[65]),"+f"(d[66]),"+f"(d[67]),"+f"(d[68]),"+f"(d[69]),"+f"(d[70]),"+f"(d[71]),"+f"(d[72]),"+f"(d[73]),"+f"(d[74]),"+f"(d[75]),"+f"(d[76]),"+f"(d[77]),"+f"(d[78]),"+f"(d[79]),"+f"(d[80]),"+f"(d[81]),"+f"(d[82]),"+f"(d[83]),"+f"(d[84]),"+f"(d[85]),"+f"(d[86]),"+f"(d[87]),"+f"(d[88]),"+f"(d[89]),"+f"(d[90]),"+f"(d[91]),"+f"(d[92]),"+f"(d[93]),"+f"(d[94]),"+f"(d[95]),"+f"(d[96]),"+f"(d[97]),"+f"(d[98]),"+f"(d[99]),"+f"(d[100]),"+f"(d[101]),"+f"(d[102]),"+f"(d[103]),"+f"(d[104]),"+f"(d[105]),"+f"(d[106]),"+f"(d[107]),"+f"(d[108]),"+f"(d[109]),"+f"(d[110]),"+f"(d[111]),"+f"(d[112]),"+f"(d[113]),"+f"(d[114]),"+f"(d[115]),"+f"(d[116]),"+f"(d[117]),"+f"(d[118]),"+f"(d[119]),"+f"(d[120]),"+f"(d[121]),"+f"(d[122]),"+f"(d[123]),"+f"(d[124]),"+f"(d[125]),"+f"(d[126]),"+f"(d[127])
    : "r"(a0), "r"(a1), "r"(a2), "r"(a3), "r"(blo), "r"(bhi), "n"(TB), "r"(sd)); }
};

template<int T> struct Conv {
    static __device__ __forceinline__ void run(float* acc, uint32_t da, uint32_t db) {
        WG<256 - 16 * T>::template ss<0, 0>(acc, da + (T >> 2) * 512 + (T & 3) * 2, dhi(1024, 1), db + T * 16, dhi(128, 0), T != 0);
        Conv<T + 1>::run(acc, da, db);
    }
};
template<> struct Conv<16> { static __device__ __forceinline__ void run(float*, uint32_t, uint32_t) {} };

template<int Q> __device__ __forceinline__ void ffn_epi(const float* g, const float* u, uint32_t* hq, char* dst, uint32_t tm, uint32_t par, float rq0, float rq1) {
    constexpr int U = Q >> 2, i = 4 * Q;
    uint32_t* o = hq + 8 * U;
    o[Q & 3] = hmul2(pack2relu(g[i], g[i + 1]), RQE == 1 ? pack2(u[i] * rq0, u[i + 1] * rq0) : pack2(u[i], u[i + 1]));
    o[4 + (Q & 3)] = hmul2(pack2relu(g[i + 2], g[i + 3]), RQE == 1 ? pack2(u[i + 2] * rq1, u[i + 3] * rq1) : pack2(u[i + 2], u[i + 3]));
    asm volatile("" : "+r"(o[Q & 3]), "+r"(o[4 + (Q & 3)]) :: "memory");
    if ((Q & 3) == 0) {
        stg_tag<0>(dst + U * 8192, o, tm, par);
        stg_tag<1>(dst + U * 8192 + 512, o + 4, tm, par);
    }
}
__device__ __forceinline__ uint32_t tagged(float x, uint32_t tag) { return (__float_as_uint(x) & ~7u) | (tag & 7u); }
__device__ __forceinline__ uint32_t split2(float x) { const float h = bfround(x); return pack2(h, x - h); }
__device__ __forceinline__ float rsqrt_(float x) { float r; asm("rsqrt.approx.ftz.f32 %0, %1;" : "=f"(r) : "f"(x)); return r; }
__device__ __forceinline__ void acc_stat(float& s, float& q, uint32_t w) { const float a = bflo(w), c = bfhi(w); s += a; q = fmaf(a, a, q); s += c; q = fmaf(c, c, q); }
template<int I, int N, typename F> __device__ __forceinline__ void static_for(F&& f) {
    if constexpr (I < N) { f(std::integral_constant<int, I>{}); static_for<I + 1, N>(f); }
}

__device__ __forceinline__ int mod_col(int i, int s) {
    const int g = 4 * i + s - 40;
    return i < 10 ? ((s & 1) ? 1280 + 1280 * (i & 1) : 640 * (i & 1)) + (i >> 1) * 128 + (s >> 1) * 64 : (g < 10 ? 1920 : 2560) + g * 64;
}
__device__ __forceinline__ uint32_t silu2(uint32_t w) {
    const float a0 = bflo(w), a1 = bfhi(w);
    return pack2(__fdividef(a0, 1.f + __expf(-a0)), __fdividef(a1, 1.f + __expf(-a1)));
}

struct Maps { CUtensorMap k, v, q, y, g1, u1, g2, u2, wd, wn, wm, out; };
struct Ptrs { const char *k, *v, *shift, *ssm, *ssmD; char *scr, *out; const char *c, *Wg, *Wu, *Wd;
};

__global__ void __cluster_dims__(2, 1, 1) __launch_bounds__(384, 1)
fused_kernel(const __grid_constant__ Ptrs P, const __grid_constant__ Maps M) {
    extern __shared__ __align__(1024) char smraw[];
    const uint32_t clk0 = clock32();
    const uint32_t sb = smem_u32(smraw);
    const int tid = threadIdx.x, b = blockIdx.x;
    #define BAR(i) (sb + BARS + 8 * (i))
    const char* pk = SBAR ? (&P.k)[tid >> 9] : P.k;
    const uint32_t rv = tid >> 3, c = (tid ^ rv) & 7, rk = rv + 2 + 2 * (rv >> 3);
    const uint32_t go = ((b >> 1) * 32 + (rv & 6) * 4 + 2 * (rv >> 3) + (rv & 1)) * 1280 + (b & 1) * 128 + c * 16, d0 = sb + st_kv(0) + rk * 128 + (((c ^ rk) & 7) << 4);
    if (SBAR) asm volatile("pmevent 1;" : "+l"(pk) : "r"(go), "r"(d0));
    if (SBAR && (go ^ d0 ^ (uint32_t)(uintptr_t)pk) == 0x80000001u) return;
    if (tid < 256 && b < 128) {
        cp16(d0, padd(pk, go));
        cp16(sb + st_kv(0) + 5120 + tid * 16, padd(P.v, go));
        sched_bar();
        if ((rv & 22) == 16)
            asm volatile("cp.async.cg.shared.global [%0], [%1], 16, %2;" :: "r"(sb + st_kv(0) + (rk - 2) * 128 + (((c ^ (rk - 2)) & 7) << 4)), "l"(padd(P.k, b < 2 ? go : go - 10240)), "r"(b < 2 ? 0 : 16) : "memory");
        if (tid < 160) cp16(sb + ST_SH + tid * 16, padd(P.shift, (tid >> 5) * 512 + (b & 1) * 512 + tid * 16));
        asm volatile("cp.async.commit_group;" ::: "memory");
    }
    const int warp = __shfl_sync(~0u, tid >> 5, 0), lane = tid & 31;
    const int rank = b & 1, cl = b >> 1;
    #define FFN_ROLE int cl_ = cl; asm volatile("pmevent 1;" : "+r"(cl_)); const int cu = cl_ - 36, cv = (cu * 37) >> 8, \
        gp_ = cl_ < 4 ? 0 : cl_ < 36 ? (cl_ - 4) & 7 : 1 + cu - 7 * cv, gi_ = cl_ < 4 ? 4 + cl_ : cl_ < 36 ? (cl_ - 4) >> 3 : 4 + cv, \
        grp = MAPM == 0 ? gp_ : MAPM == 1 ? (gp_ & 6) + (gi_ >> 2) : MAPM == 2 ? (gp_ & 6) + (gi_ & 1) : MAPM == 3 ? (gp_ & 4) + (gi_ & 3) : gi_, \
        js = MAPM == 0 ? gi_ : MAPM == 1 ? 4 * (gp_ & 1) + (gi_ & 3) : MAPM == 2 ? 4 * (gp_ & 1) + (gi_ >> 1) : MAPM == 3 ? 2 * (gp_ & 3) + (gi_ >> 2) : gp_, tile = 2 * grp + rank, dq = js & 3
    #define CNT(l, w) SC(cnt, (l) * 4096 + (w) * 4)
    uint32_t epoch = 0;

    if (b >= 128) {
        if (warp >= 10) {
            if (elect()) {
                _Pragma("unroll") for (int i = 0; i < 15; i++) mbar_init(BAR(i % 5 + i / 5 * 10) + (warp & 1) * 40, i < 5 || i >= 10 ? 1 : 4);
                asm volatile("fence.mbarrier_init.release.cluster;" ::: "memory");
                fence_async_smem();
                pf_map(&M.wm);
            }
            __syncwarp();
            asm volatile("barrier.cluster.arrive.relaxed.aligned;" ::: "memory");
            bar_arrive(0, 384);
        } else {
            epoch = ldg_late(CNT(C_Z, 6), lane);
            if (tid < 320) sts32(sb + 204800 + tid * 4, silu2(__ldg((const uint32_t*)P.c + tid)));
            fence_async_smem();
            __syncwarp();
            asm volatile("barrier.cluster.arrive.relaxed.aligned;\n barrier.cluster.wait.aligned;" ::: "memory");
            bar_sync(0, 384);
            STAMPIF(warp == 0, 7);
        }
        if (warp >= 10) {
            if (elect()) {
                wait_clock(clk0, D_SP);
                uint32_t fb = BAR(0) + (warp & 1) * 40, dst = sb + (warp & 1) * 102400, s = 0, ph = 1;
                _Pragma("unroll 1") for (int i = warp & 1; i < 15; i += 2) {
                    const int col = mod_col(i, b - 128);
                    _Pragma("unroll 1") for (int j = 0; j < 640; j += 160) {
                        mbar_wait(fb + 80, ph);
                        mbar_expect(fb, 20480);
                        tma2d(dst, &M.wm, col, j, fb);
                        fb += 8; dst += 20480;
                        if (++s == 5) { s = 0; ph ^= 1; fb -= 40; dst -= 102400; }
                    }
                }
            }
        } else if (warp == 9 && !rank) {
            epoch = (__shfl_sync(~0u, epoch, 0) >> 7) + 1;
            _Pragma("unroll 1") for (int r = 0; r < 5; r++) {
                if (lane == 0) mbar_expect(BAR(20 + r), 512);
                mbar_wait(BAR(20 + r), 0);
                uint32_t v[4];
                #pragma unroll
                for (int k = 0; k < 4; k++) asm volatile("ld.shared.b32 %0, [%1];" : "=r"(v[k]) : "r"(sb + 206336 + r * 512 + k * 128 + (lane & 16) * 4 + (lane & 3) * 16 + (lane & 12)) : "memory");
                stg_rlx128(SC(abc, (r * 64 + (b - 128) * 16 + lane) * 16), hmul2(v[2], hadd2(v[1], 0x3f803f80u)), hmul2(v[2], v[0]), hadd2(v[3], 0x3f803f80u), epoch);
                STAMP(1 + r);
            }
        } else if (warp < 8) {
            const int wg = warp >> 2;
            epoch = (__shfl_sync(~0u, epoch, 0) >> 7) + 1;
            int s = 0, ph = 0;
            _Pragma("unroll 1") for (int i = wg; i < 15; i += 2) {
                float ac5[20];
                uint32_t prev = 0;
                _Pragma("unroll 1") for (int j = 0; j < 4; j++) {
                    const int sl = wg * 5 + s;
                    mbar_wait(BAR(sl), ph);
                    wg_fence();
                    const uint32_t da = dlo(sb + sl * 20480, 16), db = dlo(sb + 204800 + j * 320, 16);
                    #pragma unroll
                    for (int ks = 0; ks < 10; ks++) WG<8>::ss<1, 0>(ac5 + 4 * (ks % 5), da + ks * 128, dhi(1024, 1), db + ks * 2, dhi(128, 0), ks >= 5 || j != 0);
                    wg_commit();
                    wg_wait<1>();
                    mbar_arrive_if(prev, lane == 0 && j);
                    prev = BAR(10 + sl);
                    if (++s == 5) { s = 0; ph ^= 1; }
                }
                wg_wait<0>();
                pin<20>(ac5);
                mbar_arrive_if(prev, lane == 0);
                const float acc[3] = {ac5[0] + ac5[4] + ac5[8] + ac5[12] + ac5[16], 0.f, ac5[2] + ac5[6] + ac5[10] + ac5[14] + ac5[18]};
                const uint32_t m0 = pack2(acc[0], __shfl_down_sync(~0u, acc[0], 4)), m1 = pack2(acc[2], __shfl_down_sync(~0u, acc[2], 4));
                if (i < 10) {
                    if ((lane & 7) == 0)
                        asm volatile("{ .reg .u32 a, m; mapa.shared::cluster.u32 a, %0, 0; mapa.shared::cluster.u32 m, %1, 0; \n"
                                     " st.async.shared::cluster.mbarrier::complete_tx::bytes.b32 [a], %2, [m]; st.async.shared::cluster.mbarrier::complete_tx::bytes.b32 [a+16], %3, [m]; }"
                                     :: "r"(sb + 206336 + (i >> 1) * 512 + rank * 256 + warp * 32 + (lane >> 3) * 4), "r"(BAR(20 + (i >> 1))), "r"(m0), "r"(m1) : "memory");
                } else if ((lane & 7) == 0) {
                    char* mp = SC(mod, ((4 * i + b - 168) * 64 + (warp & 3) * 16 + (lane >> 2)) * 4);
                    asm volatile("{ .reg .b64 x; mov.b64 x, {%1, %3}; st.relaxed.gpu.global.b64 [%0], x; mov.b64 x, {%2, %3}; st.relaxed.gpu.global.b64 [%0+32], x; }" :: "l"(mp), "r"(m0), "r"(m1), "r"(epoch) : "memory");
                }
                STAMPIF(warp == 0 && i == 12, 6); STAMPIF(warp == 0 && i == 0, 8);
            }
        }
        return;
    }

    const bool l0 = lane == 0;
    const int q = lane & 3, rr = lane >> 2;

    if (warp < 8) {
        const int wg = warp >> 2, w = warp & 3, t = tid & 127;
        if (t < 5) sts128(wg ? sb + XB + (t & 1) * XP + 4096 : sb + eslot(t), 0, 0, 0, 0);
        bar_sync(0, 384);
        asm volatile("barrier.cluster.arrive.relaxed.aligned;" ::: "memory");
        STAMPIF(warp == 0, 1);
        uint32_t dv = 0;
        if (t < 5) asm volatile("ld.global.nc.u16 %0, [%1];" : "=r"(dv) : "l"(padd(P.ssmD, (b + 128 * t) * 2)));
        FFN_ROLE;
        epoch = ldg_late(CNT(C_Z + tile, 6), lane);
        asm volatile("cp.async.wait_group 0;" ::: "memory");
        bar_sync(2, 256);
        mbar_arrive_if(BAR(B_KV), tid == 0);
        epoch = (__shfl_sync(~0u, epoch, 0) >> 7) + 1;
        asm volatile("barrier.cluster.wait.aligned;" ::: "memory");
        uint32_t g2e;
        asm("mapa.shared::cluster.u32 %0, %1, %2;" : "=r"(g2e) : "r"(BAR(B_G2E)), "r"(rank ^ (lane & 1)));
        const bool l01 = lane < 2;
        const uint32_t wre = g2e - 8 * (B_G2E - B_WE);
        {
            const uint32_t par = epoch & 1, xa = sb + XB + wg * XP;
            const char* gp = SC(kvT, (b + 128 * wg) * 4096 + t * 16);
            if (wg) bar_arrive(1, 256);
            auto krow = [&](int o) { const int tk = 39 - 8 * ((lane & 7) >> 1) - o, ro = (tk & 1) + 2 * (tk >> 3) + 10 * ((tk >> 1) & 3); return sb + ro * 128 + (((ro & 7) ^ (2 * w)) << 4); };
            const int o0 = 2 * (lane >> 3) + (lane & 1);
            const int tv = 31 - 8 * ((lane & 7) >> 1) - o0, rv = (tv & 1) + 2 * (tv >> 3) + 8 * ((tv >> 1) & 3);
            uint32_t aE = krow(o0), aH = krow(8 + (o0 & 3)), aV = sb + 5120 + rv * 128 + (((rv & 7) ^ (2 * w)) << 4);
            uint32_t tdo = (rank * 64 + w * 16 + rr) * 4096 + (252 - 4 * cl + q) * 16;
            asm volatile("" : "+r"(aE), "+r"(aH), "+r"(aV), "+r"(tdo));
            _Pragma("unroll 1") for (unsigned long long steps = wg ? SEQ1 : SEQ0; steps; steps >>= 8) {
                const int r = steps & 7;
                STAMPS(0);
                if (steps & 0x40) {
                    const uint32_t so = st_kv(r);
                    const char *dst = SC(kvT, tdo + r * 524288), *hc = CNT(C_KV + 2 * r + rank, t);
                    mbar_wait(BAR(B_KV + r), 0);
                    STAMPIF(w == 1 && (r & 3) == 0, 35 + r); STAMPS(1);
                    red_if(hc, 2, t == 0 && ((EARLYH >> r) & 1));
                    uint2 sw[2]; uint32_t ke[2][6], vv[2][4], o[2][4];
                    #pragma unroll
                    for (int u = 0; u < 2; u++) {
                        sw[u] = lds64(sb + ST_SH + r * 512 + w * 128 + rr * 8 + u * 64);
                        ldsm4t(ke[u], (aE ^ (u << 4)) + so); ldsm2t(ke[u][4], ke[u][5], (aH ^ (u << 4)) + so); ldsm4t(vv[u], (aV ^ (u << 4)) + so);
                    }
                    sched_bar();
                    #pragma unroll
                    for (int u = 0; u < 2; u++) {
                        uint32_t ko[5];
                        #pragma unroll
                        for (int j = 0; j < 5; j++) ko[j] = prmt(ke[u][j], ke[u][j + 1], 0x5432);
                        #pragma unroll
                        for (int j = 0; j < 4; j++) o[u][j] = hmul2(hfma2s<0>(ke[u][j], sw[u].x, hfma2s<1>(ko[j], sw[u].x, hfma2s<0>(ke[u][j + 1], sw[u].y, hfma2s<1>(ko[j + 1], sw[u].y, 0x80008000u)))), vv[u][j]);
                        o[u][0] = (o[u][0] & ~1u) | par;
                    }
                    asm volatile("{ .reg .pred h; setp.ne.b32 h, %10, 0; pmevent 1;\n @h red.relaxed.gpu.global.add.u32 [%9], 2;\n"
                                 " st.relaxed.gpu.global.v4.b32 [%0], {%1,%2,%3,%4}; st.relaxed.gpu.global.v4.b32 [%0+32768], {%5,%6,%7,%8}; }"
                                 :: "l"(dst), "r"(o[0][0]), "r"(o[0][1]), "r"(o[0][2]), "r"(o[0][3]), "r"(o[1][0]), "r"(o[1][1]), "r"(o[1][2]), "r"(o[1][3]),
                                    "l"(hc), "r"((int)(t == 0 && !((EARLYH >> r) & 1))) : "memory");
                    mbar_arrive_if(BAR(B_TD + r), l0 && r < 3);
                    STAMPIF(w == 1 && (r & 3) == 0, r ? 3 : 45);
                    continue;
                }
                const uint32_t eb = sb + eslot(r);
                if (steps & 0x20) {
                    const int ew = (t >> 1) & 3, et = (ew + (t >> 3)) & 3, eh = (t >> 5) & 1;
                    const uint32_t ha = eb + ((t & 64) + 16 * et + 8 * eh + 2 * ew + (t & 1)) * 16;
                    const uint32_t ea = eb + (t & 64) * 128 + (2 * ew + eh) * 1024 + ((2 * et + (t & 1)) << 4);
                    mbar_wait(BAR(B_H + r), 0);
                    STAMPIF(warp == 1 && r == 0, 2); STAMPS(1);
                    uint4 hv4[4];
                    #pragma unroll
                    for (int i = 0; i < 4; i++) hv4[i] = lds128(ha + (i >> 1) * 2048 + (i & 1) * 16);
                    if (w == 0) { const uint32_t dr = __shfl_sync(~0u, dv, r); if (l0) hv4[1].x = hadd2(hv4[1].x, dr); }
                    bar_sync(5 + wg, 128);
                    #pragma unroll
                    for (int h = 0; h < 2; h++) {
                        const uint32_t* w8 = &hv4[2 * h].x;
                        #pragma unroll
                        for (int row = 0; row < 8; row++) {
                            uint32_t o[4];
                            #pragma unroll
                            for (int i = 0; i < 4; i++) o[i] = (row & 1) ? prmt(w8[(7 - row) / 2 + i], w8[(7 - row) / 2 + i + 1], 0x5432) : w8[(8 - row) / 2 + i];
                            sts128((ea ^ (row << 4)) + row * 128 + h * 16384, o[0], o[1], o[2], o[3]);
                        }
                    }
                    if (!(steps & 0x2000)) fence_async_smem();
                    STAMPIF(w == 0, wg ? 30 : 4);
                    continue;
                }
                float acc[128];
                mbar_wait(BAR(B_X + wg), (r >> 1) & 1); STAMPS(1);
                STAMPIF(w == 0, 10 + r);
                bar_sync(1 + wg, 256);
                GSTAMPIF(w == 0 && r == 0, 7); STAMPS(2);
                _Pragma("unroll 1") for (int rep = 0;; rep++) {
                    wg_fence();
                    Conv<0>::run(acc, dlo(eb, 16), dlo(xa, 16));
                    wg_commit();
                    if (r < 4 && !rep) bar_arrive(2 - wg, 256);
                    uint32_t t0;
                    asm volatile("ld.shared.b32 %0, [%1];" : "=r"(t0) : "r"(xa + w * 512 + (lane >> 4) * 2048 + (lane & 15) * 32 + (lane & 4) * 4) : "memory");
                    wg_wait<0>();
                    pin<128>(acc);
                    STAMPIF(w == 0, 15 + r);
                    if (!bar_or(5 + wg, 128, (t0 ^ par) & 1) || rep) break;
                    VALIF(true, 90, 1);
                    _Pragma("unroll 1") for (int h = 0; h < 2; h++) {
                        uint4 kx = {0, 0, 0, 0};
                        _Pragma("unroll 1") for (int it = 0; it < 20000; it++) {
                            ldg_rlx128_if(kx, gp + h * 2048, true);
                            if (!__any_sync(~0u, (kx.x ^ par) & 1)) break;
                        }
                        sts128(xa + t * 16 + h * 2048, kx.x, kx.y, kx.z, kx.w);
                    }
                    fence_async_smem();
                    bar_sync(5 + wg, 128);
                }
                gp += 2 * 524288;
                mbar_arrive_if(BAR(B_MD + r), t == 0 && r < 3);
                const uint32_t pw = eb + w * PP + lane * 16;
                #pragma unroll
                for (int g = 0; g < 8; g++) {
                    uint32_t o[4];
                    #pragma unroll
                    for (int l = 0; l < 4; l++) { const int i = 4 * g + l;
                        o[l] = i < 31 ? pack2(acc[4 * i] + acc[4 * i + 6], acc[4 * i + 1] + acc[4 * i + 7]) : pack2(acc[4 * i], acc[4 * i + 1]); }
                    asm volatile("stmatrix.sync.aligned.m8n8.x4.trans.shared.b16 [%0], {%1,%2,%3,%4};" :: "r"(pw + g * 512), "r"(o[0]), "r"(o[1]), "r"(o[2]), "r"(o[3]) : "memory");
                    if (g & 1) sched_bar();
                }
                if (lane < 6) sts128(pw + 4096, 0, 0, 0, 0);
                bar_sync(5 + wg, 128);
                if (YH < 0) red_if(CNT(C_Y + r, t), 1, t == 0);
                char* yp = (char*)gp + (offsetof(Scratch, yT) - 2 * 524288);
                #pragma unroll
                for (int h = 0; h < 2; h++) {
                    uint4 p[4];
                    #pragma unroll
                    for (int k = 0; k < 4; k++) p[k] = lds128(eb + (t + 128 * h) * 16 + k * (PP + 32));
                    uint32_t y[4];
                    #pragma unroll
                    for (int j = 0; j < 4; j++) y[j] = hadd2((&p[0].x)[j], hadd2((&p[1].x)[j], hadd2((&p[2].x)[j], (&p[3].x)[j])));
                    stg_rlx128(yp + h * 2048, (y[0] & ~1u) | par, y[1], y[2], y[3]);
                    if (h == YH) red_if(CNT(C_Y + r, t), 1, t == 0);
                }
                __syncwarp();
                mbar_arrive_if(BAR(B_RD + r), l0);
                mbar_arrive_remote_if(wre + 16 * (r - 1) + (lane & 4) * 2, lane < 8 && (r == 1 || r == 2));
                STAMPIF(w == 0, 20 + r);
            }
        }
        float acc1[128];
        uint4 sv[2] = {};
        const char* s2p = SC(st2, (tile * 128 + wg * 64 + w * 16 + rr) * 16);
        auto pass1 = [&](int n0, int n1, auto&& top, auto&& mid) {
            _Pragma("unroll 1") for (int n = n0; n < n1; n++) {
                top();
                const uint32_t da = dlo(sb + wg * 4096, 16) + n * 512, db = dlo(sb + WR, 4096) + (n & 3) * 1024;
                TWAIT((n & 1) ? 91 : 10 + (n >> 1), mbar_wait(BAR(B_AF) + (n >> 1) * 8, 0));
                TWAIT(50 + n, mbar_wait(BAR(B_WF) + (n & 3) * 8, (n >> 2) & 1));
                GSTAMPIF(n == 0 && warp == 0, 8);
                STAMPIF(n == 0 && warp == 4, 9);
                STAMPI(warp == 0 && !(n & 1), 50 + (n >> 1));
                wg_fence();
                WG<256>::ss<0, 1>(acc1, da, dhi(512, 2), db, dhi(1024, 1), n0 ? 1 : n);
                if (ER & 1) {
                    wg_commit();
                    wg_wait<1>();
                    mbar_arrive_remote_if(wre + ((n + 3) & 3) * 8, l01 && n > 0);
                }
                WG<256>::ss<0, 1>(acc1, da + 2, dhi(512, 2), db + 128, dhi(1024, 1), 1);
                wg_commit();
                if (!(ER & 1)) {
                    wg_wait<1>();
                    mbar_arrive_remote_if(wre + ((n + 3) & 3) * 8, l01 && n > 0);
                }
                mid(n);
            }
        };
        pass1(0, N_UT, []() {}, [](int) {});
        {
            float au[8];
            const int un = min(2 * b + wg, 239), cg = (un * 205) >> 10;
            char* up = SC(ut, ((un - 5 * cg) * 3072 + cg * 64 + w * 16 + rr) * 8);
            pass1(N_UT, N_UT + 1, [&]() {
                TWAIT(20, mbar_wait(BAR(B_UF), 0));
                const uint32_t ua = dlo(sb + UST + wg * 16384, 16), ub = dlo(sb + CS_TAB + wg * 512, 32);
                wg_fence();
                #pragma unroll
                for (int ks = 0; ks < 8; ks++) WG<8>::ss<1, 0>(au + 4 * (ks & 1), ua + ks * 128, dhi(1024, 1), ub + ks * 4, dhi(128, 0), ks >= 2);
                wg_commit();
            }, [&](int) {
                pin<8>(au);
                asm volatile("{ .reg .pred p; .reg .b64 x; setp.eq.b32 p, %5, 0; mov.b64 x, {%1, %2}; @p st.relaxed.gpu.global.b64 [%0], x; mov.b64 x, {%3, %4}; @p st.relaxed.gpu.global.b64 [%0+64], x; }"
                             :: "l"(up), "r"(tagged(au[0] + au[4], epoch)), "f"(au[1] + au[5]), "r"(tagged(au[2] + au[6], epoch)), "f"(au[3] + au[7]), "r"(q | (b >= 120)) : "memory");
                mbar_arrive_if(BAR(B_UD), l0);
                STAMPIF(warp == 0, 25);
            });
        }
        pass1(N_UT + 1, 20, []() {}, [&](int n) { ldg_rlx128_if(sv[0], s2p, n == 16); ldg_rlx128_if(sv[1], s2p + 128, n == 16); });
        _Pragma("unroll 1") for (int it = 0; it < 20000 && __any_sync(~0u, sv[0].w != epoch || sv[1].w != epoch); it++) { ldg_rlx128_if(sv[0], s2p, true); ldg_rlx128_if(sv[1], s2p + 128, true); }
        float acc2[64];
        const float rq0 = __uint_as_float(sv[0].z), rq1 = __uint_as_float(sv[1].z);
        {
            uint32_t ax[4];
            const uint32_t zm = q == 0 ? ~0u : q == 1 ? 0xffffu : 0u, sh = q ? 0x5454 : 0x5410, sl = sh + 0x2222;
            uint32_t a0 = prmt(sv[0].x, sv[0].y, sh), a1 = prmt(sv[1].x, sv[1].y, sh), a2 = prmt(sv[0].x, sv[0].y, sl), a3 = prmt(sv[1].x, sv[1].y, sl);
            TWAIT(21, mbar_wait(BAR(B_T1), 0));
            wg_wait<0>();
            mbar_arrive_remote_if(wre + 24, l01);
            asm volatile("setmaxnreg.inc.sync.aligned.u32 232;\n and.b32 %0, %4, %8; and.b32 %1, %5, %8; and.b32 %2, %6, %8; and.b32 %3, %7, %8;"
                         : "=r"(ax[0]), "=r"(ax[1]), "=r"(ax[2]), "=r"(ax[3]) : "r"(a0), "r"(a1), "r"(a2), "r"(a3), "r"(zm) : "memory");
            wg_fence();
            WG<256>::rs<1>(acc1, ax[0], ax[1], ax[2], ax[3], dlo(sb + TAB1, 0), dhi(48, 0), 1);
            WG<128>::rs<1>(acc2, ax[0], ax[1], ax[2], ax[3], dlo(sb + TAB2, 0), dhi(48, 0), 0);
            wg_commit();
        }
        char* hdst = SC(hh, (tile * 24 + js * 3) * 16384 + warp * 1024 + rr * 64 + ((q ^ (rr >> 1)) << 4));
        GSTAMPIF(warp == 0, 26);
        uint32_t hq[48];
        const uint32_t tm = (lane & 7) == (w & 1) * 4;
        auto release2 = [&](int it) {
            mbar_arrive_remote_if(wre + 8 * ((it + 3) & 3), l01 && it < 7);
            mbar_arrive_if(BAR(B_HS - 7) + 8 * it, l0 && it >= 7);
            mbar_arrive_remote_if(g2e + 8 * (it - G2R), l01 && it >= G2R && it < G2R + 6);
        };
        auto pass2 = [&](int it, auto&& epi) {
            TWAIT(70 + it, mbar_wait(BAR(B_WF) + (it & 3) * 8, ((it >> 2) & 1) ^ 1));
            STAMPI(warp == 0, 60 + it);
            const uint32_t da = dlo(sb + wg * 4096, 16) + it * 1024, db = dlo(sb + WR, 8192) + (it & 3) * 1024;
            wg_fence();
            static_for<0, 4>([&](auto KS) {
                WG<128>::ss<0, 1>(acc2, da + (KS.value >> 1) * 512 + (KS.value & 1) * 2, dhi(512, 2), db + KS.value * 128, dhi(1024, 1), 1);
                if constexpr (KS.value == 3) wg_commit();
                if constexpr (KS.value == 0 && (ER & 2)) { wg_commit(); wg_wait<1>(); if (it) release2(it); }
                epi(KS);
            });
            if (!(ER & 2)) { wg_wait<1>(); if (it) release2(it); }
        };
        constexpr int NE = ((epi_slot(15) + E0) >> 2) + 1;
        static_for<0, NE>([&](auto IT) {
            pass2(IT.value, [&](auto KS) {
                if constexpr (IT.value == 0 && KS.value == 0) pin<128>(acc1);
                static_for<0, 16>([&](auto E) {
                    if constexpr (epi_slot(E.value) == 4 * IT.value + KS.value - E0) {
                        sched_bar();
                        ffn_epi<15 - E.value>(acc1, acc1 + 64, hq, hdst, tm, epoch, rq0, rq1);
                        if constexpr ((E.value & 7) == 7) { __syncwarp(); mbar_arrive_if(BAR(B_HD + (E.value >> 3)), l0); }
                        sched_bar();
                    }
                });
            });
        });
        _Pragma("unroll 1") for (int it = NE; it < 10; it++) pass2(it, [](auto) {});
        {
            float acc[80];
            static_for<0, 3>([&](auto IT) {
                constexpr int it = IT.value;
                TWAIT(35 + it, mbar_wait(BAR(B_G2F + it), 0));
                STAMPI(warp == 0 && it == 0, 70);
                const uint32_t db = dlo(sb + G2B + it * 20480, 2048);
                #pragma unroll
                for (int i = 0; i < 16; i++) asm volatile("" : "+r"(hq[16 * it + i]) :: "memory");
                wg_fence();
                static_for<0, 4>([&](auto KS) {
                    constexpr int ks = KS.value, sl = 4 * it + ks;
                    const uint32_t* o = hq + 16 * it + 8 * (ks >> 1) + 2 * (ks & 1);
                    WG<160>::rs<1>(acc, o[0], o[4], o[1], o[5], db + (ks >> 1) * 640 + (ks & 1) * 64, dhi(512, 2), it != 0 || ks != 0);
                    if constexpr (sl == 0 || ks == 3) wg_commit();
                    if constexpr (it > 0 && ks == 0 && (ER & 4)) { wg_commit(); wg_wait<1>(); mbar_arrive_remote_if(g2e + 8 * (it ? it - 1 : 0), l01); }
                    if constexpr (sl == 0) {
                        wg_wait<1>();
                        pin<64>(acc2);
                        mbar_arrive_if(BAR(B_S0), l0);
                        static_for<(G2R > 4 ? 10 - G2R : 6), 6>([&](auto G) { mbar_arrive_remote_if(g2e + 8 * G.value, l01); });
                    }
                    if constexpr (sl < 8 / Q2) {
                        sched_bar();
                        static_for<0, Q2>([&](auto J) { ffn_epi<7 - Q2 * sl - J.value>(acc2, acc2 + 32, hq + 32, hdst + 32768, tm, epoch, rq0, rq1); });
                        if constexpr (sl == 8 / Q2 - 1) { __syncwarp(); mbar_arrive_if(BAR(B_HD + 2), l0); }
                        sched_bar();
                    }
                    if constexpr (sl == 0) wg_fence();
                });
                if (it && !(ER & 4)) {
                    wg_wait<1>();
                    mbar_arrive_remote_if(g2e + 8 * (it ? it - 1 : 0), l01);
                }
            });
            mbar_wait(BAR(B_GB), 0);
            fence_async_glob();
            uint4 gw[5];
            #pragma unroll
            for (int i = 0; i < 5; i++) gw[i] = lds128(sb + GBT + q * 80 + i * 16);
            const uint32_t da = dlo(sb + G2A + wg * 4096, 16), db = dlo(sb + G2B, 2048);
            _Pragma("unroll 1") for (int it = 3; it < 12 - NST; it++) {
                const int g = it >= 6 ? it - 6 : it, ga = it >= 5 ? it - 5 : it + 1;
                TWAIT(35 + it, mbar_wait(BAR(B_G2F + g), it >= 6));
                TWAIT(77 + it, mbar_wait(BAR(B_AF - 3 + it), 1));
                STAMPI(warp == 0 && (it == 3 || it == 6), 70 + (it >> 2) + 1);
                wg_fence();
                #pragma unroll
                for (int ks = 0; ks < 4; ks++) {
                    WG<160>::ss<0, 1>(acc, da + ga * 1024 + (ks >> 1) * 512 + (ks & 1) * 2, dhi(512, 2), db + g * 1280 + (ks >> 1) * 640 + (ks & 1) * 64, dhi(512, 2), 1);
                    if (ks == 3 || (ks == 0 && (ER & 4))) wg_commit();
                    if (ks == ((ER & 4) ? 0 : 3)) {
                        wg_wait<1>();
                        mbar_arrive_remote_if(g2e + 8 * (it - 1), l01 && it < 7);
                        mbar_arrive_if(BAR(B_HS - 4) + 8 * it, l0 && it >= 4 && it < 7);
                    }
                }
            }
            mbar_wait(BAR(B_G2F + 6 - NST), 1);
            mbar_wait(BAR(B_AF + 9 - NST), 1);
            if (wg) TWAIT(47, bar_sync(7, 256));
            STAMPI(warp == 0, 73);
            float gf[80];
            wg_fence();
            static_for<48 - 4 * NST, 48>([&](auto K) {
                constexpr int it = K.value >> 2, ks = K.value & 3;
                WG<160>::ss<0, 1>(acc, da + (it == 11 ? 0 : it - 5) * 1024 + (ks >> 1) * 512 + (ks & 1) * 2, dhi(512, 2), db + (it - 6) * 1280 + (ks >> 1) * 640 + (ks & 1) * 64, dhi(512, 2), 1);
                if constexpr (it < 11 && ks == 1) TWAIT(36 + it, mbar_wait(BAR(B_G2F + it - 5), 1));
                if constexpr (it < 11 && ks == 2) TWAIT(78 + it, mbar_wait(BAR(B_AF + it - 2), 1));
                if constexpr (RQE == 2 && K.value >= 28 && K.value < 47) {
                    sched_bar();
                    #pragma unroll
                    for (int j = K.value - 28; j < (K.value == 46 ? 20 : K.value - 27); j++) {
                        const float lo = bflo((&gw[j >> 2].x)[j & 3]), hi = bfhi((&gw[j >> 2].x)[j & 3]);
                        gf[4 * j] = lo * rq0; gf[4 * j + 1] = hi * rq0; gf[4 * j + 2] = lo * rq1; gf[4 * j + 3] = hi * rq1;
                        pin<4>(gf + 4 * j);
                    }
                    sched_bar();
                }
                if constexpr (K.value == 39) wg_commit();
                if constexpr (K.value == 46) { if (!wg) bar_arrive(7, 256); }
            });
            wg_commit();
            wg_wait<1>();
            bar_sync(5 + wg, 128);
            uint32_t osts[2];
            const uint32_t orow = (lane & 7) * 336 + (lane >> 3) * 16;
            osts[0] = sb + G2A + (1 + w) * 16384 + wg * 4096; osts[1] = osts[0] + 8192;
            wg_wait<0>();
            pin<80>(acc);
            STAMPIF(w == 0, 27 + wg);
            GSTAMPIF(warp == 4, 29);
            #pragma unroll
            for (int hf = 0; hf < 2; hf++) {
                #pragma unroll
                for (int i = 0; i < 5; i++) {
                    uint32_t o[4];
                    const float rq = hf ? rq1 : rq0;
                    #pragma unroll
                    for (int j = 0; j < 4; j++) { const int n = 16 * i + 4 * j + 2 * hf; o[j] = RQE == 2 ? pack2(acc[n] * gf[n], acc[n + 1] * gf[n + 1]) : hmul2(RQE ? pack2(acc[n], acc[n + 1]) : pack2(acc[n] * rq, acc[n + 1] * rq), (&gw[i].x)[j]); }
                    asm volatile("stmatrix.sync.aligned.m8n8.x4.shared.b16 [%0], {%1,%2,%3,%4};" :: "r"(osts[hf] + orow + i * 64), "r"(o[0]), "r"(o[1]), "r"(o[2]), "r"(o[3]) : "memory");
                    if (EI && i < 4 && (EI == 1 || (i & 1))) sched_bar();
                }
                fence_async_smem();
                __syncwarp();
                if (elect()) { tma3d_red(&M.out, osts[hf], dq, 128 * tile + 16 * warp + 8 * hf); }
                sched_bar();
            }
            STAMPIF(w == 0, wg ? 31 : 85);
            if (elect()) asm volatile("cp.async.bulk.commit_group;\n cp.async.bulk.wait_group.read 0;" ::: "memory");
            STAMPIF(w == 3, wg ? 33 : 86);
            GSTAMPIF(warp == 4, 34);
        }
    } else {
        const int hw = warp & 3, wv = hw & 1;
        if (elect()) {
            if (warp & 2) {
                if (warp & 1) { _Pragma("unroll") for (int i = B_UD; i < NBARS; i++) mbar_init(BAR(i), bar_count(i)); }
                else { _Pragma("unroll") for (int i = B_WF; i < B_UD; i++) mbar_init(BAR(i), bar_count(i)); }
            } else { _Pragma("unroll") for (int i = 0; i < 20; i++) mbar_init(BAR(i) + wv * 160, 1); }
            asm volatile("fence.mbarrier_init.release.cluster;" ::: "memory");
            fence_async_smem();
        }
        __syncwarp();
        asm volatile("barrier.cluster.arrive.relaxed.aligned;" ::: "memory");
        const uint32_t t1 = clk0 + D_1 + ((((b * 37) & 127) * G_ST) >> 7);
        if (hw == 0) {
            bar_arrive(0, 384);
            if (lane < 15 && lane != B_KV) mbar_expect(BAR(lane), lane >= B_KV && lane < B_Q ? 9216 : 4096);
            __syncwarp();
            if (elect()) { wait_until(t1); bulk_g2s(sb + 16, P.ssm + b * 4096, 4096, BAR(B_H)); }
            __syncwarp();
            bar_sync(3, 128);
        } else { bar_sync(0, 384); bar_arrive(3, 128); }
        FFN_ROLE;
        const int kh = js >> 2, ft = tile * 8 + js;
        const int oz = __shfl_sync(~0u, tid >> 9, lane);
        epoch = ldg_rlx32(CNT(C_Z + tile, 6 + oz));
        if (hw == 0) {
            if (elect()) {
                auto x_fetch = [&](int r) {
                    if (!mbar_test(BAR(B_KV + r), 0)) { mbar_wait(BAR(B_KV + r), 0); pause(D_PK); }
                    poll_cnt(CNT(C_KV + 2 * r + (b >> 6), 0), (epoch | 127) + 1);
                    fence_async_glob();
                    if (r >= 2) mbar_wait(BAR(B_MD - 2 + r), 0);
                    mbar_expect(BAR(B_X + (r & 1)), 4096);
                    bulk_g2s(sb + XB + (r & 1) * XP, SC(kvT, (b + 128 * r) * 4096), 4096, BAR(B_X + (r & 1)));
                    STAMPIF(r < 2, 5 + r);
                };
                static_for<1, NORD>([&](auto I) {
                    constexpr char kind = ord_kind(I.value); constexpr int n = ord_index(I.value);
                    if constexpr (kind == 'k' && n >= 3) mbar_wait(BAR(B_TD + n - 3), 0);
                    if constexpr (kind != '_' && kind != 'x' && (TUNING || ord_time(I.value))) wait_until(t1 + TN(16 + I.value, ord_time(I.value)));
                    if constexpr (kind == 'k') { tma4d(sb + st_kv(n), &M.k, n * 128 + rank * 64, cl * 4 - 1, BAR(B_KV + n)); tma4d(sb + st_kv(n) + 5120, &M.v, n * 128 + rank * 64, cl * 4, BAR(B_KV + n)); }
                    if constexpr (kind == 'q') tma3d(sb + ST_Q + n * 4096, &M.q, ft * 16, n * 4, BAR(B_Q + n));
                    if constexpr (kind == 'h') bulk_g2s(sb + eslot(n) + 16, P.ssm + (b + 128 * n) * 4096, 4096, BAR(B_H + n));
                    if constexpr (kind == 'w') pf_l2(((n & 1) ? P.Wu : P.Wg) + (b + 128 * (n >> 1)) * 3072, 3072);
                    if constexpr (kind == 'x') x_fetch(n);
                });
                _Pragma("unroll 1") for (int r = ord_count('x'); r < 5; r++) x_fetch(r);
            }
        } else if (hw == 2 && elect()) { pf_map(&M.k); pf_map(&M.v); pf_map(&M.q); }
        __syncwarp();
        epoch = (__shfl_sync(~0u, epoch, 0) >> 7) + 1;
        const uint32_t target = epoch << 7, par = epoch & 1;
        const char* pa = lane < 8 ? CNT(C_Y, 0) : SC(abc, (lane & 7) * 128 + 12);
        const uint32_t want = lane < 8 ? target : epoch;
        auto y_poll = [&](int r) {
            if (!mbar_test(BAR(B_RD + r), 0)) { mbar_wait(BAR(B_RD + r), 0); pause(D_PY); }
            _Pragma("unroll 1") for (int it = 0; it < 20000 && __any_sync(~0u, (int)(ldg_rlx32(pa) - want) < 0); it++) {}
        };
        auto y_request = [&](int r) {
            if (elect()) {
                fence_async_glob();
                mbar_expect(BAR(B_Y + (r & 1)), 5120);
                tma5d(sb + ST_Y + (r & 1) * 4096, &M.y, 2032 - 16 * ft, 4 * r, BAR(B_Y + (r & 1)));
                bulk_g2s(sb + ST_Y + 8192 + (r & 1) * 1024, SC(abc, r * 1024), 1024, BAR(B_Y + (r & 1)));
            }
            STAMPIF(r < 2, 48 + r);
            pa += lane < 8 ? 4096 : 1024;
        };
        if (hw == 1) {
            if (elect()) pf_map(&M.y);
            mbar_wait(BAR(B_TD + 2), 0);
            wait_until(clk0 + D_M);
            _Pragma("unroll 1") for (int r = 0; r < 2; r++) {
                y_poll(r); y_request(r);
            }
        }
        if (hw >= 2) {
            pa += lane < 8 ? 8192 : 2048;
            {
                uint32_t aQ = sb + ST_Q + wv * 2048 + (lane & 15) * 64 + (((lane >> 1) + (lane >> 4)) & 3) * 16;
                float sq[4] = {0.f, 0.f, 0.f, 0.f};
                _Pragma("unroll 1") for (int rq = 0; rq < 5; rq++) {
                    mbar_wait(BAR(B_Q + rq), 0);
                    STAMPIF(wv && rq == 4, 44);
                    uint4 v[4];
                    #pragma unroll
                    for (int u = 0; u < 4; u++) v[u] = lds128((aQ ^ ((u & 1) << 5)) + (u >> 1) * 1024);
                    sched_bar();
                    #pragma unroll
                    for (int j = 0; j < 16; j++) acc_stat(sq[2 * (j & 1)], sq[2 * (j & 1) + 1], (&v[(j & 1) + (j >> 3) * 2].x)[(j >> 1) & 3]);
                    aQ += 4096;
                }
                asm volatile("st.shared.v2.f32 [%0], {%1,%2};" :: "r"(sb + ST_S + (lane & 15) * 48 + wv * 16 + (lane >> 4) * 8), "f"(sq[0] + sq[2]), "f"(sq[1] + sq[3]) : "memory");
            }
            float sa[4] = {0.f, 0.f, 0.f, 0.f};
            uint32_t yl = sb + ST_Y + wv * 1024 + lane * 32 + (lane & 4) * 4, ca = sb + ST_Y + 8192 + wv * 256 + q * 16;
            const uint32_t ym = rr ? 0u : 0x00010001u;
            char* zp = SC(z, tile * 163840 + wv * 8192 + (16 * js + 15 - rr) * 64 + ((q ^ 3 ^ (rr >> 1)) << 4));
            uint32_t xs = sb + ST_Q + wv * 1024 + (15 - rr) * 64 + q * 16;
            const uint32_t tm = (lane & 7) == (~js & 1) * 4;
            const char* zc = CNT(C_Z + tile, lane & 7);
            bar_sync(4, 64);
            STAMPIF(hw == 3, 46);
            uint32_t rs[2], mr[2];
            #pragma unroll
            for (int h = 0; h < 2; h++) {
                float f[2] = {0.f, 0.f};
                #pragma unroll
                for (int i = 0; i < 2; i++) { const uint4 a = lds128(sb + ST_S + (15 - 8 * h - rr) * 48 + i * 16); f[0] += __uint_as_float(a.x) + __uint_as_float(a.z); f[1] += __uint_as_float(a.y) + __uint_as_float(a.w); }
                const float mu = f[0] * (1.f / D_), r_ = rsqrt_(fmaxf(f[1] * (1.f / D_) - mu * mu, 0.f) + 1e-5f);
                rs[h] = pack2(r_, r_); const float m_ = -mu * bflo(rs[h]); mr[h] = pack2(m_, m_);
            }
            const int un = min(2 * b + wv, 239), cg = (un * 205) >> 10, ur = un - 5 * cg;
            char* op = padd(P.out, (ft * 16 + 15 - rr) * 1280 + wv * 64 + q * 16) - 256;
            uint4 x1[4] = {};
            const char *cp_ = SC(abc, (ur * 64 + (lane & 16) + q * 4 + (rr & 3)) * 16 + 8), *sp_ = SC(mod, (ur * 64 + lane) * 8);
            auto caddr = [&](int i) { return i < 2 ? sp_ + i * 256 : cp_ + (i & 1) * 512; };
            uint2 mv[4] = {};
            uint32_t pv = 0;
            bool asked = false;
            _Pragma("unroll 1") for (int r = 0;; r++) {
                STAMPR(0);
                uint4 x[4] = {};
                const bool ask = r >= 2 && r < 5 && wv == 0;
                if (ask) { if (!__any_sync(~0u, (int)(pv - want) < 0)) { y_request(r); asked = true; } else pv = ldg_rlx32(pa); }
                STAMPR(1);
                if (r < 5) {
                    #pragma unroll
                    for (int i = 0; i < 4; i++) x[i] = lds128(xs + (i >> 1) * 2048 - (i & 1) * 512);
                    sched_bar();
                } else {
                    mbar_wait(BAR(B_TD), 1);
                    if (elect()) {
                        mbar_expect(BAR(B_UF), 16384);
                        #pragma unroll
                        for (int i = 0; i < 2; i++) tma2d(sb + UST + wv * 16384 + i * 8192, cg >= 24 ? &M.u2 : &M.g2, (cg >= 24 ? cg - 24 : cg) * 64, ur * 128 + i * 64, BAR(B_UF));
                    }
                    ll_wait<4>(mv, epoch, caddr);
                    #pragma unroll
                    for (int i = 0; i < 4; i++) sts32(sb + CS_TAB + wv * 512 + ((i & 1) * 8 + rr) * 32 + q * 4 + (i < 2 ? 16 : 0), mv[i].x);
                    fence_async_smem(); __syncwarp(); mbar_arrive_if(BAR(B_UF), l0);
                    STAMPIF(wv, 41);
                }
                if (r) {
                    #pragma unroll
                    for (int j = 0; j < 16; j++) acc_stat(sa[j & 2], sa[(j & 2) + 1], (&x1[(j >> 1) & 3].x)[(j & 1) + (j >> 3) * 2]);
                    #pragma unroll
                    for (int j = 0; j < 4; j++) asm volatile("" : "+f"(sa[j]) :: "memory");
                    bump<32768>(zp); bump(yl, (r & 1) ? 4096 : -4096); bump(ca, (r & 1) ? 1024 : -1024);
                }
                STAMPR(2);
                uint32_t nx[16];
                #pragma unroll
                for (int j = 0; j < 16; j++) { nx[j] = hfma2((&x[j >> 2].x)[j & 3], rs[(j >> 2) & 1], mr[(j >> 2) & 1]); asm volatile("" : "+r"(nx[j]) :: "memory"); }
                sched_bar();
                if (r) {
                    #pragma unroll
                    for (int i = 0; i < 4; i++) stg128(op + (i >> 1) * 128 - (i & 1) * 10240, x1[i].x, x1[i].y, x1[i].z, x1[i].w);
                }
                if (r == 5) break;
                STAMPR(3);
                if (ask && !asked) { if (__any_sync(~0u, (int)(pv - want) < 0)) y_poll(r); y_request(r); }
                asked = false;
                STAMPR(4);
                mbar_wait(BAR(B_Y + (r & 1)), (r >> 1) & 1);
                if (wv == 0 && r) { mbar_wait(BAR(B_YE + (~r & 1)), (r - 1) >> 1 & 1); pv = ldg_rlx32(pa); }
                if (r == 4) { _Pragma("unroll") for (int i = 0; i < 4; i++) mv[i] = ldg_rlx64(caddr(i)); }
                STAMPIF(wv == 0 && r == 0, 47);
                STAMPR(5);
                uint4 cc[8];
                uint32_t y[4][4];
                _Pragma("unroll 1") for (int it = 0; it < 20000; it++) {
                    uint32_t all = ~0u, any = 0;
                    #pragma unroll
                    for (int i = 0; i < 4; i++) ldsm4t(y[i], (yl ^ ((i & 1) << 4)) + (i >> 1) * 2048);
                    #pragma unroll
                    for (int i = 0; i < 8; i++) cc[i] = lds128(ca + (i >> 2) * 512 + (i & 3) * 64);
                    #pragma unroll
                    for (int j = 0; j < 16; j++) { all &= y[j >> 2][j & 3]; any |= y[j >> 2][j & 3]; }
                    if (!__any_sync(~0u, ((par ? ~all : any) & ym) != 0)) break;
                    VALIF(true, 89, 1);
                    const char* yp = SC(yT, (r * 128 + wv * 32 + (lane & 6) * 4 + (lane >> 3) * 2 + (lane & 1)) * 4096 + (254 - 2 * ft) * 16);
                    #pragma unroll
                    for (int i = 0; i < 4; i++) cp16((yl ^ ((i & 1) << 4)) + (i >> 1) * 2048, yp + (i & 1) * 16 + (i >> 1) * 262144);
                    asm volatile("cp.async.wait_all;" ::: "memory");
                    __syncwarp();
                }
                STAMPR(6);
                bump<256>(op); bump(xs, 4096);
                if (ZE) red_if(zc, 8, lane == r);
                #pragma unroll
                for (int j = 0; j < 16; j++) {
                    (&x1[j >> 2].x)[j & 3] = hfma2(hfma2(nx[j], cc[(j >> 3) * 4 + (j & 3)].x, cc[(j >> 3) * 4 + (j & 3)].y), y[j >> 2][j & 3], (&x[j >> 2].x)[j & 3]);
                    y[j >> 2][j & 3] = hmul2((&x1[j >> 2].x)[j & 3], cc[(j >> 3) * 4 + (j & 3)].z);
                    if ((j & 3) == (~j >> 2 & 1)) y[j >> 2][j & 3] = (y[j >> 2][j & 3] & ~tm) | (par & tm);
                    asm volatile("" : "+r"(y[j >> 2][j & 3]) :: "memory");
                }
                sched_bar();
                #pragma unroll
                for (int i = 0; i < 4; i++) asm volatile("st.relaxed.gpu.global.v4.b32 [%0], {%1,%2,%3,%4};" :: "l"(zp + (i >> 1) * 16384 - (i & 1) * 512), "r"(y[i][0]), "r"(y[i][1]), "r"(y[i][2]), "r"(y[i][3]) : "memory");
                if (!ZE) red_if(zc, 8, lane == r);
                mbar_arrive_if(r == 4 ? BAR(B_TD) : BAR(B_YE + (r & 1)), lane <= (r == 4));
                mbar_arrive_if(BAR(B_H + r), tid == 352);
                STAMPIF(wv, 75 + r);
                STAMPR(7);
            }
            auto x1_release = [&]() {
                if (l0) asm volatile("fence.release.gpu;\n red.relaxed.gpu.global.add.u32 [%0], 16;" :: "l"(CNT(C_Z + tile, 6)) : "memory");
                __syncwarp();
            };
            const float e0 = ((q & 2) ? sa[2] : sa[0]) + __shfl_xor_sync(~0u, (q & 2) ? sa[0] : sa[2], 2), e1 = ((q & 2) ? sa[3] : sa[1]) + __shfl_xor_sync(~0u, (q & 2) ? sa[1] : sa[3], 2);
            float e = ((q & 1) ? e1 : e0) + __shfl_xor_sync(~0u, (q & 1) ? e0 : e1, 1);
            if (wv) sts32(sb + TAB2 + lane * 4, __float_as_uint(e));
            bar_sync(4, 64);
            if (wv) { if (!FLATE) x1_release(); }
            else {
                uint32_t oth; asm volatile("ld.shared.b32 %0, [%1];" : "=r"(oth) : "r"(sb + TAB2 + lane * 4) : "memory");
                e += __uint_as_float(oth);
                const float mu = e * (1.f / D_), ve = fmaxf(__shfl_down_sync(~0u, e, 1) * (1.f / D_) - mu * mu, 0.f) + 1e-5f, r_ = rsqrt_(ve);
                if (!(q & 1)) stg_rlx128(SC(st2, (ft * 16 + 15 - rr - 4 * q) * 16), split2(-mu), split2(ve * r_), __float_as_uint(r_ * r_), epoch);
            }
            if (!wv && elect()) pf_l2(P.Wd + b * 15360, 15360);
            mbar_wait(BAR(B_UD), 0);
            pause(D_UT);
            const char* up = SC(ut, (wv * 1536 + js * 192 + 2 * lane) * 8);
            uint4 v[15];
            _Pragma("unroll 1") for (int it = 0; it < 20000; it++) {
                uint32_t bad = 0;
                #pragma unroll
                for (int i = 0; i < 15; i++) v[i] = ldg_rlx2x64(up + (i / 3) * 24576 + (i % 3) * 512);
                #pragma unroll
                for (int i = 0; i < 15; i++) bad |= (v[i].x ^ epoch) | (v[i].z ^ epoch);
                if (!__any_sync(~0u, (bad & 7) != 0)) break;
            }
            #pragma unroll
            for (int n = 0; n < 3; n++) {
                float f[4];
                #pragma unroll
                for (int j = 0; j < 4; j++) f[j] = (__uint_as_float((&v[n].x)[j]) + __uint_as_float((&v[3 + n].x)[j])) + (__uint_as_float((&v[6 + n].x)[j]) + __uint_as_float((&v[9 + n].x)[j])) + __uint_as_float((&v[12 + n].x)[j]);
                const uint32_t ta = sb + TAB1 + ((n == 2 ? 32 + wv * 8 : n * 8 + wv * 16) + rr) * 48 + q * 4, th2 = pack2(f[1], f[3]);
                sts32(ta, pack2(f[0], f[2])); sts32(ta + 16, th2); sts32(ta + 32, pack2(f[1] - bflo(th2), f[3] - bfhi(th2)));
            }
            if (lane < 20) sts32(sb + TAB1 + 48 * 48 + lane * 4, 0);
            fence_async_smem();
            __syncwarp();
            mbar_arrive_if(BAR(B_T1), l0);
            STAMPIF(hw == 3, 43);
        }
        asm volatile("setmaxnreg.dec.sync.aligned.u32 40;");
        const uint32_t ep2 = __shfl_sync(~0u, epoch, 0), tg2 = ep2 << 7;
        const char* hfl = CNT(C_HH + tile * 2 + kh, 0);
        auto hh_src = [&](int j) { const int c = (j * 11) >> 5, m = j - 3 * c; return SC(hh, (tile * 24 + (kh * 4 + m + (m >= dq)) * 3 + (c ^ (c < 2))) * 16384); };
        if (hw == 0 || hw == 3) {
            if (hw == 0) {
            if (elect()) {
                const CUtensorMap *m1 = rank ? &M.u1 : &M.g1, *m2 = rank ? &M.u2 : &M.g2;
                const char* pw = P.Wg + (b + 128 * (NWP >> 1)) * 3072;
                const long long dw = P.Wu - P.Wg;
                pf_map(m1);
                _Pragma("unroll 1") for (int n = 0; n < 20; n += 2) {
                    #pragma unroll
                    for (int h = 0; h < 2; h++) {
                        const uint32_t so = (n & 2) + h;
                        mbar_wait(BAR(B_WE) + so * 8, (n >> 2) & 1);
                        mbar_expect(BAR(B_WF) + so * 8, 16384);
                        tma3d_mc(sb + WR + rank * 8192 + so * 16384, m1, (n + h) * 32, js * 3, BAR(B_WF) + so * 8);
                        if (n >= WP0 && n < WP0 + 10 - NWP) pf_l2(pw + h * dw, 3072);
                    }
                    if (n >= WP0) pw += 128 * 3072;
                }
                _Pragma("unroll 1") for (int n = 0; n < 10; n++) {
                    const uint32_t so = n & 3;
                    mbar_wait(BAR(B_WE) + so * 8, ((n >> 2) & 1) ^ 1);
                    mbar_expect(BAR(B_WF) + so * 8, 16384);
                    tma2d_mc(sb + WR + rank * 8192 + so * 16384, m2, js * 192 + 128, n * 64, BAR(B_WF) + so * 8);
                }
                if (FLATE) { poll_cnt(CNT(C_Z + tile, 6), tg2); fence_acq(); mbar_arrive_if(BAR(B_GB), true); }
            }
            } else {
                const char* gp = SC(mod, (320 + dq * 80 + lane) * 8);
                auto gaddr = [&](int i) { return gp + i * 192; };
                uint2 gv[3];
                #pragma unroll
                for (int i = 0; i < 3; i++) gv[i] = ldg_rlx64(gaddr(i));
                ll_wait<3>(gv, ep2, gaddr);
                if (!FLATE) { poll_cnt(CNT(C_Z + tile, 6), tg2); fence_acq(); }
                mbar_wait(BAR(B_HD), 0);
                red_if(hfl + lane * 4, 32, l0);
                STAMP(36);
                #pragma unroll
                for (int n = 0; n < 3; n++) sts32(sb + GBT + q * 80 + (rr + 6 * n) * 4, gv[n].x);
                __syncwarp();
                mbar_arrive_if(BAR(B_GB), lane <= !FLATE);
                mbar_wait(BAR(B_HD + 1), 0);
                red_if(hfl + lane * 4, 32, lane == 1);
            }
            if (elect()) {
                _Pragma("unroll 1") for (int j = 3 - hw; j < 6 + hw; j += j == 2 ? 4 : 1) {
                    const int c = (j * 11) >> 5;
                    const char* src = hh_src(j);
                    mbar_expect(BAR(B_AL + j), 16384);
                    if (j == 3 * c) { mbar_wait(BAR(B_HD + c), 0); if (c == 2) { red_if(hfl + 8, 32, true); STAMP(40); pause(D_H2); } poll_cnt(hfl + c * 4, tg2); fence_async_glob(); STAMPIF(c != 1, c ? 32 : 38); }
                    mbar_wait(c == 1 ? BAR(B_S0) : BAR(B_HS + j - 3 * c), c == 2);
                    bulk_g2s(sb + (j < 2 ? j + 12 : j < 8 ? j + 6 : 8) * 16384, src, 16384, BAR(B_AL + j));
                }
            }
        } else if (wv) {
            {
                if (lane < 10) mbar_expect(BAR(B_AL + lane), 16384);
                if (elect()) { pf_map(&M.g2); pf_map(&M.u2); }
                const char *zc = CNT(C_Z + tile, lane & 7), *zp = SC(z, tile * 163840);
                uint32_t rtp = 0, zv = tg2 - 1, al = BAR(B_AL), dst = sb;
                const uint32_t vo = lane * 128 + (lane & 3) * 16 + (lane & 8) * 8 + (lane & 4);
                int zr = 0;
                _Pragma("unroll 1") for (int i = 0; i < 19; i++) {
                    if (zr < 5) {
                        const uint32_t fre = BAR(zr == 4 ? B_UD : zr ? B_RD + 3 + (zr > 1) : B_RD);
                        bool go = (__ballot_sync(~0u, (int)(zv - tg2) >= 0) >> zr) & 1;
                        if (2 * zr <= i) {
                            mbar_wait(fre, 0);
                            if (!go) {
                                if (!mbar_test(BAR(B_H + zr), 1)) { mbar_wait(BAR(B_H + zr), 1); pause(D_PZ); }
                                poll_cnt(CNT(C_Z + tile, zr), tg2);
                            }
                            go = true;
                        } else go = go && mbar_test(fre, 0);
                        if (go) {
                            if (elect()) {
                                fence_async_glob();
                                bulk_g2s(sb + zr * 32768, zp, 16384, BAR(B_AL + 2 * zr));
                                bulk_g2s(sb + zr * 32768 + 16384, zp + 16384, 16384, BAR(B_AL + 2 * zr + 1));
                            }
                            STAMP(80 + zr);
                            zr++; zp += 32768;
                        }
                    }
                    mbar_wait(al, i >= 10);
                    _Pragma("unroll 1") for (int rt = 0; rt < 2000; rt++) {
                        uint32_t v[4];
                        #pragma unroll
                        for (int k = 0; k < 4; k++) asm volatile("ld.shared.b32 %0, [%1];" : "=r"(v[k]) : "r"(dst + vo + k * 4096) : "memory");
                        if (!__any_sync(~0u, ((v[0] ^ ep2) | (v[1] ^ ep2) | (v[2] ^ ep2) | (v[3] ^ ep2)) & 1)) break;
                        int i_ = i; asm volatile("" : "+r"(i_));
                        VALIF(true, 87 + (i >= 10), 1);
                        if (elect()) { mbar_expect(BAR(B_RT), 16384); bulk_g2s(dst, i_ < 10 ? SC(z, (tile * 10 + i_) * 16384) : hh_src(i_ - 10), 16384, BAR(B_RT)); }
                        mbar_wait(BAR(B_RT), rtp);
                        rtp ^= 1;
                    }
                    mbar_arrive_if(al - 8 * (B_AL - B_AF), l0);
                    if (zr < 5) zv = ldg_rlx32(zc);
                    al += i == 9 ? -72 : 8; dst += i == 9 ? 49152 : i == 11 || i == 17 ? -81920 : 16384;
                    STAMPIF(i == 0 || i == 10 || i == 16, i == 10 ? 37 : i ? 74 : 42);
                }
            }
        } else if (elect()) {
            if (FLATE) asm volatile("fence.release.gpu;\n red.relaxed.gpu.global.add.u32 [%0], 16;" :: "l"(CNT(C_Z + tile, 6)) : "memory");
            pf_map(&M.wn); pf_map(&M.wd); pf_map(&M.out);
            int g = 0, c = 0, m = -3;
            _Pragma("unroll 1") for (int n = 0; n < 12; n++) {
                const uint32_t st = sb + G2B + g * 20480 + rank * 10240, f = BAR(B_G2F + g);
                mbar_wait(BAR(B_G2E + g), n >= 6);
                mbar_expect(f, 20480);
                if (m < 0) tma3d_mc(st, &M.wn, (js * 3 + n) * 64 + rank * 32, dq * 5, f);
                else tma5d_mc(st, &M.wd, ((kh * 4 + m + (m >= dq)) * 3 + (c ^ (c < 2))) * 8 + rank * 4, dq * 5, f);
                g = g == 5 ? 0 : g + 1;
                if (++m == 3) { m = 0; c++; }
            }
        }
    }
}

typedef CUresult (*EncodeFn)(CUtensorMap*, CUtensorMapDataType, cuuint32_t, void*, const cuuint64_t*, const cuuint64_t*, const cuuint32_t*, const cuuint32_t*,
                             CUtensorMapInterleave, CUtensorMapSwizzle, CUtensorMapL2promotion, CUtensorMapFloatOOBfill);
void enc(EncodeFn fn, CUtensorMap* m, const void* ptr, int rank, const cuuint64_t* dims, const cuuint64_t* strides, const cuuint32_t* box, CUtensorMapSwizzle sw,
         CUtensorMapL2promotion pr = CU_TENSOR_MAP_L2_PROMOTION_L2_128B) {
    cuuint32_t es[5] = {1, 1, 1, 1, 1};
    fn(m, CU_TENSOR_MAP_DATA_TYPE_BFLOAT16, rank, (void*)ptr, dims, strides, box, es, CU_TENSOR_MAP_INTERLEAVE_NONE, sw,
       pr, CU_TENSOR_MAP_FLOAT_OOB_FILL_NONE);
}
}

extern "C" void kernel_launch(void* const* d_in, const int* in_sizes, int n_in, void* d_out, int out_size) {
    void* fnp = nullptr; cudaDriverEntryPointQueryResult st;
    cudaGetDriverEntryPoint("cuTensorMapEncodeTiled", &fnp, cudaEnableDefault, &st);
    EncodeFn fn = (EncodeFn)fnp;
    void* scr;
    cudaGetSymbolAddress(&scr, g_s);
    Maps M; Ptrs P;
    P.k = (const char*)d_in[1]; P.v = (const char*)d_in[2]; P.shift = (const char*)d_in[3]; P.ssm = (const char*)d_in[4]; P.ssmD = (const char*)d_in[5]; P.Wg = (const char*)d_in[7]; P.Wu = (const char*)d_in[8];
    P.Wd = (const char*)d_in[9]; P.c = (const char*)d_in[10]; P.out = (char*)d_out; P.scr = (char*)scr;
    { cuuint64_t d[4] = {640, 2, 256, 4}, s[3] = {1280, 8 * 1280, 2 * 1280}; cuuint32_t b1[4] = {64, 2, 5, 4}, b2[4] = {64, 2, 4, 4};
      enc(fn, &M.k, d_in[1], 4, d, s, b1, CU_TENSOR_MAP_SWIZZLE_128B); enc(fn, &M.v, d_in[2], 4, d, s, b2, CU_TENSOR_MAP_SWIZZLE_128B); }
    { cuuint64_t d[3] = {32, 2048, 20}, s[2] = {1280, 64}; cuuint32_t b1[3] = {32, 16, 4};
      enc(fn, &M.q, d_in[0], 3, d, s, b1, CU_TENSOR_MAP_SWIZZLE_NONE); }
    { cuuint64_t d[5] = {2048, 2, 4, 4, 20}, s[4] = {4096, 8 * 4096, 2 * 4096, 32 * 4096}; cuuint32_t b1[5] = {16, 2, 4, 4, 4};
      enc(fn, &M.y, (char*)scr + offsetof(Scratch, yT), 5, d, s, b1, CU_TENSOR_MAP_SWIZZLE_32B, CU_TENSOR_MAP_L2_PROMOTION_NONE); }
    { cuuint64_t d[3] = {64, 640, 24}, s[2] = {3072, 128}; cuuint32_t b1[3] = {64, 32, 2};
      enc(fn, &M.g1, P.Wg, 3, d, s, b1, CU_TENSOR_MAP_SWIZZLE_128B); enc(fn, &M.u1, P.Wu, 3, d, s, b1, CU_TENSOR_MAP_SWIZZLE_128B); }
    { cuuint64_t d[2] = {1536, 640}, s[1] = {3072}; cuuint32_t b1[2] = {64, 64};
      enc(fn, &M.g2, P.Wg, 2, d, s, b1, CU_TENSOR_MAP_SWIZZLE_128B); enc(fn, &M.u2, P.Wu, 2, d, s, b1, CU_TENSOR_MAP_SWIZZLE_128B); }
    { cuuint64_t d[5] = {32, 2, 192, 4, 20}, s[4] = {1280, 8 * 1280, 2 * 1280, 64}; cuuint32_t b1[5] = {32, 2, 4, 4, 5};
      enc(fn, &M.wd, P.Wd, 5, d, s, b1, CU_TENSOR_MAP_SWIZZLE_64B); }
    { cuuint64_t d[3] = {32, 1536, 20}, s[2] = {1280, 64}; cuuint32_t b1[3] = {32, 32, 5};
      enc(fn, &M.wn, P.Wd, 3, d, s, b1, CU_TENSOR_MAP_SWIZZLE_64B); }
    { cuuint64_t d[2] = {3840, 640}, s[1] = {7680}; cuuint32_t b1[2] = {64, 160};
      enc(fn, &M.wm, d_in[11], 2, d, s, b1, CU_TENSOR_MAP_SWIZZLE_128B); }
    { cuuint64_t d[3] = {160, 4, 2048}, s[2] = {320, 1280}; cuuint32_t b1[3] = {168, 1, 8};
      enc(fn, &M.out, d_out, 3, d, s, b1, CU_TENSOR_MAP_SWIZZLE_NONE); }
    cudaFuncSetAttribute(fused_kernel, cudaFuncAttributeMaxDynamicSharedMemorySize, SMEM_BYTES);
    fused_kernel<<<132, 384, SMEM_BYTES>>>(P, M);
}
```

```cpp
#include <cuda_runtime.h>
#include <cuda_bf16.h>
#include <cuda.h>
#include <stdint.h>
#include <stddef.h>
#include <type_traits>

namespace {

constexpr int D_ = 640;

struct Scratch {
    uint4 kvT[D_ * 256], yT[D_ * 256];
    uint4 z[16 * 10 * 1024];
    uint4 hh[16 * 24 * 1024];
    uint4 st2[2048];
    uint4 abc[320];
    uint2 mod[640];
    uint2 ut[5 * 3072];
    uint32_t cnt[64 * 1024];
};
__device__ __align__(1024) Scratch g_s;
#define SC(f, off) padd(P.scr, (uint32_t)offsetof(Scratch, f) + (off))
constexpr int C_KV = 0  , C_Y = 10  , C_Z = 16  , C_HH = 32  ;

constexpr uint32_t WR = 163840, MISC = 229376, SMEM_BYTES = 232448;
constexpr uint32_t ESLOT = 0x31650;
constexpr uint32_t XP = 4112, XB = 65536 + 18432, ST_SH = XB + 2 * XP;
constexpr uint32_t ST_Q = 131072, ST_Y = ST_Q + 20480, ST_S = ST_Y + 10240  , UST = ST_Q;
__host__ __device__ constexpr uint32_t st_kv(int r) { return r == 2 ? ST_Y : r == 1 || r == 4 ? 65536 + 9216 : 65536; }
__host__ __device__ constexpr uint32_t eslot(int r) { return ((ESLOT >> (4 * r)) & 7) << 15; }
constexpr uint32_t PP = 4352;
constexpr uint32_t BARS = MISC, TAB1 = MISC + 688, TAB2 = TAB1 + 32 * 48, CS_TAB = TAB1  , PRF = -256;
constexpr uint32_t GBT = 0, G2B = 8192, G2A = 131072;
enum { B_H = 0, B_KV = 5, B_Q = 10, B_X = 15  , B_MD = 17  , B_AF = 20, B_AL = 30, B_WF = 40, B_G2F = 44, B_OI = 50, B_RT = 51, B_Y = 52  ,
       B_WE = 54, B_G2E = 58,
       B_UD = 64, B_HD = 65  , B_S0 = 68, B_HS = 69  ,
       B_RD = 72, B_UF = 77, B_TD = 78  , B_T1 = 81, B_YE = 82  , B_GB = 84, NBARS = 85 };
__host__ __device__ constexpr uint32_t bar_count(int i) {
    return i < B_WE ? 1 : i < B_UD ? 16 : i < B_RD ? 8 : i < B_T1 ? 4 : 2;
}
#define GSTAMPIF(c, i) do {} while (0)
#define STAMPIF(c, i) do {} while (0)
#define STAMP(i) do {} while (0)
#define VALIF(c, i, v) do {} while (0)
#define STAMPI STAMPIF
#define STAMPR(i) do {} while (0)
#define TWAIT(i, stmt) stmt
#define STAMPS(k) do {} while (0)
#define QS 4
__host__ __device__ constexpr int epi_slot(int e) { return e * QS / 4; }
#define ER 7
#define MAPM 0
#define RQE 2
#define EI 1
#define SBAR 1
#define FLATE 1
#define E0 1
#define WDP 14
#define ALT 0
#define WI 0
#define Q2 4
#define G2R 5
#define YH 0
#define WP0 2
#define SEQ0 0x14124310224120ull
#define SEQ1 0x1324441123422140ull
#define NFAST 7
#define EARLYH 0
#define ZE 1
#define N_UT 13
#define NST 6
#define TN(i, v) v
#define TUNING 0
#define ORDER hkhhkxhqkxqqkqxqhwwww
#define TIMES 0, 860, 1570, 2100, 2890, 0, 3810, 0, 4520, 0, 0, 0, 6300, 0, 0, 0, 0, 8400, 0, 0, 0
#define STR2(x) #x
#define STR(x) STR2(x)
constexpr int NORD = sizeof(STR(ORDER)) - 1;
__host__ __device__ constexpr char ord_kind(int i) { return STR(ORDER)[i]; }
__host__ __device__ constexpr int ord_index(int i) { int n = ord_kind(i) == 'k'; for (int j = 0; j < i; j++) n += ord_kind(j) == ord_kind(i); return n; }
__host__ __device__ constexpr int ord_slot(int i) { int n = 0; for (int j = 0; j < i; j++) n += ord_kind(j) == 'k' ? 2 : ord_kind(j) != 'x'; return n; }
__host__ __device__ constexpr int ord_find(char c, int n) { for (int i = 0; i < NORD; i++) if (ord_kind(i) == c && ord_index(i) == n) return i; return -1; }
__host__ __device__ constexpr int ord_count(char c) { int n = 0; for (int i = 0; i < NORD; i++) n += ord_kind(i) == c; return n; }
__host__ __device__ constexpr uint32_t ord_mask(char c) { uint32_t m = 0; for (int i = 0; i < NORD; i++) m |= (uint32_t)(ord_kind(i) == c) << i; return m; }
__host__ __device__ constexpr int ord_time(int i) { constexpr int t[] = {TIMES}; return t[i]; }
constexpr int NWP = ord_count('w');
static_assert(NWP % 2 == 0 && ord_kind(0) == 'h' && ord_count('x') >= 2 && ord_count('k') == 4 && ord_count('q') == 5 && ord_count('h') == 5, "order");
#define TV0 500
#define D_1 TN(0, TV0)
#define TV1 420
#define G_U TN(1, TV1)
#define TV2 590
#define G_ST TN(2, TV2)
#define TV4 2000
#define D_SP TN(4, TV4)
#define TV5 0
#define G_F TN(5, TV5)
#define TV6 7500
#define D_M TN(6, TV6)
#define TV7 700
#define D_PK TN(7, TV7)
#define TV8 500
#define D_PY TN(8, TV8)
#define TV9 100
#define D_PZ TN(9, TV9)
#define TV10 400
#define D_H2 TN(10, TV10)
#define TV11 1600
#define D_UT TN(11, TV11)

__device__ __forceinline__ uint32_t smem_u32(const void* p) { return (uint32_t)__cvta_generic_to_shared(p); }
__device__ __forceinline__ void mbar_init(uint32_t bar, uint32_t cnt) { asm volatile("mbarrier.init.shared::cta.b64 [%0], %1;" :: "r"(bar), "r"(cnt) : "memory"); }
__device__ __forceinline__ void mbar_expect(uint32_t bar, uint32_t bytes) { asm volatile("mbarrier.arrive.expect_tx.shared::cta.b64 _, [%0], %1;" :: "r"(bar), "r"(bytes) : "memory"); }
__device__ __forceinline__ void mbar_arrive_if(uint32_t bar, bool p) { asm volatile("{ .reg .pred p; setp.ne.b32 p, %1, 0; @p mbarrier.arrive.shared::cta.b64 _, [%0]; }" :: "r"(bar), "r"((int)p) : "memory"); }
__device__ __forceinline__ void mbar_arrive_remote_if(uint32_t bar, bool p) { asm volatile("{ .reg .pred p; setp.ne.b32 p, %1, 0; @p mbarrier.arrive.shared::cluster.b64 _, [%0]; }" :: "r"(bar), "r"((int)p) : "memory"); }
#define WAIT_LOOP(op) "{\n .reg .pred p, q; .reg .u32 c; mov.u32 c, 0;\n LAB_WAIT:\n " op " p, [%0], %1;\n @p bra LAB_DONE;\n add.u32 c, c, 1; setp.lt.u32 q, c, 16384;\n @q bra LAB_WAIT;\n LAB_DONE:\n }"
__device__ __forceinline__ void mbar_wait(uint32_t bar, uint32_t parity) { asm volatile(WAIT_LOOP("mbarrier.try_wait.parity.shared::cta.b64") :: "r"(bar), "r"(parity) : "memory"); }
__device__ __forceinline__ bool mbar_test(uint32_t bar, uint32_t parity) {
    uint32_t ok; asm volatile("{ .reg .pred p; mbarrier.test_wait.parity.shared::cta.b64 p, [%1], %2; selp.u32 %0, 1, 0, p; }" : "=r"(ok) : "r"(bar), "r"(parity) : "memory"); return ok;
}
__device__ __forceinline__ uint32_t clock32() { uint32_t t; asm volatile("mov.u32 %0, %%clock;" : "=r"(t) :: "memory"); return t; }
__device__ __forceinline__ void wait_clock(uint32_t t0, uint32_t d) {
    asm volatile("{\n .reg .pred p; .reg .u32 t;\n LAB_CLK:\n mov.u32 t, %%clock; sub.u32 t, t, %0; setp.lt.u32 p, t, %1;\n @p bra LAB_CLK;\n }" :: "r"(t0), "r"(d) : "memory");
}
__device__ __forceinline__ bool elect() { uint32_t p; asm volatile("{ .reg .pred p; elect.sync _|p, 0xffffffff; selp.u32 %0, 1, 0, p; }" : "=r"(p)); return p; }
__device__ __forceinline__ void pf_map(const CUtensorMap* m) { asm volatile("prefetch.tensormap [%0];" :: "l"(m) : "memory"); }
__device__ __forceinline__ void bar_sync(int id, int n) { asm volatile("bar.sync %0, %1;" :: "r"(id), "r"(n) : "memory"); }
__device__ __forceinline__ bool bar_or(int id, int n, bool c) {
    uint32_t r; asm volatile("{ .reg .pred p, q; setp.ne.b32 p, %3, 0; bar.red.or.pred q, %1, %2, p; selp.u32 %0, 1, 0, q; }" : "=r"(r) : "r"(id), "r"(n), "r"((int)c) : "memory"); return r;
}
__device__ __forceinline__ void wait_until(uint32_t t1) {
    asm volatile("{\n .reg .pred p; .reg .s32 t;\n LAB_CLK:\n mov.u32 t, %%clock; sub.s32 t, t, %0; setp.lt.s32 p, t, 0;\n @p bra LAB_CLK;\n }" :: "r"(t1) : "memory");
}
__device__ __forceinline__ void pause(uint32_t d) { wait_clock(clock32(), d); }
__device__ __forceinline__ void bar_arrive(int id, int n) { asm volatile("bar.arrive %0, %1;" :: "r"(id), "r"(n) : "memory"); }
__device__ __forceinline__ void fence_async_smem() { asm volatile("fence.proxy.async.shared::cta;" ::: "memory"); }
__device__ __forceinline__ void fence_async_glob() { asm volatile("fence.proxy.async.global;" ::: "memory"); }
__device__ __forceinline__ void fence_acq() { asm volatile("fence.acquire.gpu;" ::: "memory"); }
__device__ __forceinline__ void bulk_g2s(uint32_t dst, const void* src, uint32_t bytes, uint32_t bar) {
    asm volatile("cp.async.bulk.shared::cluster.global.mbarrier::complete_tx::bytes [%0], [%1], %2, [%3];" :: "r"(dst), "l"(src), "r"(bytes), "r"(bar) : "memory");
}
__device__ __forceinline__ void pf_l2(const void* src, uint32_t bytes) { asm volatile("cp.async.bulk.prefetch.L2.global [%0], %1;" :: "l"(src), "r"(bytes) : "memory"); }
__device__ __forceinline__ void tma2d(uint32_t dst, const CUtensorMap* m, int c0, int c1, uint32_t bar) {
    asm volatile("cp.async.bulk.tensor.2d.shared::cluster.global.mbarrier::complete_tx::bytes [%0], [%1, {%3, %4}], [%2];" :: "r"(dst), "l"(m), "r"(bar), "r"(c0), "r"(c1) : "memory");
}
__device__ __forceinline__ void tma3d(uint32_t dst, const CUtensorMap* m, int c1, int c2, uint32_t bar) {
    asm volatile("cp.async.bulk.tensor.3d.shared::cluster.global.mbarrier::complete_tx::bytes [%0], [%1, {%5, %3, %4}], [%2];" :: "r"(dst), "l"(m), "r"(bar), "r"(c1), "r"(c2), "r"(0) : "memory");
}
__device__ __forceinline__ void tma4d(uint32_t dst, const CUtensorMap* m, int c0, int c2, uint32_t bar) {
    asm volatile("cp.async.bulk.tensor.4d.shared::cluster.global.mbarrier::complete_tx::bytes [%0], [%1, {%3, %5, %4, %5}], [%2];" :: "r"(dst), "l"(m), "r"(bar), "r"(c0), "r"(c2), "r"(0) : "memory");
}
__device__ __forceinline__ void tma5d(uint32_t dst, const CUtensorMap* m, int c0, int c4, uint32_t bar) {
    asm volatile("cp.async.bulk.tensor.5d.shared::cluster.global.mbarrier::complete_tx::bytes [%0], [%1, {%3, %5, %5, %5, %4}], [%2];" :: "r"(dst), "l"(m), "r"(bar), "r"(c0), "r"(c4), "r"(0) : "memory");
}
__device__ __forceinline__ void tma5d_mc(uint32_t dst, const CUtensorMap* m, int c2, int c4, uint32_t bar) {
    asm volatile("cp.async.bulk.tensor.5d.shared::cluster.global.mbarrier::complete_tx::bytes.multicast::cluster [%0], [%1, {%5, %5, %3, %5, %4}], [%2], %6;"
                 :: "r"(dst), "l"(m), "r"(bar), "r"(c2), "r"(c4), "r"(0), "h"((uint16_t)3) : "memory");
}
__device__ __forceinline__ void tma3d_mc(uint32_t dst, const CUtensorMap* m, int c1, int c2, uint32_t bar) {
    asm volatile("cp.async.bulk.tensor.3d.shared::cluster.global.mbarrier::complete_tx::bytes.multicast::cluster [%0], [%1, {%5, %3, %4}], [%2], %6;"
                 :: "r"(dst), "l"(m), "r"(bar), "r"(c1), "r"(c2), "r"(0), "h"((uint16_t)3) : "memory");
}
__device__ __forceinline__ void tma2d_mc(uint32_t dst, const CUtensorMap* m, int c0, int c1, uint32_t bar) {
    asm volatile("cp.async.bulk.tensor.2d.shared::cluster.global.mbarrier::complete_tx::bytes.multicast::cluster [%0], [%1, {%3, %4}], [%2], %5;"
                 :: "r"(dst), "l"(m), "r"(bar), "r"(c0), "r"(c1), "h"((uint16_t)3) : "memory");
}
__device__ __forceinline__ void tma3d_red(const CUtensorMap* m, uint32_t src, int c1, int c2) {
    asm volatile("cp.reduce.async.bulk.tensor.3d.global.shared::cta.add.bulk_group [%0, {%4, %2, %3}], [%1];" :: "l"(m), "r"(src), "r"(c1), "r"(c2), "r"(0) : "memory");
}
__device__ __forceinline__ void red_if(const void* c, uint32_t inc, bool p) { asm volatile("{ .reg .pred p; setp.ne.b32 p, %2, 0; @p red.relaxed.gpu.global.add.u32 [%0], %1; }" :: "l"(c), "r"(inc), "r"((int)p) : "memory"); }
__device__ __forceinline__ uint32_t ldg_rlx32(const void* p) { uint32_t v; asm volatile("ld.relaxed.gpu.global.u32 %0, [%1];" : "=r"(v) : "l"(p) : "memory"); return v; }
__device__ __forceinline__ uint32_t ldg_late(const char* p, int lane) { return ldg_rlx32(p + (lane & 1) * 4); }
__device__ __forceinline__ bool reached(uint32_t v, uint32_t target) { return __ballot_sync(~0u, (int)(v - target) >= 0) & 1; }
__device__ __forceinline__ uint2 ldg_rlx64(const void* p) { uint2 v; asm volatile("{ .reg .b64 x; ld.relaxed.gpu.global.b64 x, [%2]; mov.b64 {%0, %1}, x; }" : "=r"(v.x), "=r"(v.y) : "l"(p) : "memory"); return v; }
__device__ __forceinline__ void ldg_rlx128_if(uint4& v, const void* p, bool c) {
    asm volatile("{ .reg .b128 t; .reg .b64 x, y; .reg .pred p; setp.ne.b32 p, %5, 0; mov.b64 x, {%0, %1}; mov.b64 y, {%2, %3}; mov.b128 t, {x, y};\n"
                 " @p ld.relaxed.gpu.global.b128 t, [%4]; mov.b128 {x, y}, t; mov.b64 {%0, %1}, x; mov.b64 {%2, %3}, y; }"
                 : "+r"(v.x), "+r"(v.y), "+r"(v.z), "+r"(v.w) : "l"(p), "r"((int)c) : "memory");
}
__device__ __forceinline__ uint4 ldg_rlx2x64(const void* p) { uint4 v; asm volatile("{ .reg .b64 x, y; ld.relaxed.gpu.global.v2.b64 {x, y}, [%4]; mov.b64 {%0, %1}, x; mov.b64 {%2, %3}, y; }" : "=r"(v.x), "=r"(v.y), "=r"(v.z), "=r"(v.w) : "l"(p) : "memory"); return v; }
__device__ __forceinline__ void stg_rlx128(void* p, uint32_t x, uint32_t y, uint32_t z, uint32_t w) {
    asm volatile("{ .reg .b128 t; .reg .b64 a, b; mov.b64 a, {%1, %2}; mov.b64 b, {%3, %4}; mov.b128 t, {a, b}; st.relaxed.gpu.global.b128 [%0], t; }" :: "l"(p), "r"(x), "r"(y), "r"(z), "r"(w) : "memory");
}
__device__ __forceinline__ void stg_rlx128_if(void* p, const uint32_t* v, bool c) {
    asm volatile("{ .reg .pred p; .reg .b128 t; .reg .b64 a, b; setp.ne.b32 p, %5, 0; mov.b64 a, {%1, %2}; mov.b64 b, {%3, %4}; mov.b128 t, {a, b}; @p st.relaxed.gpu.global.b128 [%0], t; }" :: "l"(p), "r"(v[0]), "r"(v[1]), "r"(v[2]), "r"(v[3]), "r"((int)c) : "memory");
}
__device__ __forceinline__ void stg128(void* p, uint32_t x, uint32_t y, uint32_t z, uint32_t w) { asm volatile("st.global.v4.b32 [%0], {%1,%2,%3,%4};" :: "l"(p), "r"(x), "r"(y), "r"(z), "r"(w) : "memory"); }
template<int W> __device__ __forceinline__ void stg_tag(void* p, const uint32_t* o, uint32_t tm, uint32_t par) {
    const uint32_t t = (o[W] & ~tm) | (par & tm);
    asm volatile("st.relaxed.gpu.global.v4.b32 [%0], {%1,%2,%3,%4};" :: "l"(p), "r"(W ? o[0] : t), "r"(W ? t : o[1]), "r"(o[2]), "r"(o[3]) : "memory");
}
__device__ __forceinline__ void poll_cnt(const void* c, uint32_t target) {
    asm volatile("{\n .reg .pred p, q; .reg .u32 c, v; mov.u32 c, 0;\n LAB_POLL:\n ld.relaxed.gpu.global.u32 v, [%0];\n sub.u32 v, v, %1; setp.ge.s32 p, v, 0;\n @p bra LAB_PDONE;\n"
                 " add.u32 c, c, 1; setp.lt.u32 q, c, 20000;\n @q bra LAB_POLL;\n LAB_PDONE:\n }" :: "l"(c), "r"(target) : "memory");
}
template<int N, typename F> __device__ __forceinline__ void ll_wait(uint2* v, uint32_t tag, F&& addr) {
    #pragma unroll 1
    for (int it = 0; it < 20000; it++) {
        uint32_t bad = 0;
        #pragma unroll
        for (int i = 0; i < N; i++) bad |= v[i].y ^ tag;
        if (!__any_sync(~0u, bad != 0)) break;
        asm volatile("nanosleep.u32 100;");
        #pragma unroll
        for (int i = 0; i < N; i++) v[i] = ldg_rlx64(addr(i));
    }
}
__device__ __forceinline__ uint4 lds128(uint32_t a) { uint4 v; asm volatile("ld.shared.v4.b32 {%0,%1,%2,%3}, [%4];" : "=r"(v.x), "=r"(v.y), "=r"(v.z), "=r"(v.w) : "r"(a) : "memory"); return v; }
__device__ __forceinline__ uint2 lds64(uint32_t a) { uint2 v; asm volatile("ld.shared.v2.b32 {%0,%1}, [%2];" : "=r"(v.x), "=r"(v.y) : "r"(a) : "memory"); return v; }
__device__ __forceinline__ void sts128(uint32_t a, uint32_t x, uint32_t y, uint32_t z, uint32_t w) { asm volatile("st.shared.v4.b32 [%0], {%1,%2,%3,%4};" :: "r"(a), "r"(x), "r"(y), "r"(z), "r"(w) : "memory"); }
__device__ __forceinline__ void sts32(uint32_t a, uint32_t x) { asm volatile("st.shared.b32 [%0], %1;" :: "r"(a), "r"(x) : "memory"); }
__device__ __forceinline__ void ldsm4t(uint32_t* r, uint32_t a) { asm volatile("ldmatrix.sync.aligned.m8n8.x4.trans.shared.b16 {%0,%1,%2,%3}, [%4];" : "=r"(r[0]), "=r"(r[1]), "=r"(r[2]), "=r"(r[3]) : "r"(a) : "memory"); }
__device__ __forceinline__ void ldsm2t(uint32_t& r0, uint32_t& r1, uint32_t a) { asm volatile("ldmatrix.sync.aligned.m8n8.x2.trans.shared.b16 {%0,%1}, [%2];" : "=r"(r0), "=r"(r1) : "r"(a) : "memory"); }
__device__ __forceinline__ void ldsm4t_if(uint32_t* r, uint32_t a, bool c) { asm volatile("{ .reg .pred p; setp.ne.b32 p, %5, 0; @p ldmatrix.sync.aligned.m8n8.x4.trans.shared.b16 {%0,%1,%2,%3}, [%4]; }" : "+r"(r[0]), "+r"(r[1]), "+r"(r[2]), "+r"(r[3]) : "r"(a), "r"((int)c) : "memory"); }
__device__ __forceinline__ void ldsm2t_if(uint32_t* r, uint32_t a, bool c) { asm volatile("{ .reg .pred p; setp.ne.b32 p, %3, 0; @p ldmatrix.sync.aligned.m8n8.x2.trans.shared.b16 {%0,%1}, [%2]; }" : "+r"(r[0]), "+r"(r[1]) : "r"(a), "r"((int)c) : "memory"); }
__device__ __forceinline__ void lds128_if(uint4& v, uint32_t a, bool c) { asm volatile("{ .reg .pred p; setp.ne.b32 p, %5, 0; @p ld.shared.v4.b32 {%0,%1,%2,%3}, [%4]; }" : "+r"(v.x), "+r"(v.y), "+r"(v.z), "+r"(v.w) : "r"(a), "r"((int)c) : "memory"); }
__device__ __forceinline__ void cp16(uint32_t d, const void* s) { asm volatile("cp.async.cg.shared.global [%0], [%1], 16;" :: "r"(d), "l"(s) : "memory"); }
__device__ __forceinline__ char* padd(const void* p, uint32_t off) { char* r; asm("{ .reg .u64 t; cvt.u64.u32 t, %2; add.u64 %0, %1, t; }" : "=l"(r) : "l"(p), "r"(off)); return r; }
__device__ __forceinline__ uint32_t prmt(uint32_t a, uint32_t b, uint32_t s) { uint32_t r; asm("prmt.b32 %0, %1, %2, %3;" : "=r"(r) : "r"(a), "r"(b), "r"(s)); return r; }
__device__ __forceinline__ uint32_t pack2(float lo, float hi) { uint32_t r; asm("cvt.rn.bf16x2.f32 %0, %1, %2;" : "=r"(r) : "f"(hi), "f"(lo)); return r; }
__device__ __forceinline__ uint32_t pack2relu(float lo, float hi) { uint32_t r; asm("cvt.rn.relu.bf16x2.f32 %0, %1, %2;" : "=r"(r) : "f"(hi), "f"(lo)); return r; }
__device__ __forceinline__ float bflo(uint32_t w) { return __uint_as_float(w << 16); }
__device__ __forceinline__ float bfhi(uint32_t w) { return __uint_as_float(w & 0xffff0000u); }
__device__ __forceinline__ float bfround(float x) { return bflo(pack2(x, x)); }
__device__ __forceinline__ uint32_t hmul2(uint32_t a, uint32_t b) { uint32_t r; asm("mul.rn.bf16x2 %0, %1, %2;" : "=r"(r) : "r"(a), "r"(b)); return r; }
__device__ __forceinline__ uint32_t hadd2(uint32_t a, uint32_t b) { uint32_t r; asm("add.rn.bf16x2 %0, %1, %2;" : "=r"(r) : "r"(a), "r"(b)); return r; }
__device__ __forceinline__ uint32_t hfma2(uint32_t a, uint32_t b, uint32_t c) { uint32_t r; asm("fma.rn.bf16x2 %0, %1, %2, %3;" : "=r"(r) : "r"(a), "r"(b), "r"(c)); return r; }
__device__ __forceinline__ void sched_bar() { asm volatile("pmevent 1;" ::: "memory"); }
template<int H> __device__ __forceinline__ uint32_t hfma2s(uint32_t a, uint32_t w, uint32_t c) {
    uint32_t r;
    if (H) asm("{ .reg .b16 l, h; .reg .b32 t; mov.b32 {l, h}, %2; mov.b32 t, {h, h}; fma.rn.bf16x2 %0, %1, t, %3; }" : "=r"(r) : "r"(a), "r"(w), "r"(c));
    else asm("{ .reg .b16 l, h; .reg .b32 t; mov.b32 {l, h}, %2; mov.b32 t, {l, l}; fma.rn.bf16x2 %0, %1, t, %3; }" : "=r"(r) : "r"(a), "r"(w), "r"(c));
    return r;
}
__device__ __forceinline__ void bump(uint32_t& a, uint32_t d) { asm volatile("add.u32 %0, %0, %1;" : "+r"(a) : "r"(d) : "memory"); }
template<int D> __device__ __forceinline__ void bump(char*& p) { asm volatile("add.s64 %0, %0, %1;" : "+l"(p) : "n"(D) : "memory"); }
__device__ __forceinline__ void wg_fence() { asm volatile("wgmma.fence.sync.aligned;" ::: "memory"); }
__device__ __forceinline__ void wg_commit() { asm volatile("wgmma.commit_group.sync.aligned;" ::: "memory"); }
template<int N> __device__ __forceinline__ void wg_wait() { asm volatile("wgmma.wait_group.sync.aligned %0;" :: "n"(N) : "memory"); }
template<int N> __device__ __forceinline__ void pin(float* d) {
    #pragma unroll
    for (int i = 0; i < N; i++) asm volatile("" : "+f"(d[i]) :: "memory");
}
__device__ __forceinline__ uint32_t dlo(uint32_t addr, uint32_t lbo) { return ((addr & 0x3FFFF) >> 4) | ((lbo >> 4) << 16); }
__host__ __device__ constexpr uint32_t dhi(uint32_t sbo, uint32_t sw) { return (sbo >> 4) | (sw << 30); }

template<int N> struct WG;
template<> struct WG<8> { template<int TA, int TB> static __device__ __forceinline__ void ss(float* d, uint32_t alo, uint32_t ahi, uint32_t blo, uint32_t bhi, int sd) {
  asm volatile("{ .reg .pred p; .reg .b64 da, db; mov.b64 da, {%4,%5}; mov.b64 db, {%6,%7}; setp.ne.b32 p, %8, 0;\n"
    "wgmma.mma_async.sync.aligned.m64n8k16.f32.bf16.bf16 {%0,%1,%2,%3}, da, db, p, 1, 1, %9, %10; }"
    : "+f"(d[0]),"+f"(d[1]),"+f"(d[2]),"+f"(d[3])
    : "r"(alo), "r"(ahi), "r"(blo), "r"(bhi), "r"(sd), "n"(TA), "n"(TB)); }
};
template<> struct WG<16> { template<int TA, int TB> static __device__ __forceinline__ void ss(float* d, uint32_t alo, uint32_t ahi, uint32_t blo, uint32_t bhi, int sd) {
  asm volatile("{ .reg .pred p; .reg .b64 da, db; mov.b64 da, {%8,%9}; mov.b64 db, {%10,%11}; setp.ne.b32 p, %12, 0;\n"
    "wgmma.mma_async.sync.aligned.m64n16k16.f32.bf16.bf16 {%0,%1,%2,%3,%4,%5,%6,%7}, da, db, p, 1, 1, %13, %14; }"
    : "+f"(d[0]),"+f"(d[1]),"+f"(d[2]),"+f"(d[3]),"+f"(d[4]),"+f"(d[5]),"+f"(d[6]),"+f"(d[7])
    : "r"(alo), "r"(ahi), "r"(blo), "r"(bhi), "r"(sd), "n"(TA), "n"(TB)); }
};
template<> struct WG<32> { template<int TA, int TB> static __device__ __forceinline__ void ss(float* d, uint32_t alo, uint32_t ahi, uint32_t blo, uint32_t bhi, int sd) {
  asm volatile("{ .reg .pred p; .reg .b64 da, db; mov.b64 da, {%16,%17}; mov.b64 db, {%18,%19}; setp.ne.b32 p, %20, 0;\n"
    "wgmma.mma_async.sync.aligned.m64n32k16.f32.bf16.bf16 {%0,%1,%2,%3,%4,%5,%6,%7,%8,%9,%10,%11,%12,%13,%14,%15}, da, db, p, 1, 1, %21, %22; }"
    : "+f"(d[0]),"+f"(d[1]),"+f"(d[2]),"+f"(d[3]),"+f"(d[4]),"+f"(d[5]),"+f"(d[6]),"+f"(d[7]),"+f"(d[8]),"+f"(d[9]),"+f"(d[10]),"+f"(d[11]),"+f"(d[12]),"+f"(d[13]),"+f"(d[14]),"+f"(d[15])
    : "r"(alo), "r"(ahi), "r"(blo), "r"(bhi), "r"(sd), "n"(TA), "n"(TB)); }
};
template<> struct WG<48> { template<int TA, int TB> static __device__ __forceinline__ void ss(float* d, uint32_t alo, uint32_t ahi, uint32_t blo, uint32_t bhi, int sd) {
  asm volatile("{ .reg .pred p; .reg .b64 da, db; mov.b64 da, {%24,%25}; mov.b64 db, {%26,%27}; setp.ne.b32 p, %28, 0;\n"
    "wgmma.mma_async.sync.aligned.m64n48k16.f32.bf16.bf16 {%0,%1,%2,%3,%4,%5,%6,%7,%8,%9,%10,%11,%12,%13,%14,%15,%16,%17,%18,%19,%20,%21,%22,%23}, da, db, p, 1, 1, %29, %30; }"
    : "+f"(d[0]),"+f"(d[1]),"+f"(d[2]),"+f"(d[3]),"+f"(d[4]),"+f"(d[5]),"+f"(d[6]),"+f"(d[7]),"+f"(d[8]),"+f"(d[9]),"+f"(d[10]),"+f"(d[11]),"+f"(d[12]),"+f"(d[13]),"+f"(d[14]),"+f"(d[15]),"+f"(d[16]),"+f"(d[17]),"+f"(d[18]),"+f"(d[19]),"+f"(d[20]),"+f"(d[21]),"+f"(d[22]),"+f"(d[23])
    : "r"(alo), "r"(ahi), "r"(blo), "r"(bhi), "r"(sd), "n"(TA), "n"(TB)); }
};
template<> struct WG<64> { template<int TA, int TB> static __device__ __forceinline__ void ss(float* d, uint32_t alo, uint32_t ahi, uint32_t blo, uint32_t bhi, int sd) {
  asm volatile("{ .reg .pred p; .reg .b64 da, db; mov.b64 da, {%32,%33}; mov.b64 db, {%34,%35}; setp.ne.b32 p, %36, 0;\n"
    "wgmma.mma_async.sync.aligned.m64n64k16.f32.bf16.bf16 {%0,%1,%2,%3,%4,%5,%6,%7,%8,%9,%10,%11,%12,%13,%14,%15,%16,%17,%18,%19,%20,%21,%22,%23,%24,%25,%26,%27,%28,%29,%30,%31}, da, db, p, 1, 1, %37, %38; }"
    : "+f"(d[0]),"+f"(d[1]),"+f"(d[2]),"+f"(d[3]),"+f"(d[4]),"+f"(d[5]),"+f"(d[6]),"+f"(d[7]),"+f"(d[8]),"+f"(d[9]),"+f"(d[10]),"+f"(d[11]),"+f"(d[12]),"+f"(d[13]),"+f"(d[14]),"+f"(d[15]),"+f"(d[16]),"+f"(d[17]),"+f"(d[18]),"+f"(d[19]),"+f"(d[20]),"+f"(d[21]),"+f"(d[22]),"+f"(d[23]),"+f"(d[24]),"+f"(d[25]),"+f"(d[26]),"+f"(d[27]),"+f"(d[28]),"+f"(d[29]),"+f"(d[30]),"+f"(d[31])
    : "r"(alo), "r"(ahi), "r"(blo), "r"(bhi), "r"(sd), "n"(TA), "n"(TB)); }
};
template<> struct WG<80> { template<int TA, int TB> static __device__ __forceinline__ void ss(float* d, uint32_t alo, uint32_t ahi, uint32_t blo, uint32_t bhi, int sd) {
  asm volatile("{ .reg .pred p; .reg .b64 da, db; mov.b64 da, {%40,%41}; mov.b64 db, {%42,%43}; setp.ne.b32 p, %44, 0;\n"
    "wgmma.mma_async.sync.aligned.m64n80k16.f32.bf16.bf16 {%0,%1,%2,%3,%4,%5,%6,%7,%8,%9,%10,%11,%12,%13,%14,%15,%16,%17,%18,%19,%20,%21,%22,%23,%24,%25,%26,%27,%28,%29,%30,%31,%32,%33,%34,%35,%36,%37,%38,%39}, da, db, p, 1, 1, %45, %46; }"
    : "+f"(d[0]),"+f"(d[1]),"+f"(d[2]),"+f"(d[3]),"+f"(d[4]),"+f"(d[5]),"+f"(d[6]),"+f"(d[7]),"+f"(d[8]),"+f"(d[9]),"+f"(d[10]),"+f"(d[11]),"+f"(d[12]),"+f"(d[13]),"+f"(d[14]),"+f"(d[15]),"+f"(d[16]),"+f"(d[17]),"+f"(d[18]),"+f"(d[19]),"+f"(d[20]),"+f"(d[21]),"+f"(d[22]),"+f"(d[23]),"+f"(d[24]),"+f"(d[25]),"+f"(d[26]),"+f"(d[27]),"+f"(d[28]),"+f"(d[29]),"+f"(d[30]),"+f"(d[31]),"+f"(d[32]),"+f"(d[33]),"+f"(d[34]),"+f"(d[35]),"+f"(d[36]),"+f"(d[37]),"+f"(d[38]),"+f"(d[39])
    : "r"(alo), "r"(ahi), "r"(blo), "r"(bhi), "r"(sd), "n"(TA), "n"(TB)); }
};
template<> struct WG<96> { template<int TA, int TB> static __device__ __forceinline__ void ss(float* d, uint32_t alo, uint32_t ahi, uint32_t blo, uint32_t bhi, int sd) {
  asm volatile("{ .reg .pred p; .reg .b64 da, db; mov.b64 da, {%48,%49}; mov.b64 db, {%50,%51}; setp.ne.b32 p, %52, 0;\n"
    "wgmma.mma_async.sync.aligned.m64n96k16.f32.bf16.bf16 {%0,%1,%2,%3,%4,%5,%6,%7,%8,%9,%10,%11,%12,%13,%14,%15,%16,%17,%18,%19,%20,%21,%22,%23,%24,%25,%26,%27,%28,%29,%30,%31,%32,%33,%34,%35,%36,%37,%38,%39,%40,%41,%42,%43,%44,%45,%46,%47}, da, db, p, 1, 1, %53, %54; }"
    : "+f"(d[0]),"+f"(d[1]),"+f"(d[2]),"+f"(d[3]),"+f"(d[4]),"+f"(d[5]),"+f"(d[6]),"+f"(d[7]),"+f"(d[8]),"+f"(d[9]),"+f"(d[10]),"+f"(d[11]),"+f"(d[12]),"+f"(d[13]),"+f"(d[14]),"+f"(d[15]),"+f"(d[16]),"+f"(d[17]),"+f"(d[18]),"+f"(d[19]),"+f"(d[20]),"+f"(d[21]),"+f"(d[22]),"+f"(d[23]),"+f"(d[24]),"+f"(d[25]),"+f"(d[26]),"+f"(d[27]),"+f"(d[28]),"+f"(d[29]),"+f"(d[30]),"+f"(d[31]),"+f"(d[32]),"+f"(d[33]),"+f"(d[34]),"+f"(d[35]),"+f"(d[36]),"+f"(d[37]),"+f"(d[38]),"+f"(d[39]),"+f"(d[40]),"+f"(d[41]),"+f"(d[42]),"+f"(d[43]),"+f"(d[44]),"+f"(d[45]),"+f"(d[46]),"+f"(d[47])
    : "r"(alo), "r"(ahi), "r"(blo), "r"(bhi), "r"(sd), "n"(TA), "n"(TB)); }
};
template<> struct WG<112> { template<int TA, int TB> static __device__ __forceinline__ void ss(float* d, uint32_t alo, uint32_t ahi, uint32_t blo, uint32_t bhi, int sd) {
  asm volatile("{ .reg .pred p; .reg .b64 da, db; mov.b64 da, {%56,%57}; mov.b64 db, {%58,%59}; setp.ne.b32 p, %60, 0;\n"
    "wgmma.mma_async.sync.aligned.m64n112k16.f32.bf16.bf16 {%0,%1,%2,%3,%4,%5,%6,%7,%8,%9,%10,%11,%12,%13,%14,%15,%16,%17,%18,%19,%20,%21,%22,%23,%24,%25,%26,%27,%28,%29,%30,%31,%32,%33,%34,%35,%36,%37,%38,%39,%40,%41,%42,%43,%44,%45,%46,%47,%48,%49,%50,%51,%52,%53,%54,%55}, da, db, p, 1, 1, %61, %62; }"
    : "+f"(d[0]),"+f"(d[1]),"+f"(d[2]),"+f"(d[3]),"+f"(d[4]),"+f"(d[5]),"+f"(d[6]),"+f"(d[7]),"+f"(d[8]),"+f"(d[9]),"+f"(d[10]),"+f"(d[11]),"+f"(d[12]),"+f"(d[13]),"+f"(d[14]),"+f"(d[15]),"+f"(d[16]),"+f"(d[17]),"+f"(d[18]),"+f"(d[19]),"+f"(d[20]),"+f"(d[21]),"+f"(d[22]),"+f"(d[23]),"+f"(d[24]),"+f"(d[25]),"+f"(d[26]),"+f"(d[27]),"+f"(d[28]),"+f"(d[29]),"+f"(d[30]),"+f"(d[31]),"+f"(d[32]),"+f"(d[33]),"+f"(d[34]),"+f"(d[35]),"+f"(d[36]),"+f"(d[37]),"+f"(d[38]),"+f"(d[39]),"+f"(d[40]),"+f"(d[41]),"+f"(d[42]),"+f"(d[43]),"+f"(d[44]),"+f"(d[45]),"+f"(d[46]),"+f"(d[47]),"+f"(d[48]),"+f"(d[49]),"+f"(d[50]),"+f"(d[51]),"+f"(d[52]),"+f"(d[53]),"+f"(d[54]),"+f"(d[55])
    : "r"(alo), "r"(ahi), "r"(blo), "r"(bhi), "r"(sd), "n"(TA), "n"(TB)); }
};
template<> struct WG<128> { template<int TA, int TB> static __device__ __forceinline__ void ss(float* d, uint32_t alo, uint32_t ahi, uint32_t blo, uint32_t bhi, int sd) {
  asm volatile("{ .reg .pred p; .reg .b64 da, db; mov.b64 da, {%64,%65}; mov.b64 db, {%66,%67}; setp.ne.b32 p, %68, 0;\n"
    "wgmma.mma_async.sync.aligned.m64n128k16.f32.bf16.bf16 {%0,%1,%2,%3,%4,%5,%6,%7,%8,%9,%10,%11,%12,%13,%14,%15,%16,%17,%18,%19,%20,%21,%22,%23,%24,%25,%26,%27,%28,%29,%30,%31,%32,%33,%34,%35,%36,%37,%38,%39,%40,%41,%42,%43,%44,%45,%46,%47,%48,%49,%50,%51,%52,%53,%54,%55,%56,%57,%58,%59,%60,%61,%62,%63}, da, db, p, 1, 1, %69, %70; }"
    : "+f"(d[0]),"+f"(d[1]),"+f"(d[2]),"+f"(d[3]),"+f"(d[4]),"+f"(d[5]),"+f"(d[6]),"+f"(d[7]),"+f"(d[8]),"+f"(d[9]),"+f"(d[10]),"+f"(d[11]),"+f"(d[12]),"+f"(d[13]),"+f"(d[14]),"+f"(d[15]),"+f"(d[16]),"+f"(d[17]),"+f"(d[18]),"+f"(d[19]),"+f"(d[20]),"+f"(d[21]),"+f"(d[22]),"+f"(d[23]),"+f"(d[24]),"+f"(d[25]),"+f"(d[26]),"+f"(d[27]),"+f"(d[28]),"+f"(d[29]),"+f"(d[30]),"+f"(d[31]),"+f"(d[32]),"+f"(d[33]),"+f"(d[34]),"+f"(d[35]),"+f"(d[36]),"+f"(d[37]),"+f"(d[38]),"+f"(d[39]),"+f"(d[40]),"+f"(d[41]),"+f"(d[42]),"+f"(d[43]),"+f"(d[44]),"+f"(d[45]),"+f"(d[46]),"+f"(d[47]),"+f"(d[48]),"+f"(d[49]),"+f"(d[50]),"+f"(d[51]),"+f"(d[52]),"+f"(d[53]),"+f"(d[54]),"+f"(d[55]),"+f"(d[56]),"+f"(d[57]),"+f"(d[58]),"+f"(d[59]),"+f"(d[60]),"+f"(d[61]),"+f"(d[62]),"+f"(d[63])
    : "r"(alo), "r"(ahi), "r"(blo), "r"(bhi), "r"(sd), "n"(TA), "n"(TB)); }
  template<int TB> static __device__ __forceinline__ void rs(float* d, uint32_t a0, uint32_t a1, uint32_t a2, uint32_t a3, uint32_t blo, uint32_t bhi, int sd) {
  asm volatile("{ .reg .pred p; .reg .b64 db; mov.b64 db, {%68,%69}; setp.ne.b32 p, %71, 0;\n"
    "wgmma.mma_async.sync.aligned.m64n128k16.f32.bf16.bf16 {%0,%1,%2,%3,%4,%5,%6,%7,%8,%9,%10,%11,%12,%13,%14,%15,%16,%17,%18,%19,%20,%21,%22,%23,%24,%25,%26,%27,%28,%29,%30,%31,%32,%33,%34,%35,%36,%37,%38,%39,%40,%41,%42,%43,%44,%45,%46,%47,%48,%49,%50,%51,%52,%53,%54,%55,%56,%57,%58,%59,%60,%61,%62,%63}, {%64,%65,%66,%67}, db, p, 1, 1, %70; }"
    : "+f"(d[0]),"+f"(d[1]),"+f"(d[2]),"+f"(d[3]),"+f"(d[4]),"+f"(d[5]),"+f"(d[6]),"+f"(d[7]),"+f"(d[8]),"+f"(d[9]),"+f"(d[10]),"+f"(d[11]),"+f"(d[12]),"+f"(d[13]),"+f"(d[14]),"+f"(d[15]),"+f"(d[16]),"+f"(d[17]),"+f"(d[18]),"+f"(d[19]),"+f"(d[20]),"+f"(d[21]),"+f"(d[22]),"+f"(d[23]),"+f"(d[24]),"+f"(d[25]),"+f"(d[26]),"+f"(d[27]),"+f"(d[28]),"+f"(d[29]),"+f"(d[30]),"+f"(d[31]),"+f"(d[32]),"+f"(d[33]),"+f"(d[34]),"+f"(d[35]),"+f"(d[36]),"+f"(d[37]),"+f"(d[38]),"+f"(d[39]),"+f"(d[40]),"+f"(d[41]),"+f"(d[42]),"+f"(d[43]),"+f"(d[44]),"+f"(d[45]),"+f"(d[46]),"+f"(d[47]),"+f"(d[48]),"+f"(d[49]),"+f"(d[50]),"+f"(d[51]),"+f"(d[52]),"+f"(d[53]),"+f"(d[54]),"+f"(d[55]),"+f"(d[56]),"+f"(d[57]),"+f"(d[58]),"+f"(d[59]),"+f"(d[60]),"+f"(d[61]),"+f"(d[62]),"+f"(d[63])
    : "r"(a0), "r"(a1), "r"(a2), "r"(a3), "r"(blo), "r"(bhi), "n"(TB), "r"(sd)); }
};
template<> struct WG<144> { template<int TA, int TB> static __device__ __forceinline__ void ss(float* d, uint32_t alo, uint32_t ahi, uint32_t blo, uint32_t bhi, int sd) {
  asm volatile("{ .reg .pred p; .reg .b64 da, db; mov.b64 da, {%72,%73}; mov.b64 db, {%74,%75}; setp.ne.b32 p, %76, 0;\n"
    "wgmma.mma_async.sync.aligned.m64n144k16.f32.bf16.bf16 {%0,%1,%2,%3,%4,%5,%6,%7,%8,%9,%10,%11,%12,%13,%14,%15,%16,%17,%18,%19,%20,%21,%22,%23,%24,%25,%26,%27,%28,%29,%30,%31,%32,%33,%34,%35,%36,%37,%38,%39,%40,%41,%42,%43,%44,%45,%46,%47,%48,%49,%50,%51,%52,%53,%54,%55,%56,%57,%58,%59,%60,%61,%62,%63,%64,%65,%66,%67,%68,%69,%70,%71}, da, db, p, 1, 1, %77, %78; }"
    : "+f"(d[0]),"+f"(d[1]),"+f"(d[2]),"+f"(d[3]),"+f"(d[4]),"+f"(d[5]),"+f"(d[6]),"+f"(d[7]),"+f"(d[8]),"+f"(d[9]),"+f"(d[10]),"+f"(d[11]),"+f"(d[12]),"+f"(d[13]),"+f"(d[14]),"+f"(d[15]),"+f"(d[16]),"+f"(d[17]),"+f"(d[18]),"+f"(d[19]),"+f"(d[20]),"+f"(d[21]),"+f"(d[22]),"+f"(d[23]),"+f"(d[24]),"+f"(d[25]),"+f"(d[26]),"+f"(d[27]),"+f"(d[28]),"+f"(d[29]),"+f"(d[30]),"+f"(d[31]),"+f"(d[32]),"+f"(d[33]),"+f"(d[34]),"+f"(d[35]),"+f"(d[36]),"+f"(d[37]),"+f"(d[38]),"+f"(d[39]),"+f"(d[40]),"+f"(d[41]),"+f"(d[42]),"+f"(d[43]),"+f"(d[44]),"+f"(d[45]),"+f"(d[46]),"+f"(d[47]),"+f"(d[48]),"+f"(d[49]),"+f"(d[50]),"+f"(d[51]),"+f"(d[52]),"+f"(d[53]),"+f"(d[54]),"+f"(d[55]),"+f"(d[56]),"+f"(d[57]),"+f"(d[58]),"+f"(d[59]),"+f"(d[60]),"+f"(d[61]),"+f"(d[62]),"+f"(d[63]),"+f"(d[64]),"+f"(d[65]),"+f"(d[66]),"+f"(d[67]),"+f"(d[68]),"+f"(d[69]),"+f"(d[70]),"+f"(d[71])
    : "r"(alo), "r"(ahi), "r"(blo), "r"(bhi), "r"(sd), "n"(TA), "n"(TB)); }
};
template<> struct WG<160> { template<int TA, int TB> static __device__ __forceinline__ void ss(float* d, uint32_t alo, uint32_t ahi, uint32_t blo, uint32_t bhi, int sd) {
  asm volatile("{ .reg .pred p; .reg .b64 da, db; mov.b64 da, {%80,%81}; mov.b64 db, {%82,%83}; setp.ne.b32 p, %84, 0;\n"
    "wgmma.mma_async.sync.aligned.m64n160k16.f32.bf16.bf16 {%0,%1,%2,%3,%4,%5,%6,%7,%8,%9,%10,%11,%12,%13,%14,%15,%16,%17,%18,%19,%20,%21,%22,%23,%24,%25,%26,%27,%28,%29,%30,%31,%32,%33,%34,%35,%36,%37,%38,%39,%40,%41,%42,%43,%44,%45,%46,%47,%48,%49,%50,%51,%52,%53,%54,%55,%56,%57,%58,%59,%60,%61,%62,%63,%64,%65,%66,%67,%68,%69,%70,%71,%72,%73,%74,%75,%76,%77,%78,%79}, da, db, p, 1, 1, %85, %86; }"
    : "+f"(d[0]),"+f"(d[1]),"+f"(d[2]),"+f"(d[3]),"+f"(d[4]),"+f"(d[5]),"+f"(d[6]),"+f"(d[7]),"+f"(d[8]),"+f"(d[9]),"+f"(d[10]),"+f"(d[11]),"+f"(d[12]),"+f"(d[13]),"+f"(d[14]),"+f"(d[15]),"+f"(d[16]),"+f"(d[17]),"+f"(d[18]),"+f"(d[19]),"+f"(d[20]),"+f"(d[21]),"+f"(d[22]),"+f"(d[23]),"+f"(d[24]),"+f"(d[25]),"+f"(d[26]),"+f"(d[27]),"+f"(d[28]),"+f"(d[29]),"+f"(d[30]),"+f"(d[31]),"+f"(d[32]),"+f"(d[33]),"+f"(d[34]),"+f"(d[35]),"+f"(d[36]),"+f"(d[37]),"+f"(d[38]),"+f"(d[39]),"+f"(d[40]),"+f"(d[41]),"+f"(d[42]),"+f"(d[43]),"+f"(d[44]),"+f"(d[45]),"+f"(d[46]),"+f"(d[47]),"+f"(d[48]),"+f"(d[49]),"+f"(d[50]),"+f"(d[51]),"+f"(d[52]),"+f"(d[53]),"+f"(d[54]),"+f"(d[55]),"+f"(d[56]),"+f"(d[57]),"+f"(d[58]),"+f"(d[59]),"+f"(d[60]),"+f"(d[61]),"+f"(d[62]),"+f"(d[63]),"+f"(d[64]),"+f"(d[65]),"+f"(d[66]),"+f"(d[67]),"+f"(d[68]),"+f"(d[69]),"+f"(d[70]),"+f"(d[71]),"+f"(d[72]),"+f"(d[73]),"+f"(d[74]),"+f"(d[75]),"+f"(d[76]),"+f"(d[77]),"+f"(d[78]),"+f"(d[79])
    : "r"(alo), "r"(ahi), "r"(blo), "r"(bhi), "r"(sd), "n"(TA), "n"(TB)); }
  template<int TB> static __device__ __forceinline__ void rs(float* d, uint32_t a0, uint32_t a1, uint32_t a2, uint32_t a3, uint32_t blo, uint32_t bhi, int sd) {
  asm volatile("{ .reg .pred p; .reg .b64 db; mov.b64 db, {%84,%85}; setp.ne.b32 p, %87, 0;\n"
    "wgmma.mma_async.sync.aligned.m64n160k16.f32.bf16.bf16 {%0,%1,%2,%3,%4,%5,%6,%7,%8,%9,%10,%11,%12,%13,%14,%15,%16,%17,%18,%19,%20,%21,%22,%23,%24,%25,%26,%27,%28,%29,%30,%31,%32,%33,%34,%35,%36,%37,%38,%39,%40,%41,%42,%43,%44,%45,%46,%47,%48,%49,%50,%51,%52,%53,%54,%55,%56,%57,%58,%59,%60,%61,%62,%63,%64,%65,%66,%67,%68,%69,%70,%71,%72,%73,%74,%75,%76,%77,%78,%79}, {%80,%81,%82,%83}, db, p, 1, 1, %86; }"
    : "+f"(d[0]),"+f"(d[1]),"+f"(d[2]),"+f"(d[3]),"+f"(d[4]),"+f"(d[5]),"+f"(d[6]),"+f"(d[7]),"+f"(d[8]),"+f"(d[9]),"+f"(d[10]),"+f"(d[11]),"+f"(d[12]),"+f"(d[13]),"+f"(d[14]),"+f"(d[15]),"+f"(d[16]),"+f"(d[17]),"+f"(d[18]),"+f"(d[19]),"+f"(d[20]),"+f"(d[21]),"+f"(d[22]),"+f"(d[23]),"+f"(d[24]),"+f"(d[25]),"+f"(d[26]),"+f"(d[27]),"+f"(d[28]),"+f"(d[29]),"+f"(d[30]),"+f"(d[31]),"+f"(d[32]),"+f"(d[33]),"+f"(d[34]),"+f"(d[35]),"+f"(d[36]),"+f"(d[37]),"+f"(d[38]),"+f"(d[39]),"+f"(d[40]),"+f"(d[41]),"+f"(d[42]),"+f"(d[43]),"+f"(d[44]),"+f"(d[45]),"+f"(d[46]),"+f"(d[47]),"+f"(d[48]),"+f"(d[49]),"+f"(d[50]),"+f"(d[51]),"+f"(d[52]),"+f"(d[53]),"+f"(d[54]),"+f"(d[55]),"+f"(d[56]),"+f"(d[57]),"+f"(d[58]),"+f"(d[59]),"+f"(d[60]),"+f"(d[61]),"+f"(d[62]),"+f"(d[63]),"+f"(d[64]),"+f"(d[65]),"+f"(d[66]),"+f"(d[67]),"+f"(d[68]),"+f"(d[69]),"+f"(d[70]),"+f"(d[71]),"+f"(d[72]),"+f"(d[73]),"+f"(d[74]),"+f"(d[75]),"+f"(d[76]),"+f"(d[77]),"+f"(d[78]),"+f"(d[79])
    : "r"(a0), "r"(a1), "r"(a2), "r"(a3), "r"(blo), "r"(bhi), "n"(TB), "r"(sd)); }
};
template<> struct WG<176> { template<int TA, int TB> static __device__ __forceinline__ void ss(float* d, uint32_t alo, uint32_t ahi, uint32_t blo, uint32_t bhi, int sd) {
  asm volatile("{ .reg .pred p; .reg .b64 da, db; mov.b64 da, {%88,%89}; mov.b64 db, {%90,%91}; setp.ne.b32 p, %92, 0;\n"
    "wgmma.mma_async.sync.aligned.m64n176k16.f32.bf16.bf16 {%0,%1,%2,%3,%4,%5,%6,%7,%8,%9,%10,%11,%12,%13,%14,%15,%16,%17,%18,%19,%20,%21,%22,%23,%24,%25,%26,%27,%28,%29,%30,%31,%32,%33,%34,%35,%36,%37,%38,%39,%40,%41,%42,%43,%44,%45,%46,%47,%48,%49,%50,%51,%52,%53,%54,%55,%56,%57,%58,%59,%60,%61,%62,%63,%64,%65,%66,%67,%68,%69,%70,%71,%72,%73,%74,%75,%76,%77,%78,%79,%80,%81,%82,%83,%84,%85,%86,%87}, da, db, p, 1, 1, %93, %94; }"
    : "+f"(d[0]),"+f"(d[1]),"+f"(d[2]),"+f"(d[3]),"+f"(d[4]),"+f"(d[5]),"+f"(d[6]),"+f"(d[7]),"+f"(d[8]),"+f"(d[9]),"+f"(d[10]),"+f"(d[11]),"+f"(d[12]),"+f"(d[13]),"+f"(d[14]),"+f"(d[15]),"+f"(d[16]),"+f"(d[17]),"+f"(d[18]),"+f"(d[19]),"+f"(d[20]),"+f"(d[21]),"+f"(d[22]),"+f"(d[23]),"+f"(d[24]),"+f"(d[25]),"+f"(d[26]),"+f"(d[27]),"+f"(d[28]),"+f"(d[29]),"+f"(d[30]),"+f"(d[31]),"+f"(d[32]),"+f"(d[33]),"+f"(d[34]),"+f"(d[35]),"+f"(d[36]),"+f"(d[37]),"+f"(d[38]),"+f"(d[39]),"+f"(d[40]),"+f"(d[41]),"+f"(d[42]),"+f"(d[43]),"+f"(d[44]),"+f"(d[45]),"+f"(d[46]),"+f"(d[47]),"+f"(d[48]),"+f"(d[49]),"+f"(d[50]),"+f"(d[51]),"+f"(d[52]),"+f"(d[53]),"+f"(d[54]),"+f"(d[55]),"+f"(d[56]),"+f"(d[57]),"+f"(d[58]),"+f"(d[59]),"+f"(d[60]),"+f"(d[61]),"+f"(d[62]),"+f"(d[63]),"+f"(d[64]),"+f"(d[65]),"+f"(d[66]),"+f"(d[67]),"+f"(d[68]),"+f"(d[69]),"+f"(d[70]),"+f"(d[71]),"+f"(d[72]),"+f"(d[73]),"+f"(d[74]),"+f"(d[75]),"+f"(d[76]),"+f"(d[77]),"+f"(d[78]),"+f"(d[79]),"+f"(d[80]),"+f"(d[81]),"+f"(d[82]),"+f"(d[83]),"+f"(d[84]),"+f"(d[85]),"+f"(d[86]),"+f"(d[87])
    : "r"(alo), "r"(ahi), "r"(blo), "r"(bhi), "r"(sd), "n"(TA), "n"(TB)); }
};
template<> struct WG<192> { template<int TA, int TB> static __device__ __forceinline__ void ss(float* d, uint32_t alo, uint32_t ahi, uint32_t blo, uint32_t bhi, int sd) {
  asm volatile("{ .reg .pred p; .reg .b64 da, db; mov.b64 da, {%96,%97}; mov.b64 db, {%98,%99}; setp.ne.b32 p, %100, 0;\n"
    "wgmma.mma_async.sync.aligned.m64n192k16.f32.bf16.bf16 {%0,%1,%2,%3,%4,%5,%6,%7,%8,%9,%10,%11,%12,%13,%14,%15,%16,%17,%18,%19,%20,%21,%22,%23,%24,%25,%26,%27,%28,%29,%30,%31,%32,%33,%34,%35,%36,%37,%38,%39,%40,%41,%42,%43,%44,%45,%46,%47,%48,%49,%50,%51,%52,%53,%54,%55,%56,%57,%58,%59,%60,%61,%62,%63,%64,%65,%66,%67,%68,%69,%70,%71,%72,%73,%74,%75,%76,%77,%78,%79,%80,%81,%82,%83,%84,%85,%86,%87,%88,%89,%90,%91,%92,%93,%94,%95}, da, db, p, 1, 1, %101, %102; }"
    : "+f"(d[0]),"+f"(d[1]),"+f"(d[2]),"+f"(d[3]),"+f"(d[4]),"+f"(d[5]),"+f"(d[6]),"+f"(d[7]),"+f"(d[8]),"+f"(d[9]),"+f"(d[10]),"+f"(d[11]),"+f"(d[12]),"+f"(d[13]),"+f"(d[14]),"+f"(d[15]),"+f"(d[16]),"+f"(d[17]),"+f"(d[18]),"+f"(d[19]),"+f"(d[20]),"+f"(d[21]),"+f"(d[22]),"+f"(d[23]),"+f"(d[24]),"+f"(d[25]),"+f"(d[26]),"+f"(d[27]),"+f"(d[28]),"+f"(d[29]),"+f"(d[30]),"+f"(d[31]),"+f"(d[32]),"+f"(d[33]),"+f"(d[34]),"+f"(d[35]),"+f"(d[36]),"+f"(d[37]),"+f"(d[38]),"+f"(d[39]),"+f"(d[40]),"+f"(d[41]),"+f"(d[42]),"+f"(d[43]),"+f"(d[44]),"+f"(d[45]),"+f"(d[46]),"+f"(d[47]),"+f"(d[48]),"+f"(d[49]),"+f"(d[50]),"+f"(d[51]),"+f"(d[52]),"+f"(d[53]),"+f"(d[54]),"+f"(d[55]),"+f"(d[56]),"+f"(d[57]),"+f"(d[58]),"+f"(d[59]),"+f"(d[60]),"+f"(d[61]),"+f"(d[62]),"+f"(d[63]),"+f"(d[64]),"+f"(d[65]),"+f"(d[66]),"+f"(d[67]),"+f"(d[68]),"+f"(d[69]),"+f"(d[70]),"+f"(d[71]),"+f"(d[72]),"+f"(d[73]),"+f"(d[74]),"+f"(d[75]),"+f"(d[76]),"+f"(d[77]),"+f"(d[78]),"+f"(d[79]),"+f"(d[80]),"+f"(d[81]),"+f"(d[82]),"+f"(d[83]),"+f"(d[84]),"+f"(d[85]),"+f"(d[86]),"+f"(d[87]),"+f"(d[88]),"+f"(d[89]),"+f"(d[90]),"+f"(d[91]),"+f"(d[92]),"+f"(d[93]),"+f"(d[94]),"+f"(d[95])
    : "r"(alo), "r"(ahi), "r"(blo), "r"(bhi), "r"(sd), "n"(TA), "n"(TB)); }
};
template<> struct WG<208> { template<int TA, int TB> static __device__ __forceinline__ void ss(float* d, uint32_t alo, uint32_t ahi, uint32_t blo, uint32_t bhi, int sd) {
  asm volatile("{ .reg .pred p; .reg .b64 da, db; mov.b64 da, {%104,%105}; mov.b64 db, {%106,%107}; setp.ne.b32 p, %108, 0;\n"
    "wgmma.mma_async.sync.aligned.m64n208k16.f32.bf16.bf16 {%0,%1,%2,%3,%4,%5,%6,%7,%8,%9,%10,%11,%12,%13,%14,%15,%16,%17,%18,%19,%20,%21,%22,%23,%24,%25,%26,%27,%28,%29,%30,%31,%32,%33,%34,%35,%36,%37,%38,%39,%40,%41,%42,%43,%44,%45,%46,%47,%48,%49,%50,%51,%52,%53,%54,%55,%56,%57,%58,%59,%60,%61,%62,%63,%64,%65,%66,%67,%68,%69,%70,%71,%72,%73,%74,%75,%76,%77,%78,%79,%80,%81,%82,%83,%84,%85,%86,%87,%88,%89,%90,%91,%92,%93,%94,%95,%96,%97,%98,%99,%100,%101,%102,%103}, da, db, p, 1, 1, %109, %110; }"
    : "+f"(d[0]),"+f"(d[1]),"+f"(d[2]),"+f"(d[3]),"+f"(d[4]),"+f"(d[5]),"+f"(d[6]),"+f"(d[7]),"+f"(d[8]),"+f"(d[9]),"+f"(d[10]),"+f"(d[11]),"+f"(d[12]),"+f"(d[13]),"+f"(d[14]),"+f"(d[15]),"+f"(d[16]),"+f"(d[17]),"+f"(d[18]),"+f"(d[19]),"+f"(d[20]),"+f"(d[21]),"+f"(d[22]),"+f"(d[23]),"+f"(d[24]),"+f"(d[25]),"+f"(d[26]),"+f"(d[27]),"+f"(d[28]),"+f"(d[29]),"+f"(d[30]),"+f"(d[31]),"+f"(d[32]),"+f"(d[33]),"+f"(d[34]),"+f"(d[35]),"+f"(d[36]),"+f"(d[37]),"+f"(d[38]),"+f"(d[39]),"+f"(d[40]),"+f"(d[41]),"+f"(d[42]),"+f"(d[43]),"+f"(d[44]),"+f"(d[45]),"+f"(d[46]),"+f"(d[47]),"+f"(d[48]),"+f"(d[49]),"+f"(d[50]),"+f"(d[51]),"+f"(d[52]),"+f"(d[53]),"+f"(d[54]),"+f"(d[55]),"+f"(d[56]),"+f"(d[57]),"+f"(d[58]),"+f"(d[59]),"+f"(d[60]),"+f"(d[61]),"+f"(d[62]),"+f"(d[63]),"+f"(d[64]),"+f"(d[65]),"+f"(d[66]),"+f"(d[67]),"+f"(d[68]),"+f"(d[69]),"+f"(d[70]),"+f"(d[71]),"+f"(d[72]),"+f"(d[73]),"+f"(d[74]),"+f"(d[75]),"+f"(d[76]),"+f"(d[77]),"+f"(d[78]),"+f"(d[79]),"+f"(d[80]),"+f"(d[81]),"+f"(d[82]),"+f"(d[83]),"+f"(d[84]),"+f"(d[85]),"+f"(d[86]),"+f"(d[87]),"+f"(d[88]),"+f"(d[89]),"+f"(d[90]),"+f"(d[91]),"+f"(d[92]),"+f"(d[93]),"+f"(d[94]),"+f"(d[95]),"+f"(d[96]),"+f"(d[97]),"+f"(d[98]),"+f"(d[99]),"+f"(d[100]),"+f"(d[101]),"+f"(d[102]),"+f"(d[103])
    : "r"(alo), "r"(ahi), "r"(blo), "r"(bhi), "r"(sd), "n"(TA), "n"(TB)); }
};
template<> struct WG<224> { template<int TA, int TB> static __device__ __forceinline__ void ss(float* d, uint32_t alo, uint32_t ahi, uint32_t blo, uint32_t bhi, int sd) {
  asm volatile("{ .reg .pred p; .reg .b64 da, db; mov.b64 da, {%112,%113}; mov.b64 db, {%114,%115}; setp.ne.b32 p, %116, 0;\n"
    "wgmma.mma_async.sync.aligned.m64n224k16.f32.bf16.bf16 {%0,%1,%2,%3,%4,%5,%6,%7,%8,%9,%10,%11,%12,%13,%14,%15,%16,%17,%18,%19,%20,%21,%22,%23,%24,%25,%26,%27,%28,%29,%30,%31,%32,%33,%34,%35,%36,%37,%38,%39,%40,%41,%42,%43,%44,%45,%46,%47,%48,%49,%50,%51,%52,%53,%54,%55,%56,%57,%58,%59,%60,%61,%62,%63,%64,%65,%66,%67,%68,%69,%70,%71,%72,%73,%74,%75,%76,%77,%78,%79,%80,%81,%82,%83,%84,%85,%86,%87,%88,%89,%90,%91,%92,%93,%94,%95,%96,%97,%98,%99,%100,%101,%102,%103,%104,%105,%106,%107,%108,%109,%110,%111}, da, db, p, 1, 1, %117, %118; }"
    : "+f"(d[0]),"+f"(d[1]),"+f"(d[2]),"+f"(d[3]),"+f"(d[4]),"+f"(d[5]),"+f"(d[6]),"+f"(d[7]),"+f"(d[8]),"+f"(d[9]),"+f"(d[10]),"+f"(d[11]),"+f"(d[12]),"+f"(d[13]),"+f"(d[14]),"+f"(d[15]),"+f"(d[16]),"+f"(d[17]),"+f"(d[18]),"+f"(d[19]),"+f"(d[20]),"+f"(d[21]),"+f"(d[22]),"+f"(d[23]),"+f"(d[24]),"+f"(d[25]),"+f"(d[26]),"+f"(d[27]),"+f"(d[28]),"+f"(d[29]),"+f"(d[30]),"+f"(d[31]),"+f"(d[32]),"+f"(d[33]),"+f"(d[34]),"+f"(d[35]),"+f"(d[36]),"+f"(d[37]),"+f"(d[38]),"+f"(d[39]),"+f"(d[40]),"+f"(d[41]),"+f"(d[42]),"+f"(d[43]),"+f"(d[44]),"+f"(d[45]),"+f"(d[46]),"+f"(d[47]),"+f"(d[48]),"+f"(d[49]),"+f"(d[50]),"+f"(d[51]),"+f"(d[52]),"+f"(d[53]),"+f"(d[54]),"+f"(d[55]),"+f"(d[56]),"+f"(d[57]),"+f"(d[58]),"+f"(d[59]),"+f"(d[60]),"+f"(d[61]),"+f"(d[62]),"+f"(d[63]),"+f"(d[64]),"+f"(d[65]),"+f"(d[66]),"+f"(d[67]),"+f"(d[68]),"+f"(d[69]),"+f"(d[70]),"+f"(d[71]),"+f"(d[72]),"+f"(d[73]),"+f"(d[74]),"+f"(d[75]),"+f"(d[76]),"+f"(d[77]),"+f"(d[78]),"+f"(d[79]),"+f"(d[80]),"+f"(d[81]),"+f"(d[82]),"+f"(d[83]),"+f"(d[84]),"+f"(d[85]),"+f"(d[86]),"+f"(d[87]),"+f"(d[88]),"+f"(d[89]),"+f"(d[90]),"+f"(d[91]),"+f"(d[92]),"+f"(d[93]),"+f"(d[94]),"+f"(d[95]),"+f"(d[96]),"+f"(d[97]),"+f"(d[98]),"+f"(d[99]),"+f"(d[100]),"+f"(d[101]),"+f"(d[102]),"+f"(d[103]),"+f"(d[104]),"+f"(d[105]),"+f"(d[106]),"+f"(d[107]),"+f"(d[108]),"+f"(d[109]),"+f"(d[110]),"+f"(d[111])
    : "r"(alo), "r"(ahi), "r"(blo), "r"(bhi), "r"(sd), "n"(TA), "n"(TB)); }
};
template<> struct WG<240> { template<int TA, int TB> static __device__ __forceinline__ void ss(float* d, uint32_t alo, uint32_t ahi, uint32_t blo, uint32_t bhi, int sd) {
  asm volatile("{ .reg .pred p; .reg .b64 da, db; mov.b64 da, {%120,%121}; mov.b64 db, {%122,%123}; setp.ne.b32 p, %124, 0;\n"
    "wgmma.mma_async.sync.aligned.m64n240k16.f32.bf16.bf16 {%0,%1,%2,%3,%4,%5,%6,%7,%8,%9,%10,%11,%12,%13,%14,%15,%16,%17,%18,%19,%20,%21,%22,%23,%24,%25,%26,%27,%28,%29,%30,%31,%32,%33,%34,%35,%36,%37,%38,%39,%40,%41,%42,%43,%44,%45,%46,%47,%48,%49,%50,%51,%52,%53,%54,%55,%56,%57,%58,%59,%60,%61,%62,%63,%64,%65,%66,%67,%68,%69,%70,%71,%72,%73,%74,%75,%76,%77,%78,%79,%80,%81,%82,%83,%84,%85,%86,%87,%88,%89,%90,%91,%92,%93,%94,%95,%96,%97,%98,%99,%100,%101,%102,%103,%104,%105,%106,%107,%108,%109,%110,%111,%112,%113,%114,%115,%116,%117,%118,%119}, da, db, p, 1, 1, %125, %126; }"
    : "+f"(d[0]),"+f"(d[1]),"+f"(d[2]),"+f"(d[3]),"+f"(d[4]),"+f"(d[5]),"+f"(d[6]),"+f"(d[7]),"+f"(d[8]),"+f"(d[9]),"+f"(d[10]),"+f"(d[11]),"+f"(d[12]),"+f"(d[13]),"+f"(d[14]),"+f"(d[15]),"+f"(d[16]),"+f"(d[17]),"+f"(d[18]),"+f"(d[19]),"+f"(d[20]),"+f"(d[21]),"+f"(d[22]),"+f"(d[23]),"+f"(d[24]),"+f"(d[25]),"+f"(d[26]),"+f"(d[27]),"+f"(d[28]),"+f"(d[29]),"+f"(d[30]),"+f"(d[31]),"+f"(d[32]),"+f"(d[33]),"+f"(d[34]),"+f"(d[35]),"+f"(d[36]),"+f"(d[37]),"+f"(d[38]),"+f"(d[39]),"+f"(d[40]),"+f"(d[41]),"+f"(d[42]),"+f"(d[43]),"+f"(d[44]),"+f"(d[45]),"+f"(d[46]),"+f"(d[47]),"+f"(d[48]),"+f"(d[49]),"+f"(d[50]),"+f"(d[51]),"+f"(d[52]),"+f"(d[53]),"+f"(d[54]),"+f"(d[55]),"+f"(d[56]),"+f"(d[57]),"+f"(d[58]),"+f"(d[59]),"+f"(d[60]),"+f"(d[61]),"+f"(d[62]),"+f"(d[63]),"+f"(d[64]),"+f"(d[65]),"+f"(d[66]),"+f"(d[67]),"+f"(d[68]),"+f"(d[69]),"+f"(d[70]),"+f"(d[71]),"+f"(d[72]),"+f"(d[73]),"+f"(d[74]),"+f"(d[75]),"+f"(d[76]),"+f"(d[77]),"+f"(d[78]),"+f"(d[79]),"+f"(d[80]),"+f"(d[81]),"+f"(d[82]),"+f"(d[83]),"+f"(d[84]),"+f"(d[85]),"+f"(d[86]),"+f"(d[87]),"+f"(d[88]),"+f"(d[89]),"+f"(d[90]),"+f"(d[91]),"+f"(d[92]),"+f"(d[93]),"+f"(d[94]),"+f"(d[95]),"+f"(d[96]),"+f"(d[97]),"+f"(d[98]),"+f"(d[99]),"+f"(d[100]),"+f"(d[101]),"+f"(d[102]),"+f"(d[103]),"+f"(d[104]),"+f"(d[105]),"+f"(d[106]),"+f"(d[107]),"+f"(d[108]),"+f"(d[109]),"+f"(d[110]),"+f"(d[111]),"+f"(d[112]),"+f"(d[113]),"+f"(d[114]),"+f"(d[115]),"+f"(d[116]),"+f"(d[117]),"+f"(d[118]),"+f"(d[119])
    : "r"(alo), "r"(ahi), "r"(blo), "r"(bhi), "r"(sd), "n"(TA), "n"(TB)); }
};
template<> struct WG<256> { template<int TA, int TB> static __device__ __forceinline__ void ss(float* d, uint32_t alo, uint32_t ahi, uint32_t blo, uint32_t bhi, int sd) {
  asm volatile("{ .reg .pred p; .reg .b64 da, db; mov.b64 da, {%128,%129}; mov.b64 db, {%130,%131}; setp.ne.b32 p, %132, 0;\n"
    "wgmma.mma_async.sync.aligned.m64n256k16.f32.bf16.bf16 {%0,%1,%2,%3,%4,%5,%6,%7,%8,%9,%10,%11,%12,%13,%14,%15,%16,%17,%18,%19,%20,%21,%22,%23,%24,%25,%26,%27,%28,%29,%30,%31,%32,%33,%34,%35,%36,%37,%38,%39,%40,%41,%42,%43,%44,%45,%46,%47,%48,%49,%50,%51,%52,%53,%54,%55,%56,%57,%58,%59,%60,%61,%62,%63,%64,%65,%66,%67,%68,%69,%70,%71,%72,%73,%74,%75,%76,%77,%78,%79,%80,%81,%82,%83,%84,%85,%86,%87,%88,%89,%90,%91,%92,%93,%94,%95,%96,%97,%98,%99,%100,%101,%102,%103,%104,%105,%106,%107,%108,%109,%110,%111,%112,%113,%114,%115,%116,%117,%118,%119,%120,%121,%122,%123,%124,%125,%126,%127}, da, db, p, 1, 1, %133, %134; }"
    : "+f"(d[0]),"+f"(d[1]),"+f"(d[2]),"+f"(d[3]),"+f"(d[4]),"+f"(d[5]),"+f"(d[6]),"+f"(d[7]),"+f"(d[8]),"+f"(d[9]),"+f"(d[10]),"+f"(d[11]),"+f"(d[12]),"+f"(d[13]),"+f"(d[14]),"+f"(d[15]),"+f"(d[16]),"+f"(d[17]),"+f"(d[18]),"+f"(d[19]),"+f"(d[20]),"+f"(d[21]),"+f"(d[22]),"+f"(d[23]),"+f"(d[24]),"+f"(d[25]),"+f"(d[26]),"+f"(d[27]),"+f"(d[28]),"+f"(d[29]),"+f"(d[30]),"+f"(d[31]),"+f"(d[32]),"+f"(d[33]),"+f"(d[34]),"+f"(d[35]),"+f"(d[36]),"+f"(d[37]),"+f"(d[38]),"+f"(d[39]),"+f"(d[40]),"+f"(d[41]),"+f"(d[42]),"+f"(d[43]),"+f"(d[44]),"+f"(d[45]),"+f"(d[46]),"+f"(d[47]),"+f"(d[48]),"+f"(d[49]),"+f"(d[50]),"+f"(d[51]),"+f"(d[52]),"+f"(d[53]),"+f"(d[54]),"+f"(d[55]),"+f"(d[56]),"+f"(d[57]),"+f"(d[58]),"+f"(d[59]),"+f"(d[60]),"+f"(d[61]),"+f"(d[62]),"+f"(d[63]),"+f"(d[64]),"+f"(d[65]),"+f"(d[66]),"+f"(d[67]),"+f"(d[68]),"+f"(d[69]),"+f"(d[70]),"+f"(d[71]),"+f"(d[72]),"+f"(d[73]),"+f"(d[74]),"+f"(d[75]),"+f"(d[76]),"+f"(d[77]),"+f"(d[78]),"+f"(d[79]),"+f"(d[80]),"+f"(d[81]),"+f"(d[82]),"+f"(d[83]),"+f"(d[84]),"+f"(d[85]),"+f"(d[86]),"+f"(d[87]),"+f"(d[88]),"+f"(d[89]),"+f"(d[90]),"+f"(d[91]),"+f"(d[92]),"+f"(d[93]),"+f"(d[94]),"+f"(d[95]),"+f"(d[96]),"+f"(d[97]),"+f"(d[98]),"+f"(d[99]),"+f"(d[100]),"+f"(d[101]),"+f"(d[102]),"+f"(d[103]),"+f"(d[104]),"+f"(d[105]),"+f"(d[106]),"+f"(d[107]),"+f"(d[108]),"+f"(d[109]),"+f"(d[110]),"+f"(d[111]),"+f"(d[112]),"+f"(d[113]),"+f"(d[114]),"+f"(d[115]),"+f"(d[116]),"+f"(d[117]),"+f"(d[118]),"+f"(d[119]),"+f"(d[120]),"+f"(d[121]),"+f"(d[122]),"+f"(d[123]),"+f"(d[124]),"+f"(d[125]),"+f"(d[126]),"+f"(d[127])
    : "r"(alo), "r"(ahi), "r"(blo), "r"(bhi), "r"(sd), "n"(TA), "n"(TB)); }
  template<int TB> static __device__ __forceinline__ void rs(float* d, uint32_t a0, uint32_t a1, uint32_t a2, uint32_t a3, uint32_t blo, uint32_t bhi, int sd) {
  asm volatile("{ .reg .pred p; .reg .b64 db; mov.b64 db, {%132,%133}; setp.ne.b32 p, %135, 0;\n"
    "wgmma.mma_async.sync.aligned.m64n256k16.f32.bf16.bf16 {%0,%1,%2,%3,%4,%5,%6,%7,%8,%9,%10,%11,%12,%13,%14,%15,%16,%17,%18,%19,%20,%21,%22,%23,%24,%25,%26,%27,%28,%29,%30,%31,%32,%33,%34,%35,%36,%37,%38,%39,%40,%41,%42,%43,%44,%45,%46,%47,%48,%49,%50,%51,%52,%53,%54,%55,%56,%57,%58,%59,%60,%61,%62,%63,%64,%65,%66,%67,%68,%69,%70,%71,%72,%73,%74,%75,%76,%77,%78,%79,%80,%81,%82,%83,%84,%85,%86,%87,%88,%89,%90,%91,%92,%93,%94,%95,%96,%97,%98,%99,%100,%101,%102,%103,%104,%105,%106,%107,%108,%109,%110,%111,%112,%113,%114,%115,%116,%117,%118,%119,%120,%121,%122,%123,%124,%125,%126,%127}, {%128,%129,%130,%131}, db, p, 1, 1, %134; }"
    : "+f"(d[0]),"+f"(d[1]),"+f"(d[2]),"+f"(d[3]),"+f"(d[4]),"+f"(d[5]),"+f"(d[6]),"+f"(d[7]),"+f"(d[8]),"+f"(d[9]),"+f"(d[10]),"+f"(d[11]),"+f"(d[12]),"+f"(d[13]),"+f"(d[14]),"+f"(d[15]),"+f"(d[16]),"+f"(d[17]),"+f"(d[18]),"+f"(d[19]),"+f"(d[20]),"+f"(d[21]),"+f"(d[22]),"+f"(d[23]),"+f"(d[24]),"+f"(d[25]),"+f"(d[26]),"+f"(d[27]),"+f"(d[28]),"+f"(d[29]),"+f"(d[30]),"+f"(d[31]),"+f"(d[32]),"+f"(d[33]),"+f"(d[34]),"+f"(d[35]),"+f"(d[36]),"+f"(d[37]),"+f"(d[38]),"+f"(d[39]),"+f"(d[40]),"+f"(d[41]),"+f"(d[42]),"+f"(d[43]),"+f"(d[44]),"+f"(d[45]),"+f"(d[46]),"+f"(d[47]),"+f"(d[48]),"+f"(d[49]),"+f"(d[50]),"+f"(d[51]),"+f"(d[52]),"+f"(d[53]),"+f"(d[54]),"+f"(d[55]),"+f"(d[56]),"+f"(d[57]),"+f"(d[58]),"+f"(d[59]),"+f"(d[60]),"+f"(d[61]),"+f"(d[62]),"+f"(d[63]),"+f"(d[64]),"+f"(d[65]),"+f"(d[66]),"+f"(d[67]),"+f"(d[68]),"+f"(d[69]),"+f"(d[70]),"+f"(d[71]),"+f"(d[72]),"+f"(d[73]),"+f"(d[74]),"+f"(d[75]),"+f"(d[76]),"+f"(d[77]),"+f"(d[78]),"+f"(d[79]),"+f"(d[80]),"+f"(d[81]),"+f"(d[82]),"+f"(d[83]),"+f"(d[84]),"+f"(d[85]),"+f"(d[86]),"+f"(d[87]),"+f"(d[88]),"+f"(d[89]),"+f"(d[90]),"+f"(d[91]),"+f"(d[92]),"+f"(d[93]),"+f"(d[94]),"+f"(d[95]),"+f"(d[96]),"+f"(d[97]),"+f"(d[98]),"+f"(d[99]),"+f"(d[100]),"+f"(d[101]),"+f"(d[102]),"+f"(d[103]),"+f"(d[104]),"+f"(d[105]),"+f"(d[106]),"+f"(d[107]),"+f"(d[108]),"+f"(d[109]),"+f"(d[110]),"+f"(d[111]),"+f"(d[112]),"+f"(d[113]),"+f"(d[114]),"+f"(d[115]),"+f"(d[116]),"+f"(d[117]),"+f"(d[118]),"+f"(d[119]),"+f"(d[120]),"+f"(d[121]),"+f"(d[122]),"+f"(d[123]),"+f"(d[124]),"+f"(d[125]),"+f"(d[126]),"+f"(d[127])
    : "r"(a0), "r"(a1), "r"(a2), "r"(a3), "r"(blo), "r"(bhi), "n"(TB), "r"(sd)); }
};

template<int T> struct Conv {
    static __device__ __forceinline__ void run(float* acc, uint32_t da, uint32_t db) {
        WG<256 - 16 * T>::template ss<0, 0>(acc, da + (T >> 2) * 512 + (T & 3) * 2, dhi(1024, 1), db + T * 16, dhi(128, 0), T != 0);
        Conv<T + 1>::run(acc, da, db);
    }
};
template<> struct Conv<16> { static __device__ __forceinline__ void run(float*, uint32_t, uint32_t) {} };

template<int Q> __device__ __forceinline__ void ffn_epi(const float* g, const float* u, uint32_t* hq, char* dst, uint32_t tm, uint32_t par, float rq0, float rq1) {
    constexpr int U = Q >> 2, i = 4 * Q;
    uint32_t* o = hq + 8 * U;
    o[Q & 3] = hmul2(pack2relu(g[i], g[i + 1]), RQE == 1 ? pack2(u[i] * rq0, u[i + 1] * rq0) : pack2(u[i], u[i + 1]));
    o[4 + (Q & 3)] = hmul2(pack2relu(g[i + 2], g[i + 3]), RQE == 1 ? pack2(u[i + 2] * rq1, u[i + 3] * rq1) : pack2(u[i + 2], u[i + 3]));
    asm volatile("" : "+r"(o[Q & 3]), "+r"(o[4 + (Q & 3)]) :: "memory");
    if ((Q & 3) == 0) {
        stg_tag<0>(dst + U * 8192, o, tm, par);
        stg_tag<1>(dst + U * 8192 + 512, o + 4, tm, par);
    }
}
__device__ __forceinline__ uint32_t tagged(float x, uint32_t tag) { return (__float_as_uint(x) & ~7u) | (tag & 7u); }
__device__ __forceinline__ uint32_t split2(float x) { const float h = bfround(x); return pack2(h, x - h); }
__device__ __forceinline__ float rsqrt_(float x) { float r; asm("rsqrt.approx.ftz.f32 %0, %1;" : "=f"(r) : "f"(x)); return r; }
__device__ __forceinline__ void acc_stat(float& s, float& q, uint32_t w) { const float a = bflo(w), c = bfhi(w); s += a; q = fmaf(a, a, q); s += c; q = fmaf(c, c, q); }
template<int I, int N, typename F> __device__ __forceinline__ void static_for(F&& f) {
    if constexpr (I < N) { f(std::integral_constant<int, I>{}); static_for<I + 1, N>(f); }
}

__device__ __forceinline__ int mod_col(int i, int s) {
    const int g = 4 * i + s - 40;
    return i < 10 ? ((s & 1) ? 1280 + 1280 * (i & 1) : 640 * (i & 1)) + (i >> 1) * 128 + (s >> 1) * 64 : (g < 10 ? 1920 : 2560) + g * 64;
}
__device__ __forceinline__ uint32_t silu2(uint32_t w) {
    const float a0 = bflo(w), a1 = bfhi(w);
    return pack2(__fdividef(a0, 1.f + __expf(-a0)), __fdividef(a1, 1.f + __expf(-a1)));
}

struct Maps { CUtensorMap k, v, q, y, g1, u1, g2, u2, wd, wn, wm, out; };
struct Ptrs { const char *k, *v, *shift, *ssm, *ssmD; char *scr, *out; const char *c, *Wg, *Wu, *Wd;
};

__global__ void __cluster_dims__(2, 1, 1) __launch_bounds__(384, 1)
fused_kernel(const __grid_constant__ Ptrs P, const __grid_constant__ Maps M) {
    extern __shared__ __align__(1024) char smraw[];
    const uint32_t clk0 = clock32();
    const uint32_t sb = smem_u32(smraw);
    const int tid = threadIdx.x, b = blockIdx.x;
    #define BAR(i) (sb + BARS + 8 * (i))
    const char* pk = SBAR ? (&P.k)[tid >> 9] : P.k;
    const uint32_t rv = tid >> 3, c = (tid ^ rv) & 7, rk = rv + 2 + 2 * (rv >> 3);
    const uint32_t go = ((b >> 1) * 32 + (rv & 6) * 4 + 2 * (rv >> 3) + (rv & 1)) * 1280 + (b & 1) * 128 + c * 16, d0 = sb + st_kv(0) + rk * 128 + (((c ^ rk) & 7) << 4);
    if (SBAR) asm volatile("pmevent 1;" : "+l"(pk) : "r"(go), "r"(d0));
    if (SBAR && (go ^ d0 ^ (uint32_t)(uintptr_t)pk) == 0x80000001u) return;
    if (tid < 256 && b < 128) {
        cp16(d0, padd(pk, go));
        cp16(sb + st_kv(0) + 5120 + tid * 16, padd(P.v, go));
        sched_bar();
        if ((rv & 22) == 16)
            asm volatile("cp.async.cg.shared.global [%0], [%1], 16, %2;" :: "r"(sb + st_kv(0) + (rk - 2) * 128 + (((c ^ (rk - 2)) & 7) << 4)), "l"(padd(P.k, b < 2 ? go : go - 10240)), "r"(b < 2 ? 0 : 16) : "memory");
        if (tid < 160) cp16(sb + ST_SH + tid * 16, padd(P.shift, (tid >> 5) * 512 + (b & 1) * 512 + tid * 16));
        asm volatile("cp.async.commit_group;" ::: "memory");
    }
    const int warp = __shfl_sync(~0u, tid >> 5, 0), lane = tid & 31;
    const int rank = b & 1, cl = b >> 1;
    #define FFN_ROLE int cl_ = cl; asm volatile("pmevent 1;" : "+r"(cl_)); const int cu = cl_ - 36, cv = (cu * 37) >> 8, \
        gp_ = cl_ < 4 ? 0 : cl_ < 36 ? (cl_ - 4) & 7 : 1 + cu - 7 * cv, gi_ = cl_ < 4 ? 4 + cl_ : cl_ < 36 ? (cl_ - 4) >> 3 : 4 + cv, \
        grp = MAPM == 0 ? gp_ : MAPM == 1 ? (gp_ & 6) + (gi_ >> 2) : MAPM == 2 ? (gp_ & 6) + (gi_ & 1) : MAPM == 3 ? (gp_ & 4) + (gi_ & 3) : gi_, \
        js = MAPM == 0 ? gi_ : MAPM == 1 ? 4 * (gp_ & 1) + (gi_ & 3) : MAPM == 2 ? 4 * (gp_ & 1) + (gi_ >> 1) : MAPM == 3 ? 2 * (gp_ & 3) + (gi_ >> 2) : gp_, tile = 2 * grp + rank, dq = js & 3
    #define CNT(l, w) SC(cnt, (l) * 4096 + (w) * 4)
    uint32_t epoch = 0;

    if (b >= 128) {
        if (warp >= 10) {
            if (elect()) {
                _Pragma("unroll") for (int i = 0; i < 15; i++) mbar_init(BAR(i % 5 + i / 5 * 10) + (warp & 1) * 40, i < 5 || i >= 10 ? 1 : 4);
                asm volatile("fence.mbarrier_init.release.cluster;" ::: "memory");
                fence_async_smem();
                pf_map(&M.wm);
            }
            __syncwarp();
            asm volatile("barrier.cluster.arrive.relaxed.aligned;" ::: "memory");
            bar_arrive(0, 384);
        } else {
            epoch = ldg_late(CNT(C_Z, 6), lane);
            if (tid < 320) sts32(sb + 204800 + tid * 4, silu2(__ldg((const uint32_t*)P.c + tid)));
            fence_async_smem();
            __syncwarp();
            asm volatile("barrier.cluster.arrive.relaxed.aligned;\n barrier.cluster.wait.aligned;" ::: "memory");
            bar_sync(0, 384);
            STAMPIF(warp == 0, 7);
        }
        if (warp >= 10) {
            if (elect()) {
                wait_clock(clk0, D_SP);
                uint32_t fb = BAR(0) + (warp & 1) * 40, dst = sb + (warp & 1) * 102400, s = 0, ph = 1;
                _Pragma("unroll 1") for (int i = warp & 1; i < 15; i += 2) {
                    const int col = mod_col(i, b - 128);
                    _Pragma("unroll 1") for (int j = 0; j < 640; j += 160) {
                        mbar_wait(fb + 80, ph);
                        mbar_expect(fb, 20480);
                        tma2d(dst, &M.wm, col, j, fb);
                        fb += 8; dst += 20480;
                        if (++s == 5) { s = 0; ph ^= 1; fb -= 40; dst -= 102400; }
                    }
                }
            }
        } else if (warp == 9 && !rank) {
            epoch = (__shfl_sync(~0u, epoch, 0) >> 7) + 1;
            _Pragma("unroll 1") for (int r = 0; r < 5; r++) {
                if (lane == 0) mbar_expect(BAR(20 + r), 512);
                mbar_wait(BAR(20 + r), 0);
                uint32_t v[4];
                #pragma unroll
                for (int k = 0; k < 4; k++) asm volatile("ld.shared.b32 %0, [%1];" : "=r"(v[k]) : "r"(sb + 206336 + r * 512 + k * 128 + (lane & 16) * 4 + (lane & 3) * 16 + (lane & 12)) : "memory");
                stg_rlx128(SC(abc, (r * 64 + (b - 128) * 16 + lane) * 16), hmul2(v[2], hadd2(v[1], 0x3f803f80u)), hmul2(v[2], v[0]), hadd2(v[3], 0x3f803f80u), epoch);
                STAMP(1 + r);
            }
        } else if (warp < 8) {
            const int wg = warp >> 2;
            epoch = (__shfl_sync(~0u, epoch, 0) >> 7) + 1;
            int s = 0, ph = 0;
            _Pragma("unroll 1") for (int i = wg; i < 15; i += 2) {
                float ac5[20];
                uint32_t prev = 0;
                _Pragma("unroll 1") for (int j = 0; j < 4; j++) {
                    const int sl = wg * 5 + s;
                    mbar_wait(BAR(sl), ph);
                    wg_fence();
                    const uint32_t da = dlo(sb + sl * 20480, 16), db = dlo(sb + 204800 + j * 320, 16);
                    #pragma unroll
                    for (int ks = 0; ks < 10; ks++) WG<8>::ss<1, 0>(ac5 + 4 * (ks % 5), da + ks * 128, dhi(1024, 1), db + ks * 2, dhi(128, 0), ks >= 5 || j != 0);
                    wg_commit();
                    wg_wait<1>();
                    mbar_arrive_if(prev, lane == 0 && j);
                    prev = BAR(10 + sl);
                    if (++s == 5) { s = 0; ph ^= 1; }
                }
                wg_wait<0>();
                pin<20>(ac5);
                mbar_arrive_if(prev, lane == 0);
                const float acc[3] = {ac5[0] + ac5[4] + ac5[8] + ac5[12] + ac5[16], 0.f, ac5[2] + ac5[6] + ac5[10] + ac5[14] + ac5[18]};
                const uint32_t m0 = pack2(acc[0], __shfl_down_sync(~0u, acc[0], 4)), m1 = pack2(acc[2], __shfl_down_sync(~0u, acc[2], 4));
                if (i < 10) {
                    if ((lane & 7) == 0)
                        asm volatile("{ .reg .u32 a, m; mapa.shared::cluster.u32 a, %0, 0; mapa.shared::cluster.u32 m, %1, 0; \n"
                                     " st.async.shared::cluster.mbarrier::complete_tx::bytes.b32 [a], %2, [m]; st.async.shared::cluster.mbarrier::complete_tx::bytes.b32 [a+16], %3, [m]; }"
                                     :: "r"(sb + 206336 + (i >> 1) * 512 + rank * 256 + warp * 32 + (lane >> 3) * 4), "r"(BAR(20 + (i >> 1))), "r"(m0), "r"(m1) : "memory");
                } else if ((lane & 7) == 0) {
                    char* mp = SC(mod, ((4 * i + b - 168) * 64 + (warp & 3) * 16 + (lane >> 2)) * 4);
                    asm volatile("{ .reg .b64 x; mov.b64 x, {%1, %3}; st.relaxed.gpu.global.b64 [%0], x; mov.b64 x, {%2, %3}; st.relaxed.gpu.global.b64 [%0+32], x; }" :: "l"(mp), "r"(m0), "r"(m1), "r"(epoch) : "memory");
                }
                STAMPIF(warp == 0 && i == 12, 6); STAMPIF(warp == 0 && i == 0, 8);
            }
        }
        return;
    }

    const bool l0 = lane == 0;
    const int q = lane & 3, rr = lane >> 2;

    if (warp < 8) {
        const int wg = warp >> 2, w = warp & 3, t = tid & 127;
        if (t < 5) sts128(wg ? sb + XB + (t & 1) * XP + 4096 : sb + eslot(t), 0, 0, 0, 0);
        bar_sync(0, 384);
        asm volatile("barrier.cluster.arrive.relaxed.aligned;" ::: "memory");
        STAMPIF(warp == 0, 1);
        uint32_t dv = 0;
        if (t < 5) asm volatile("ld.global.nc.u16 %0, [%1];" : "=r"(dv) : "l"(padd(P.ssmD, (b + 128 * t) * 2)));
        FFN_ROLE;
        epoch = ldg_late(CNT(C_Z + tile, 6), lane);
        asm volatile("cp.async.wait_group 0;" ::: "memory");
        bar_sync(2, 256);
        mbar_arrive_if(BAR(B_KV), tid == 0);
        epoch = (__shfl_sync(~0u, epoch, 0) >> 7) + 1;
        asm volatile("barrier.cluster.wait.aligned;" ::: "memory");
        uint32_t g2e;
        asm("mapa.shared::cluster.u32 %0, %1, %2;" : "=r"(g2e) : "r"(BAR(B_G2E)), "r"(rank ^ (lane & 1)));
        const bool l01 = lane < 2;
        const uint32_t wre = g2e - 8 * (B_G2E - B_WE);
        {
            const uint32_t par = epoch & 1, xa = sb + XB + wg * XP, ye = ~lane & 1;
            const char* gp = SC(kvT, (b + 128 * wg) * 4096 + t * 16);
            if (wg) bar_arrive(1, 256);
            auto krow = [&](int o) { const int tk = 39 - 8 * ((lane & 7) >> 1) - o, ro = (tk & 1) + 2 * (tk >> 3) + 10 * ((tk >> 1) & 3); return sb + ro * 128 + (((ro & 7) ^ (2 * w)) << 4); };
            const int o0 = 2 * (lane >> 3) + (lane & 1);
            const int tv = 31 - 8 * ((lane & 7) >> 1) - o0, rv = (tv & 1) + 2 * (tv >> 3) + 8 * ((tv >> 1) & 3);
            uint32_t aE = krow(o0), aH = krow(8 + (o0 & 3)), aV = sb + 5120 + rv * 128 + (((rv & 7) ^ (2 * w)) << 4);
            uint32_t tdo = (rank * 64 + w * 16 + rr) * 4096 + (252 - 4 * cl + q) * 16;
            asm volatile("" : "+r"(aE), "+r"(aH), "+r"(aV), "+r"(tdo));
            _Pragma("unroll 1") for (unsigned long long steps = wg ? SEQ1 : SEQ0; steps; steps >>= 8) {
                const int r = steps & 7;
                STAMPS(0);
                if (steps & 0x40) {
                    const uint32_t so = st_kv(r);
                    const char *dst = SC(kvT, tdo + r * 524288), *hc = CNT(C_KV + 2 * r + rank, t);
                    mbar_wait(BAR(B_KV + r), 0);
                    STAMPIF(w == 1 && (r & 3) == 0, 35 + r); STAMPS(1);
                    red_if(hc, 2, t == 0 && ((EARLYH >> r) & 1));
                    uint2 sw[2]; uint32_t ke[2][6], vv[2][4], o[2][4];
                    #pragma unroll
                    for (int u = 0; u < 2; u++) {
                        sw[u] = lds64(sb + ST_SH + r * 512 + w * 128 + rr * 8 + u * 64);
                        ldsm4t(ke[u], (aE ^ (u << 4)) + so); ldsm2t(ke[u][4], ke[u][5], (aH ^ (u << 4)) + so); ldsm4t(vv[u], (aV ^ (u << 4)) + so);
                    }
                    sched_bar();
                    #pragma unroll
                    for (int u = 0; u < 2; u++) {
                        uint32_t ko[5];
                        #pragma unroll
                        for (int j = 0; j < 5; j++) ko[j] = prmt(ke[u][j], ke[u][j + 1], 0x5432);
                        #pragma unroll
                        for (int j = 0; j < 4; j++) o[u][j] = hmul2(hfma2s<0>(ke[u][j], sw[u].x, hfma2s<1>(ko[j], sw[u].x, hfma2s<0>(ke[u][j + 1], sw[u].y, hfma2s<1>(ko[j + 1], sw[u].y, 0x80008000u)))), vv[u][j]);
                        o[u][0] = (o[u][0] & ~1u) | par;
                    }
                    asm volatile("{ .reg .pred h; setp.ne.b32 h, %10, 0; pmevent 1;\n @h red.relaxed.gpu.global.add.u32 [%9], 2;\n"
                                 " st.relaxed.gpu.global.v4.b32 [%0], {%1,%2,%3,%4}; st.relaxed.gpu.global.v4.b32 [%0+32768], {%5,%6,%7,%8}; }"
                                 :: "l"(dst), "r"(o[0][0]), "r"(o[0][1]), "r"(o[0][2]), "r"(o[0][3]), "r"(o[1][0]), "r"(o[1][1]), "r"(o[1][2]), "r"(o[1][3]),
                                    "l"(hc), "r"((int)(t == 0 && !((EARLYH >> r) & 1))) : "memory");
                    mbar_arrive_if(BAR(B_TD + r), l0 && r < 3);
                    STAMPIF(w == 1 && (r & 3) == 0, r ? 3 : 45);
                    continue;
                }
                const uint32_t eb = sb + eslot(r);
                if (steps & 0x20) {
                    const int ew = (t >> 1) & 3, et = (ew + (t >> 3)) & 3, eh = (t >> 5) & 1;
                    const uint32_t ha = eb + ((t & 64) + 16 * et + 8 * eh + 2 * ew + (t & 1)) * 16;
                    const uint32_t ea = eb + (t & 64) * 128 + (2 * ew + eh) * 1024 + ((2 * et + (t & 1)) << 4);
                    mbar_wait(BAR(B_H + r), 0);
                    STAMPIF(warp == 1 && r == 0, 2); STAMPS(1);
                    uint4 hv4[4];
                    #pragma unroll
                    for (int i = 0; i < 4; i++) hv4[i] = lds128(ha + (i >> 1) * 2048 + (i & 1) * 16);
                    if (w == 0) { const uint32_t dr = __shfl_sync(~0u, dv, r); if (l0) hv4[1].x = hadd2(hv4[1].x, dr); }
                    bar_sync(5 + wg, 128);
                    #pragma unroll
                    for (int h = 0; h < 2; h++) {
                        const uint32_t* w8 = &hv4[2 * h].x;
                        #pragma unroll
                        for (int row = 0; row < ((WI & 64) ? 2 : 8); row++) {
                            uint32_t o[4];
                            #pragma unroll
                            for (int i = 0; i < 4; i++) o[i] = (row & 1) ? prmt(w8[(7 - row) / 2 + i], w8[(7 - row) / 2 + i + 1], 0x5432) : w8[(8 - row) / 2 + i];
                            sts128((ea ^ (row << 4)) + row * 128 + h * 16384, o[0], o[1], o[2], o[3]);
                        }
                    }
                    if (!(steps & 0x2000)) fence_async_smem();
                    STAMPIF(w == 0, wg ? 30 : 4);
                    continue;
                }
                float acc[128];
                mbar_wait(BAR(B_X + wg), (r >> 1) & 1); STAMPS(1);
                STAMPIF(w == 0, 10 + r);
                bar_sync(1 + wg, 256);
                GSTAMPIF(w == 0 && r == 0, 7); STAMPS(2);
                _Pragma("unroll 1") for (int rep = 0;; rep++) {
                    wg_fence();
                    Conv<0>::run(acc, dlo(eb, 16), dlo(xa, 16));
                    wg_commit();
                    if (r < 4 && !rep) bar_arrive(2 - wg, 256);
                    uint32_t t0;
                    asm volatile("ld.shared.b32 %0, [%1];" : "=r"(t0) : "r"(xa + w * 512 + (lane >> 4) * 2048 + (lane & 15) * 32 + (lane & 4) * 4) : "memory");
                    wg_wait<0>();
                    pin<128>(acc);
                    STAMPIF(w == 0, 15 + r);
                    if (!bar_or(5 + wg, 128, (t0 ^ par) & 1) || rep) break;
                    VALIF(true, 90, 1);
                    _Pragma("unroll 1") for (int h = 0; h < 2; h++) {
                        uint4 kx = {0, 0, 0, 0};
                        _Pragma("unroll 1") for (int it = 0; it < 20000; it++) {
                            ldg_rlx128_if(kx, gp + h * 2048, true);
                            if (!__any_sync(~0u, (kx.x ^ par) & 1)) break;
                        }
                        sts128(xa + t * 16 + h * 2048, kx.x, kx.y, kx.z, kx.w);
                    }
                    fence_async_smem();
                    bar_sync(5 + wg, 128);
                }
                gp += 2 * 524288;
                mbar_arrive_if(BAR(B_MD + r), t == 0 && r < 3);
                const uint32_t pw = eb + w * PP + lane * 16;
                #pragma unroll
                for (int g = 0; g < 8; g++) {
                    uint32_t o[4];
                    #pragma unroll
                    for (int l = 0; l < 4; l++) { const int i = 4 * g + l;
                        o[l] = i < 31 ? pack2(acc[4 * i] + acc[4 * i + 6], acc[4 * i + 1] + acc[4 * i + 7]) : pack2(acc[4 * i], acc[4 * i + 1]); }
                    asm volatile("stmatrix.sync.aligned.m8n8.x4.trans.shared.b16 [%0], {%1,%2,%3,%4};" :: "r"(pw + g * 512), "r"(o[0]), "r"(o[1]), "r"(o[2]), "r"(o[3]) : "memory");
                    if (g & 1) sched_bar();
                }
                if (lane < 6) sts128(pw + 4096, 0, 0, 0, 0);
                bar_sync(5 + wg, 128);
                if (YH < 0) red_if(CNT(C_Y + r, t), 1, t == 0);
                char* yp = (char*)gp + (offsetof(Scratch, yT) - 2 * 524288);
                #pragma unroll
                for (int h = 0; h < 2; h++) {
                    uint4 p[4];
                    #pragma unroll
                    for (int k = 0; k < 4; k++) p[k] = (WI & 128) && k > 0 ? p[0] : lds128(eb + (t + 128 * h) * 16 + k * (PP + 32));
                    uint32_t y[4];
                    #pragma unroll
                    for (int j = 0; j < 4; j++) y[j] = hadd2((&p[0].x)[j], hadd2((&p[1].x)[j], hadd2((&p[2].x)[j], (&p[3].x)[j])));
                    stg_rlx128(yp + h * 2048, (y[0] & ~ye) | (par & ye), y[1], y[2], y[3]);
                    if (h == YH) red_if(CNT(C_Y + r, t), 1, t == 0);
                }
                __syncwarp();
                mbar_arrive_if(BAR(B_RD + r), l0);
                mbar_arrive_remote_if(wre + 16 * (r - 1) + (lane & 4) * 2, lane < 8 && (r == 1 || r == 2));
                STAMPIF(w == 0, 20 + r);
            }
        }
        float acc1[128];
        uint4 sv[2] = {};
        const char* s2p = SC(st2, (tile * 128 + wg * 64 + w * 16 + rr) * 16);
        auto pass1 = [&](int n0, int n1, auto&& top, auto&& mid) {
            _Pragma("unroll 1") for (int n = n0; n < n1; n++) {
                top();
                const uint32_t da = dlo(sb + wg * 4096, 16) + n * 512, db = dlo(sb + WR, 4096) + (n & 3) * 1024;
                TWAIT((n & 1) ? 91 : 10 + (n >> 1), mbar_wait(BAR(B_AF) + (n >> 1) * 8, 0));
                TWAIT(50 + n, mbar_wait(BAR(B_WF) + (n & 3) * 8, (n >> 2) & 1));
                GSTAMPIF(n == 0 && warp == 0, 8);
                STAMPIF(n == 0 && warp == 4, 9);
                STAMPI(warp == 0 && !(n & 1), 50 + (n >> 1));
                wg_fence();
                WG<256>::ss<0, 1>(acc1, da, dhi(512, 2), db, dhi(1024, 1), n0 ? 1 : n);
                if (ER & 1) {
                    wg_commit();
                    wg_wait<1>();
                    mbar_arrive_remote_if(wre + ((n + 3) & 3) * 8, l01 && n > 0);
                }
                WG<256>::ss<0, 1>(acc1, da + 2, dhi(512, 2), db + 128, dhi(1024, 1), 1);
                wg_commit();
                if (!(ER & 1)) {
                    wg_wait<1>();
                    mbar_arrive_remote_if(wre + ((n + 3) & 3) * 8, l01 && n > 0);
                }
                mid(n);
            }
        };
        pass1(0, N_UT, []() {}, [](int) {});
        {
            float au[8];
            const int un = min(2 * b + wg, 239), cg = (un * 205) >> 10;
            char* up = SC(ut, ((un - 5 * cg) * 3072 + cg * 64 + w * 16 + rr) * 8);
            pass1(N_UT, N_UT + 1, [&]() {
                TWAIT(20, mbar_wait(BAR(B_UF), 0));
                const uint32_t ua = dlo(sb + UST + wg * 16384, 16), ub = dlo(sb + CS_TAB + wg * 512, 32);
                wg_fence();
                #pragma unroll
                for (int ks = 0; ks < 8; ks++) WG<8>::ss<1, 0>(au + 4 * (ks & 1), ua + ks * 128, dhi(1024, 1), ub + ks * 4, dhi(128, 0), ks >= 2);
                wg_commit();
            }, [&](int) {
                pin<8>(au);
                asm volatile("{ .reg .pred p; .reg .b64 x; setp.eq.b32 p, %5, 0; mov.b64 x, {%1, %2}; @p st.relaxed.gpu.global.b64 [%0], x; mov.b64 x, {%3, %4}; @p st.relaxed.gpu.global.b64 [%0+64], x; }"
                             :: "l"(up), "r"(tagged(au[0] + au[4], epoch)), "f"(au[1] + au[5]), "r"(tagged(au[2] + au[6], epoch)), "f"(au[3] + au[7]), "r"(q | (b >= 120)) : "memory");
                mbar_arrive_if(BAR(B_UD), l0);
                STAMPIF(warp == 0, 25);
            });
        }
        pass1(N_UT + 1, 20, []() {}, [&](int n) { ldg_rlx128_if(sv[0], s2p, n == 16); ldg_rlx128_if(sv[1], s2p + 128, n == 16); });
        _Pragma("unroll 1") for (int it = 0; it < 20000 && __any_sync(~0u, sv[0].w != epoch || sv[1].w != epoch); it++) { ldg_rlx128_if(sv[0], s2p, true); ldg_rlx128_if(sv[1], s2p + 128, true); }
        float acc2[64];
        const float rq0 = __uint_as_float(sv[0].z), rq1 = __uint_as_float(sv[1].z);
        {
            uint32_t ax[4];
            const uint32_t zm = q == 0 ? ~0u : q == 1 ? 0xffffu : 0u, sh = q ? 0x5454 : 0x5410, sl = sh + 0x2222;
            uint32_t a0 = prmt(sv[0].x, sv[0].y, sh), a1 = prmt(sv[1].x, sv[1].y, sh), a2 = prmt(sv[0].x, sv[0].y, sl), a3 = prmt(sv[1].x, sv[1].y, sl);
            TWAIT(21, mbar_wait(BAR(B_T1), 0));
            wg_wait<0>();
            mbar_arrive_remote_if(wre + 24, l01);
            asm volatile("setmaxnreg.inc.sync.aligned.u32 232;\n and.b32 %0, %4, %8; and.b32 %1, %5, %8; and.b32 %2, %6, %8; and.b32 %3, %7, %8;"
                         : "=r"(ax[0]), "=r"(ax[1]), "=r"(ax[2]), "=r"(ax[3]) : "r"(a0), "r"(a1), "r"(a2), "r"(a3), "r"(zm) : "memory");
            wg_fence();
            WG<256>::rs<1>(acc1, ax[0], ax[1], ax[2], ax[3], dlo(sb + TAB1, 0), dhi(48, 0), 1);
            WG<128>::rs<1>(acc2, ax[0], ax[1], ax[2], ax[3], dlo(sb + TAB2, 0), dhi(48, 0), 0);
            wg_commit();
        }
        char* hdst = SC(hh, (tile * 24 + js * 3) * 16384 + warp * 1024 + rr * 64 + ((q ^ (rr >> 1)) << 4));
        GSTAMPIF(warp == 0, 26);
        uint32_t hq[48];
        const uint32_t tm = (lane & 7) == (w & 1) * 4;
        auto release2 = [&](int it) {
            mbar_arrive_remote_if(wre + 8 * ((it + 3) & 3), l01 && it < 7);
            mbar_arrive_if(BAR(B_HS - 7) + 8 * it, l0 && it >= 7);
            mbar_arrive_remote_if(g2e + 8 * (it - G2R), l01 && it >= G2R && it < G2R + 6);
        };
        auto pass2 = [&](int it, auto&& epi) {
            TWAIT(70 + it, mbar_wait(BAR(B_WF) + (it & 3) * 8, ((it >> 2) & 1) ^ 1));
            STAMPI(warp == 0, 60 + it);
            const uint32_t da = dlo(sb + wg * 4096, 16) + it * 1024, db = dlo(sb + WR, 8192) + (it & 3) * 1024;
            wg_fence();
            static_for<0, 4>([&](auto KS) {
                WG<128>::ss<0, 1>(acc2, da + (KS.value >> 1) * 512 + (KS.value & 1) * 2, dhi(512, 2), db + KS.value * 128, dhi(1024, 1), 1);
                if constexpr (KS.value == 3) wg_commit();
                if constexpr (KS.value == 0 && (ER & 2)) { wg_commit(); wg_wait<1>(); if (it) release2(it); }
                epi(KS);
            });
            if (!(ER & 2)) { wg_wait<1>(); if (it) release2(it); }
        };
        constexpr int NE = ((epi_slot(15) + E0) >> 2) + 1;
        static_for<0, NE>([&](auto IT) {
            pass2(IT.value, [&](auto KS) {
                if constexpr (IT.value == 0 && KS.value == 0) pin<128>(acc1);
                static_for<0, 16>([&](auto E) {
                    if constexpr (epi_slot(E.value) == 4 * IT.value + KS.value - E0) {
                        sched_bar();
                        ffn_epi<15 - E.value>(acc1, acc1 + 64, hq, hdst, tm, epoch, rq0, rq1);
                        if constexpr ((E.value & 7) == 7) { __syncwarp(); mbar_arrive_if(BAR(B_HD + (E.value >> 3)), l0); }
                        sched_bar();
                    }
                });
            });
        });
        _Pragma("unroll 1") for (int it = NE; it < 10; it++) pass2(it, [](auto) {});
        {
            float acc[80];
            static_for<0, 3>([&](auto IT) {
                constexpr int it = IT.value;
                TWAIT(35 + it, mbar_wait(BAR(B_G2F + it), 0));
                STAMPI(warp == 0 && it == 0, 70);
                const uint32_t db = dlo(sb + G2B + it * 20480, 2048);
                #pragma unroll
                for (int i = 0; i < 16; i++) asm volatile("" : "+r"(hq[16 * it + i]) :: "memory");
                wg_fence();
                static_for<0, 4>([&](auto KS) {
                    constexpr int ks = KS.value, sl = 4 * it + ks;
                    const uint32_t* o = hq + 16 * it + 8 * (ks >> 1) + 2 * (ks & 1);
                    WG<160>::rs<1>(acc, o[0], o[4], o[1], o[5], db + (ks >> 1) * 640 + (ks & 1) * 64, dhi(512, 2), it != 0 || ks != 0);
                    if constexpr (sl == 0 || ks == 3) wg_commit();
                    if constexpr (it > 0 && ks == 0 && (ER & 4)) { wg_commit(); wg_wait<1>(); mbar_arrive_remote_if(g2e + 8 * (it ? it - 1 : 0), l01); }
                    if constexpr (sl == 0) {
                        wg_wait<1>();
                        pin<64>(acc2);
                        mbar_arrive_if(BAR(B_S0), l0);
                        static_for<(G2R > 4 ? 10 - G2R : 6), 6>([&](auto G) { mbar_arrive_remote_if(g2e + 8 * G.value, l01); });
                    }
                    if constexpr (sl < 8 / Q2) {
                        sched_bar();
                        static_for<0, Q2>([&](auto J) { ffn_epi<7 - Q2 * sl - J.value>(acc2, acc2 + 32, hq + 32, hdst + 32768, tm, epoch, rq0, rq1); });
                        if constexpr (sl == 8 / Q2 - 1) { __syncwarp(); mbar_arrive_if(BAR(B_HD + 2), l0); }
                        sched_bar();
                    }
                    if constexpr (sl == 0) wg_fence();
                });
                if (it && !(ER & 4)) {
                    wg_wait<1>();
                    mbar_arrive_remote_if(g2e + 8 * (it ? it - 1 : 0), l01);
                }
            });
            uint4 gw[5];
            mbar_wait(BAR(B_GB), 0);
            #pragma unroll
            for (int i = 0; i < 5; i++) gw[i] = lds128(sb + GBT + q * 80 + i * 16);
            const uint32_t da = dlo(sb + G2A + wg * 4096, 16), db = dlo(sb + G2B, 2048);
            _Pragma("unroll 1") for (int it = 3; it < 12 - NST; it++) {
                const int g = it >= 6 ? it - 6 : it, ga = it >= 5 ? it - 5 : it + 1;
                TWAIT(35 + it, mbar_wait(BAR(B_G2F + g), it >= 6));
                TWAIT(77 + it, mbar_wait(BAR(B_AF - 3 + it), 1));
                STAMPI(warp == 0 && (it == 3 || it == 6), 70 + (it >> 2) + 1);
                wg_fence();
                #pragma unroll
                for (int ks = 0; ks < 4; ks++) {
                    WG<160>::ss<0, 1>(acc, da + ga * 1024 + (ks >> 1) * 512 + (ks & 1) * 2, dhi(512, 2), db + g * 1280 + (ks >> 1) * 640 + (ks & 1) * 64, dhi(512, 2), 1);
                    if (ks == 3 || (ks == 0 && (ER & 4))) wg_commit();
                    if (ks == ((ER & 4) ? 0 : 3)) {
                        wg_wait<1>();
                        mbar_arrive_remote_if(g2e + 8 * (it - 1), l01 && it < 7);
                        mbar_arrive_if(BAR(B_HS - 4) + 8 * it, l0 && it >= 4 && it < 7);
                    }
                }
            }
            mbar_wait(BAR(B_G2F + 6 - NST), 1);
            mbar_wait(BAR(B_AF + 9 - NST), 1);
            auto rel5 = [&](bool p) { mbar_arrive_remote_if(g2e + 40, l01 && p); mbar_arrive_if(BAR(B_HS + 2), l0 && p); };
            if (NST == 6 && wg) { wg_wait<0>(); rel5(true); }
            if (wg) TWAIT(47, bar_sync(7, 256));
            STAMPI(warp == 0, 73);
            float gf[80];
            wg_fence();
            static_for<48 - 4 * NST, 48>([&](auto K) {
                constexpr int it = K.value >> 2, ks = K.value & 3;
                WG<160>::ss<0, 1>(acc, da + (it == 11 ? 0 : it - 5) * 1024 + (ks >> 1) * 512 + (ks & 1) * 2, dhi(512, 2), db + (it - 6) * 1280 + (ks >> 1) * 640 + (ks & 1) * 64, dhi(512, 2), 1);
                if constexpr (K.value == 24) { wg_commit(); wg_wait<1>(); rel5(!wg); }
                if constexpr (it < 11 && ks == 1) TWAIT(36 + it, mbar_wait(BAR(B_G2F + it - 5), 1));
                if constexpr (it < 11 && ks == 2) TWAIT(78 + it, mbar_wait(BAR(B_AF + it - 2), 1));
                if constexpr (RQE == 2 && K.value >= 28 && K.value < 47) {
                    sched_bar();
                    #pragma unroll
                    for (int j = K.value - 28; j < (K.value == 46 ? 20 : K.value - 27); j++) {
                        const float lo = bflo((&gw[j >> 2].x)[j & 3]), hi = bfhi((&gw[j >> 2].x)[j & 3]);
                        gf[4 * j] = lo * rq0; gf[4 * j + 1] = hi * rq0; gf[4 * j + 2] = lo * rq1; gf[4 * j + 3] = hi * rq1;
                        pin<4>(gf + 4 * j);
                    }
                    sched_bar();
                }
                if constexpr (K.value == 45) { mbar_wait(BAR(B_OI), 0); fence_async_glob(); }
                if constexpr (K.value == 39) wg_commit();
                if constexpr (K.value == 46) { if (!wg) bar_arrive(7, 256); }
            });
            wg_commit();
            wg_wait<1>();
            bar_sync(5 + wg, 128);
            uint32_t osts[2];
            const uint32_t orow = (lane & 7) * 336 + (lane >> 3) * 16;
            osts[0] = sb + G2A + (1 + w) * 16384 + wg * 4096; osts[1] = osts[0] + 8192;
            wg_wait<0>();
            pin<80>(acc);
            STAMPIF(w == 0, 27 + wg);
            GSTAMPIF(warp == 4, 29);
            #pragma unroll
            for (int hf = 0; hf < 2; hf++) {
                #pragma unroll
                for (int i = 0; i < 5; i++) {
                    uint32_t o[4];
                    const float rq = hf ? rq1 : rq0;
                    #pragma unroll
                    for (int j = 0; j < 4; j++) { const int n = 16 * i + 4 * j + 2 * hf; o[j] = RQE == 2 ? pack2(acc[n] * gf[n], acc[n + 1] * gf[n + 1]) : hmul2(RQE ? pack2(acc[n], acc[n + 1]) : pack2(acc[n] * rq, acc[n + 1] * rq), (&gw[i].x)[j]); }
                    asm volatile("stmatrix.sync.aligned.m8n8.x4.shared.b16 [%0], {%1,%2,%3,%4};" :: "r"(osts[hf] + orow + i * 64), "r"(o[0]), "r"(o[1]), "r"(o[2]), "r"(o[3]) : "memory");
                    if (EI && i < 4 && (EI == 1 || (i & 1))) sched_bar();
                }
                fence_async_smem();
                __syncwarp();
                if (elect() && !((WI & 8) && hf)) { tma3d_red(&M.out, osts[hf], dq, 128 * tile + 16 * warp + 8 * hf); }
                sched_bar();
            }
            STAMPIF(w == 0, wg ? 31 : 85);
            if (elect()) asm volatile("cp.async.bulk.commit_group;\n cp.async.bulk.wait_group.read 0;" ::: "memory");
            STAMPIF(w == 3, wg ? 33 : 86);
            GSTAMPIF(warp == 4, 34);
        }
    } else {
        const int hw = warp & 3, wv = hw & 1;
        if (elect()) {
            if (warp & 2) {
                if (warp & 1) { _Pragma("unroll") for (int i = B_UD; i < NBARS; i++) mbar_init(BAR(i), bar_count(i)); }
                else { _Pragma("unroll") for (int i = B_WF; i < B_UD; i++) mbar_init(BAR(i), bar_count(i)); }
            } else { _Pragma("unroll") for (int i = 0; i < 20; i++) mbar_init(BAR(i) + wv * 160, 1); }
            asm volatile("fence.mbarrier_init.release.cluster;" ::: "memory");
            fence_async_smem();
        }
        __syncwarp();
        asm volatile("barrier.cluster.arrive.relaxed.aligned;" ::: "memory");
        const uint32_t t1 = clk0 + D_1 + ((((b * 37) & 127) * G_ST) >> 7);
        if (hw == 0) {
            bar_arrive(0, 384);
            if (lane < 15 && lane != B_KV) mbar_expect(BAR(lane), lane >= B_KV && lane < B_Q ? 9216 : 4096);
            __syncwarp();
            if (elect()) { wait_until(t1); bulk_g2s(sb + 16, P.ssm + b * 4096, 4096, BAR(B_H)); }
            __syncwarp();
            bar_sync(3, 128);
        } else { bar_sync(0, 384); bar_arrive(3, 128); }
        FFN_ROLE;
        const int kh = js >> 2, ft = tile * 8 + js;
        const int oz = __shfl_sync(~0u, tid >> 9, lane);
        epoch = ldg_rlx32(CNT(C_Z + tile, 6 + oz));
        if (hw == 0) {
            if (elect()) {
                auto x_fetch = [&](int r) {
                    if (!mbar_test(BAR(B_KV + r), 0)) { mbar_wait(BAR(B_KV + r), 0); pause(D_PK); }
                    poll_cnt(CNT(C_KV + 2 * r + (b >> 6), 0), (epoch | 127) + 1);
                    fence_async_glob();
                    if (r >= 2) mbar_wait(BAR(B_MD - 2 + r), 0);
                    mbar_expect(BAR(B_X + (r & 1)), 4096);
                    bulk_g2s(sb + XB + (r & 1) * XP, SC(kvT, (b + 128 * r) * 4096), 4096, BAR(B_X + (r & 1)));
                    STAMPIF(r < 2, 5 + r);
                };
                static_for<1, NORD>([&](auto I) {
                    constexpr char kind = ord_kind(I.value); constexpr int n = ord_index(I.value);
                    if constexpr (kind == 'k' && n >= 3) mbar_wait(BAR(B_TD + n - 3), 0);
                    if constexpr (kind != '_' && kind != 'x' && (TUNING || ord_time(I.value))) wait_until(t1 + TN(16 + I.value, ord_time(I.value)));
                    if constexpr (kind == 'k') { tma4d(sb + st_kv(n), &M.k, n * 128 + rank * 64, cl * 4 - 1, BAR(B_KV + n)); tma4d(sb + st_kv(n) + 5120, &M.v, n * 128 + rank * 64, cl * 4, BAR(B_KV + n)); }
                    if constexpr (kind == 'q') tma3d(sb + ST_Q + n * 4096, &M.q, ft * 16, n * 4, BAR(B_Q + n));
                    if constexpr (kind == 'h') bulk_g2s(sb + eslot(n) + 16, P.ssm + (b + 128 * n) * 4096, 4096, BAR(B_H + n));
                    if constexpr (kind == 'w') pf_l2(((n & 1) ? P.Wu : P.Wg) + (b + 128 * (n >> 1)) * 3072, 3072);
                    if constexpr (kind == 'x') x_fetch(n);
                });
                _Pragma("unroll 1") for (int r = ord_count('x'); r < 5; r++) x_fetch(r);
            }
        } else if (hw == 2 && elect()) { pf_map(&M.k); pf_map(&M.v); pf_map(&M.q); }
        __syncwarp();
        epoch = (__shfl_sync(~0u, epoch, 0) >> 7) + 1;
        const uint32_t target = epoch << 7, par = epoch & 1;
        const char* pa = lane < 8 ? CNT(C_Y, 0) : SC(abc, (lane & 7) * 128 + 12);
        const uint32_t want = lane < 8 ? target : epoch;
        auto y_poll = [&](int r) {
            if (!mbar_test(BAR(B_RD + r), 0)) { mbar_wait(BAR(B_RD + r), 0); pause(D_PY); }
            _Pragma("unroll 1") for (int it = 0; it < 20000 && __any_sync(~0u, (int)(ldg_rlx32(pa) - want) < 0); it++) {}
        };
        auto y_request = [&](int r) {
            if (elect()) {
                fence_async_glob();
                mbar_expect(BAR(B_Y + (r & 1)), 5120);
                tma5d(sb + ST_Y + (r & 1) * 4096, &M.y, 2032 - 16 * ft, 4 * r, BAR(B_Y + (r & 1)));
                bulk_g2s(sb + ST_Y + 8192 + (r & 1) * 1024, SC(abc, r * 1024), 1024, BAR(B_Y + (r & 1)));
            }
            STAMPIF(r < 2, 48 + r);
            pa += lane < 8 ? 4096 : 1024;
        };
        if (hw == 1) {
            if (elect()) pf_map(&M.y);
            mbar_wait(BAR(B_TD + 2), 0);
            wait_until(clk0 + D_M);
            _Pragma("unroll 1") for (int r = 0; r < 2; r++) {
                y_poll(r); y_request(r);
            }
        }
        if (hw >= 2) {
            pa += lane < 8 ? 8192 : 2048;
            {
                uint32_t aQ = sb + ST_Q + wv * 2048 + (lane & 15) * 64 + (((lane >> 1) + (lane >> 4)) & 3) * 16;
                float sq[4] = {0.f, 0.f, 0.f, 0.f};
                _Pragma("unroll 1") for (int rq = 0; rq < 5; rq++) {
                    mbar_wait(BAR(B_Q + rq), 0);
                    STAMPIF(wv && rq == 4, 44);
                    uint4 v[4];
                    #pragma unroll
                    for (int u = 0; u < 4; u++) v[u] = lds128((aQ ^ ((u & 1) << 5)) + (u >> 1) * 1024);
                    sched_bar();
                    #pragma unroll
                    for (int j = 0; j < ((WI & 256) ? 2 : 16); j++) acc_stat(sq[2 * (j & 1)], sq[2 * (j & 1) + 1], (&v[(j & 1) + (j >> 3) * 2].x)[(j >> 1) & 3]);
                    aQ += 4096;
                }
                asm volatile("st.shared.v2.f32 [%0], {%1,%2};" :: "r"(sb + ST_S + (lane & 15) * 48 + wv * 16 + (lane >> 4) * 8), "f"(sq[0] + sq[2]), "f"(sq[1] + sq[3]) : "memory");
            }
            float sa[4] = {0.f, 0.f, 0.f, 0.f};
            uint32_t yl = sb + ST_Y + wv * 1024 + lane * 32 + (lane & 4) * 4, ca = sb + ST_Y + 8192 + wv * 256 + q * 16;
            const uint32_t ym = rr ? 0u : 0x00010001u;
            char* zp = SC(z, tile * 163840 + wv * 8192 + (16 * js + 15 - rr) * 64 + ((q ^ 3 ^ (rr >> 1)) << 4));
            uint32_t xs = sb + ST_Q + wv * 1024 + (15 - rr) * 64 + q * 16;
            const uint32_t tm = (lane & 7) == (~js & 1) * 4;
            const char* zc = CNT(C_Z + tile, lane & 7);
            bar_sync(4, 64);
            STAMPIF(hw == 3, 46);
            uint32_t rs[2], mr[2];
            #pragma unroll
            for (int h = 0; h < 2; h++) {
                float f[2] = {0.f, 0.f};
                #pragma unroll
                for (int i = 0; i < 2; i++) { const uint4 a = lds128(sb + ST_S + (15 - 8 * h - rr) * 48 + i * 16); f[0] += __uint_as_float(a.x) + __uint_as_float(a.z); f[1] += __uint_as_float(a.y) + __uint_as_float(a.w); }
                const float mu = f[0] * (1.f / D_), r_ = rsqrt_(fmaxf(f[1] * (1.f / D_) - mu * mu, 0.f) + 1e-5f);
                rs[h] = pack2(r_, r_); const float m_ = -mu * bflo(rs[h]); mr[h] = pack2(m_, m_);
            }
            const int un = min(2 * b + wv, 239), cg = (un * 205) >> 10, ur = un - 5 * cg;
            char* op = padd(P.out, (ft * 16 + 15 - rr) * 1280 + wv * 64 + q * 16) - 256;
            uint4 x1[4] = {};
            const char *cp_ = SC(abc, (ur * 64 + (lane & 16) + q * 4 + (rr & 3)) * 16 + 8), *sp_ = SC(mod, (ur * 64 + lane) * 8);
            auto caddr = [&](int i) { return i < 2 ? sp_ + i * 256 : cp_ + (i & 1) * 512; };
            uint2 mv[4] = {};
            uint32_t pv = 0;
            bool asked = false;
            _Pragma("unroll 1") for (int r = 0;; r++) {
                STAMPR(0);
                uint4 x[4] = {};
                const bool ask = r >= 2 && r < 5 && wv == (ALT & r);
                if (ask) { if (!__any_sync(~0u, (int)(pv - want) < 0)) { y_request(r); asked = true; } else pv = ldg_rlx32(pa); }
                STAMPR(1);
                if (r < 5) {
                    #pragma unroll
                    for (int i = 0; i < 4; i++) x[i] = lds128(xs + (i >> 1) * 2048 - (i & 1) * 512);
                    sched_bar();
                } else {
                    mbar_wait(BAR(B_TD), 1);
                    if (elect()) {
                        mbar_expect(BAR(B_UF), (WI & 1) ? 0 : 16384);
                        #pragma unroll
                        for (int i = 0; i < ((WI & 1) ? 0 : 2); i++) tma2d(sb + UST + wv * 16384 + i * 8192, cg >= 24 ? &M.u2 : &M.g2, (cg >= 24 ? cg - 24 : cg) * 64, ur * 128 + i * 64, BAR(B_UF));
                    }
                    ll_wait<4>(mv, epoch, caddr);
                    #pragma unroll
                    for (int i = 0; i < 4; i++) sts32(sb + CS_TAB + wv * 512 + ((i & 1) * 8 + rr) * 32 + q * 4 + (i < 2 ? 16 : 0), mv[i].x);
                    fence_async_smem(); __syncwarp(); mbar_arrive_if(BAR(B_UF), l0);
                    STAMPIF(wv, 41);
                }
                if (r) {
                    #pragma unroll
                    for (int j = 0; j < ((WI & 16) ? 1 : 16); j++) acc_stat(sa[j & 2], sa[(j & 2) + 1], (&x1[(j >> 1) & 3].x)[(j & 1) + (j >> 3) * 2]);
                    #pragma unroll
                    for (int j = 0; j < 4; j++) asm volatile("" : "+f"(sa[j]) :: "memory");
                    bump<32768>(zp); bump(yl, (r & 1) ? 4096 : -4096); bump(ca, (r & 1) ? 1024 : -1024);
                }
                STAMPR(2);
                uint32_t nx[16];
                #pragma unroll
                for (int j = 0; j < 16; j++) { nx[j] = hfma2((&x[j >> 2].x)[j & 3], rs[(j >> 2) & 1], mr[(j >> 2) & 1]); asm volatile("" : "+r"(nx[j]) :: "memory"); }
                sched_bar();
                if (r) {
                    #pragma unroll
                    for (int i = 0; i < ((WI & 32) ? 0 : 4); i++) stg128(op + (i >> 1) * 128 - (i & 1) * 10240, x1[i].x, x1[i].y, x1[i].z, x1[i].w);
                }
                if (r == 5) break;
                STAMPR(3);
                if (ask && !asked) { if (__any_sync(~0u, (int)(pv - want) < 0)) y_poll(r); y_request(r); }
                asked = false;
                STAMPR(4);
                mbar_wait(BAR(B_Y + (r & 1)), (r >> 1) & 1);
                if (ALT && r >= 2 && !ask) pa += lane < 8 ? 4096 : 1024;
                if (wv == (ALT & (r + 1)) && r) { mbar_wait(BAR(B_YE + (~r & 1)), (r - 1) >> 1 & 1); pv = ldg_rlx32(pa); }
                if (r == 4) { _Pragma("unroll") for (int i = 0; i < 4; i++) mv[i] = ldg_rlx64(caddr(i)); }
                STAMPIF(wv == 0 && r == 0, 47);
                STAMPR(5);
                uint4 cc[8];
                uint32_t y[4][4];
                _Pragma("unroll 1") for (int it = 0; it < 20000; it++) {
                    uint32_t all = ~0u, any = 0;
                    #pragma unroll
                    for (int i = 0; i < 4; i++) ldsm4t(y[i], (yl ^ ((i & 1) << 4)) + (i >> 1) * 2048);
                    #pragma unroll
                    for (int i = 0; i < 8; i++) cc[i] = lds128(ca + (i >> 2) * 512 + (i & 3) * 64);
                    #pragma unroll
                    for (int j = 0; j < 8; j++) { all &= y[(j >> 2) * 2][j & 3]; any |= y[(j >> 2) * 2][j & 3]; }
                    if (!__any_sync(~0u, ((par ? ~all : any) & ym) != 0)) break;
                    VALIF(true, 89, 1);
                    const char* yp = SC(yT, (r * 128 + wv * 32 + (lane & 6) * 4 + (lane >> 3) * 2 + (lane & 1)) * 4096 + (254 - 2 * ft) * 16);
                    #pragma unroll
                    for (int i = 0; i < 4; i++) cp16((yl ^ ((i & 1) << 4)) + (i >> 1) * 2048, yp + (i & 1) * 16 + (i >> 1) * 262144);
                    asm volatile("cp.async.wait_all;" ::: "memory");
                    __syncwarp();
                }
                STAMPR(6);
                bump<256>(op); bump(xs, 4096);
                if (ZE) red_if(zc, 8, lane == r);
                #pragma unroll
                for (int j = 0; j < 16; j++) {
                    (&x1[j >> 2].x)[j & 3] = hfma2(hfma2(nx[j], cc[(j >> 3) * 4 + (j & 3)].x, cc[(j >> 3) * 4 + (j & 3)].y), y[j >> 2][j & 3], (&x[j >> 2].x)[j & 3]);
                    y[j >> 2][j & 3] = hmul2((&x1[j >> 2].x)[j & 3], cc[(j >> 3) * 4 + (j & 3)].z);
                    if ((j & 3) == (~j >> 2 & 1)) y[j >> 2][j & 3] = (y[j >> 2][j & 3] & ~tm) | (par & tm);
                    asm volatile("" : "+r"(y[j >> 2][j & 3]) :: "memory");
                }
                sched_bar();
                #pragma unroll
                for (int i = 0; i < 4; i++) asm volatile("st.relaxed.gpu.global.v4.b32 [%0], {%1,%2,%3,%4};" :: "l"(zp + (i >> 1) * 16384 - (i & 1) * 512), "r"(y[i][0]), "r"(y[i][1]), "r"(y[i][2]), "r"(y[i][3]) : "memory");
                if (!ZE) red_if(zc, 8, lane == r);
                mbar_arrive_if(r == 4 ? BAR(B_TD) : BAR(B_YE + (r & 1)), lane <= (r == 4));
                mbar_arrive_if(BAR(B_H + r), tid == 352);
                STAMPIF(wv, 75 + r);
                STAMPR(7);
            }
            auto x1_release = [&]() {
                if (l0) asm volatile("fence.release.gpu;\n red.relaxed.gpu.global.add.u32 [%0], 16;" :: "l"(CNT(C_Z + tile, 6)) : "memory");
                __syncwarp();
            };
            const float e0 = ((q & 2) ? sa[2] : sa[0]) + __shfl_xor_sync(~0u, (q & 2) ? sa[0] : sa[2], 2), e1 = ((q & 2) ? sa[3] : sa[1]) + __shfl_xor_sync(~0u, (q & 2) ? sa[1] : sa[3], 2);
            float e = ((q & 1) ? e1 : e0) + __shfl_xor_sync(~0u, (q & 1) ? e0 : e1, 1);
            if (wv) sts32(sb + TAB2 + lane * 4, __float_as_uint(e));
            bar_sync(4, 64);
            if (wv) { if (!FLATE) x1_release(); }
            else {
                uint32_t oth; asm volatile("ld.shared.b32 %0, [%1];" : "=r"(oth) : "r"(sb + TAB2 + lane * 4) : "memory");
                e += __uint_as_float(oth);
                const float mu = e * (1.f / D_), ve = fmaxf(__shfl_down_sync(~0u, e, 1) * (1.f / D_) - mu * mu, 0.f) + 1e-5f, r_ = rsqrt_(ve);
                if (!(q & 1)) stg_rlx128(SC(st2, (ft * 16 + 15 - rr - 4 * q) * 16), split2(-mu), split2(ve * r_), __float_as_uint(r_ * r_), epoch);
            }
            if (WDP == 0 && !wv && elect()) pf_l2(P.Wd + b * 15360, 15360);
            mbar_wait(BAR(B_UD), 0);
            if (!(WI & 2)) pause(D_UT);
            if (WDP == 1 && !wv && elect()) pf_l2(P.Wd + b * 15360, 15360);
            const char* up = SC(ut, (wv * 1536 + js * 192 + 2 * lane) * 8);
            uint4 v[15] = {};
            _Pragma("unroll 1") for (int it = 0; it < ((WI & 2) ? 0 : 20000); it++) {
                uint32_t bad = 0;
                #pragma unroll
                for (int i = 0; i < 15; i++) v[i] = ldg_rlx2x64(up + (i / 3) * 24576 + (i % 3) * 512);
                #pragma unroll
                for (int i = 0; i < 15; i++) bad |= (v[i].x ^ epoch) | (v[i].z ^ epoch);
                if (!__any_sync(~0u, (bad & 7) != 0)) break;
            }
            #pragma unroll
            for (int n = 0; n < 3; n++) {
                float f[4];
                #pragma unroll
                for (int j = 0; j < 4; j++) f[j] = (__uint_as_float((&v[n].x)[j]) + __uint_as_float((&v[3 + n].x)[j])) + (__uint_as_float((&v[6 + n].x)[j]) + __uint_as_float((&v[9 + n].x)[j])) + __uint_as_float((&v[12 + n].x)[j]);
                const uint32_t ta = sb + TAB1 + ((n == 2 ? 32 + wv * 8 : n * 8 + wv * 16) + rr) * 48 + q * 4, th2 = pack2(f[1], f[3]);
                sts32(ta, pack2(f[0], f[2])); sts32(ta + 16, th2); sts32(ta + 32, pack2(f[1] - bflo(th2), f[3] - bfhi(th2)));
            }
            if (lane < 20) sts32(sb + TAB1 + 48 * 48 + lane * 4, 0);
            fence_async_smem();
            __syncwarp();
            mbar_arrive_if(BAR(B_T1), l0);
            STAMPIF(hw == 3, 43);
        }
        asm volatile("setmaxnreg.dec.sync.aligned.u32 40;");
        const uint32_t ep2 = __shfl_sync(~0u, epoch, 0), tg2 = ep2 << 7;
        const char* hfl = CNT(C_HH + tile * 2 + kh, 0);
        auto hh_src = [&](int j) { const int c = (j * 11) >> 5, m = j - 3 * c; return SC(hh, (tile * 24 + (kh * 4 + m + (m >= dq)) * 3 + (c ^ (c < 2))) * 16384); };
        if (hw == 0 || hw == 3) {
            if (hw == 0) {
            if (elect()) {
                const CUtensorMap *m1 = rank ? &M.u1 : &M.g1, *m2 = rank ? &M.u2 : &M.g2;
                const char* pw = P.Wg + (b + 128 * (NWP >> 1)) * 3072;
                const long long dw = P.Wu - P.Wg;
                pf_map(m1);
                _Pragma("unroll 1") for (int n = 0; n < 20; n += 2) {
                    #pragma unroll
                    for (int h = 0; h < 2; h++) {
                        const uint32_t so = (n & 2) + h;
                        mbar_wait(BAR(B_WE) + so * 8, (n >> 2) & 1);
                        mbar_expect(BAR(B_WF) + so * 8, 16384);
                        tma3d_mc(sb + WR + rank * 8192 + so * 16384, m1, (n + h) * 32, js * 3, BAR(B_WF) + so * 8);
                        if (n >= WP0 && n < WP0 + 10 - NWP) pf_l2(pw + h * dw, 3072);
                    }
                    if (n >= WP0) pw += 128 * 3072;
                    if (WDP >= 8 && n >= WDP && n < WDP + 6) pf_l2(P.Wd + b * 15360 + (n - WDP) * 2560, 5120);
                }
                _Pragma("unroll 1") for (int n = 0; n < 10; n++) {
                    const uint32_t so = n & 3;
                    mbar_wait(BAR(B_WE) + so * 8, ((n >> 2) & 1) ^ 1);
                    mbar_expect(BAR(B_WF) + so * 8, 16384);
                    tma2d_mc(sb + WR + rank * 8192 + so * 16384, m2, js * 192 + 128, n * 64, BAR(B_WF) + so * 8);
                }
            }
            } else {
                const char* gp = SC(mod, (320 + dq * 80 + lane) * 8);
                auto gaddr = [&](int i) { return gp + i * 192; };
                uint2 gv[3];
                #pragma unroll
                for (int i = 0; i < 3; i++) gv[i] = ldg_rlx64(gaddr(i));
                ll_wait<3>(gv, ep2, gaddr);
                mbar_wait(BAR(B_HD), 0);
                red_if(hfl + lane * 4, 32, l0);
                STAMP(36);
                #pragma unroll
                for (int n = 0; n < 3; n++) sts32(sb + GBT + q * 80 + (rr + 6 * n) * 4, gv[n].x);
                __syncwarp();
                mbar_arrive_if(BAR(B_GB), lane < 2);
                mbar_wait(BAR(B_HD + 1), 0);
                red_if(hfl + lane * 4, 32, lane == 1);
            }
            if (elect()) {
                _Pragma("unroll 1") for (int j = 3 - hw; j < 6 + hw; j += j == 2 ? 4 : 1) {
                    const int c = (j * 11) >> 5;
                    const char* src = hh_src(j);
                    mbar_expect(BAR(B_AL + j), 16384);
                    if (j == 3 * c) { mbar_wait(BAR(B_HD + c), 0); if (c == 2) { red_if(hfl + 8, 32, true); STAMP(40); pause(D_H2); } poll_cnt(hfl + c * 4, tg2); fence_async_glob(); STAMPIF(c != 1, c ? 32 : 38); }
                    mbar_wait(c == 1 ? BAR(B_S0) : BAR(B_HS + j - 3 * c), c == 2);
                    bulk_g2s(sb + (j < 2 ? j + 12 : j < 8 ? j + 6 : 8) * 16384, src, 16384, BAR(B_AL + j));
                }
                if (hw == 0) { poll_cnt(CNT(C_Z + tile, 6), tg2); fence_acq(); mbar_arrive_if(BAR(B_OI), true); }
            }
        } else if (wv) {
            {
                if (lane < 10) mbar_expect(BAR(B_AL + lane), 16384);
                if (elect()) { pf_map(&M.g2); pf_map(&M.u2); }
                const char *zc = CNT(C_Z + tile, lane & 7), *zp = SC(z, tile * 163840);
                uint32_t rtp = 0, zv = tg2 - 1, al = BAR(B_AL), dst = sb;
                const uint32_t vo = lane * 128 + (lane & 3) * 16 + (lane & 8) * 8 + (lane & 4);
                int zr = 0;
                _Pragma("unroll 1") for (int i = 0; i < 19; i++) {
                    if (zr < 5) {
                        const uint32_t fre = BAR(zr == 4 ? B_UD : zr ? B_RD + 3 + (zr > 1) : B_RD);
                        bool go = (__ballot_sync(~0u, (int)(zv - tg2) >= 0) >> zr) & 1;
                        if (2 * zr <= i) {
                            mbar_wait(fre, 0);
                            if (!go) {
                                if (!mbar_test(BAR(B_H + zr), 1)) { mbar_wait(BAR(B_H + zr), 1); pause(D_PZ); }
                                poll_cnt(CNT(C_Z + tile, zr), tg2);
                            }
                            go = true;
                        } else go = go && mbar_test(fre, 0);
                        if (go) {
                            if (elect()) {
                                fence_async_glob();
                                bulk_g2s(sb + zr * 32768, zp, 16384, BAR(B_AL + 2 * zr));
                                bulk_g2s(sb + zr * 32768 + 16384, zp + 16384, 16384, BAR(B_AL + 2 * zr + 1));
                            }
                            STAMP(80 + zr);
                            zr++; zp += 32768;
                        }
                    }
                    mbar_wait(al, i >= 10);
                    _Pragma("unroll 1") for (int rt = 0; rt < 2000; rt++) {
                        uint32_t v[4];
                        #pragma unroll
                        for (int k = 0; k < 4; k++) asm volatile("ld.shared.b32 %0, [%1];" : "=r"(v[k]) : "r"(dst + vo + k * 4096) : "memory");
                        if (!__any_sync(~0u, ((v[0] ^ ep2) | (v[1] ^ ep2) | (v[2] ^ ep2) | (v[3] ^ ep2)) & 1)) break;
                        int i_ = i; asm volatile("" : "+r"(i_));
                        VALIF(true, 87 + (i >= 10), 1);
                        if (elect()) { mbar_expect(BAR(B_RT), 16384); bulk_g2s(dst, i_ < 10 ? SC(z, (tile * 10 + i_) * 16384) : hh_src(i_ - 10), 16384, BAR(B_RT)); }
                        mbar_wait(BAR(B_RT), rtp);
                        rtp ^= 1;
                    }
                    mbar_arrive_if(al - 8 * (B_AL - B_AF), l0);
                    if (zr < 5) zv = ldg_rlx32(zc);
                    al += i == 9 ? -72 : 8; dst += i == 9 ? 49152 : i == 11 || i == 17 ? -81920 : 16384;
                    STAMPIF(i == 0 || i == 10 || i == 16, i == 10 ? 37 : i ? 74 : 42);
                }
            }
        } else if (elect()) {
            if (WDP == 2) pf_l2(P.Wd + b * 15360, 15360);
            if (FLATE) asm volatile("fence.release.gpu;\n red.relaxed.gpu.global.add.u32 [%0], 16;" :: "l"(CNT(C_Z + tile, 6)) : "memory");
            pf_map(&M.wn); pf_map(&M.wd); pf_map(&M.out);
            int g = 0, c = 0, m = -3;
            _Pragma("unroll 1") for (int n = 0; n < 12; n++) {
                const uint32_t st = sb + G2B + g * 20480 + rank * 10240, f = BAR(B_G2F + g);
                mbar_wait(BAR(B_G2E + g), n >= 6);
                mbar_expect(f, 20480);
                if (m < 0) tma3d_mc(st, &M.wn, (js * 3 + n) * 64 + rank * 32, dq * 5, f);
                else tma5d_mc(st, &M.wd, ((kh * 4 + m + (m >= dq)) * 3 + (c ^ (c < 2))) * 8 + rank * 4, dq * 5, f);
                g = g == 5 ? 0 : g + 1;
                if (++m == 3) { m = 0; c++; }
            }
        }
    }
}

typedef CUresult (*EncodeFn)(CUtensorMap*, CUtensorMapDataType, cuuint32_t, void*, const cuuint64_t*, const cuuint64_t*, const cuuint32_t*, const cuuint32_t*,
                             CUtensorMapInterleave, CUtensorMapSwizzle, CUtensorMapL2promotion, CUtensorMapFloatOOBfill);
void enc(EncodeFn fn, CUtensorMap* m, const void* ptr, int rank, const cuuint64_t* dims, const cuuint64_t* strides, const cuuint32_t* box, CUtensorMapSwizzle sw,
         CUtensorMapL2promotion pr = CU_TENSOR_MAP_L2_PROMOTION_L2_128B) {
    cuuint32_t es[5] = {1, 1, 1, 1, 1};
    fn(m, CU_TENSOR_MAP_DATA_TYPE_BFLOAT16, rank, (void*)ptr, dims, strides, box, es, CU_TENSOR_MAP_INTERLEAVE_NONE, sw,
       pr, CU_TENSOR_MAP_FLOAT_OOB_FILL_NONE);
}
}

extern "C" void kernel_launch(void* const* d_in, const int* in_sizes, int n_in, void* d_out, int out_size) {
    void* fnp = nullptr; cudaDriverEntryPointQueryResult st;
    cudaGetDriverEntryPoint("cuTensorMapEncodeTiled", &fnp, cudaEnableDefault, &st);
    EncodeFn fn = (EncodeFn)fnp;
    void* scr;
    cudaGetSymbolAddress(&scr, g_s);
    Maps M; Ptrs P;
    P.k = (const char*)d_in[1]; P.v = (const char*)d_in[2]; P.shift = (const char*)d_in[3]; P.ssm = (const char*)d_in[4]; P.ssmD = (const char*)d_in[5]; P.Wg = (const char*)d_in[7]; P.Wu = (const char*)d_in[8];
    P.Wd = (const char*)d_in[9]; P.c = (const char*)d_in[10]; P.out = (char*)d_out; P.scr = (char*)scr;
    { cuuint64_t d[4] = {640, 2, 256, 4}, s[3] = {1280, 8 * 1280, 2 * 1280}; cuuint32_t b1[4] = {64, 2, 5, 4}, b2[4] = {64, 2, 4, 4};
      enc(fn, &M.k, d_in[1], 4, d, s, b1, CU_TENSOR_MAP_SWIZZLE_128B); enc(fn, &M.v, d_in[2], 4, d, s, b2, CU_TENSOR_MAP_SWIZZLE_128B); }
    { cuuint64_t d[3] = {32, 2048, 20}, s[2] = {1280, 64}; cuuint32_t b1[3] = {32, 16, 4};
      enc(fn, &M.q, d_in[0], 3, d, s, b1, CU_TENSOR_MAP_SWIZZLE_NONE); }
    { cuuint64_t d[5] = {2048, 2, 4, 4, 20}, s[4] = {4096, 8 * 4096, 2 * 4096, 32 * 4096}; cuuint32_t b1[5] = {16, 2, 4, 4, 4};
      enc(fn, &M.y, (char*)scr + offsetof(Scratch, yT), 5, d, s, b1, CU_TENSOR_MAP_SWIZZLE_32B, CU_TENSOR_MAP_L2_PROMOTION_NONE); }
    { cuuint64_t d[3] = {64, 640, 24}, s[2] = {3072, 128}; cuuint32_t b1[3] = {64, 32, 2};
      enc(fn, &M.g1, P.Wg, 3, d, s, b1, CU_TENSOR_MAP_SWIZZLE_128B); enc(fn, &M.u1, P.Wu, 3, d, s, b1, CU_TENSOR_MAP_SWIZZLE_128B); }
    { cuuint64_t d[2] = {1536, 640}, s[1] = {3072}; cuuint32_t b1[2] = {64, 64};
      enc(fn, &M.g2, P.Wg, 2, d, s, b1, CU_TENSOR_MAP_SWIZZLE_128B); enc(fn, &M.u2, P.Wu, 2, d, s, b1, CU_TENSOR_MAP_SWIZZLE_128B); }
    { cuuint64_t d[5] = {32, 2, 192, 4, 20}, s[4] = {1280, 8 * 1280, 2 * 1280, 64}; cuuint32_t b1[5] = {32, 2, 4, 4, 5};
      enc(fn, &M.wd, P.Wd, 5, d, s, b1, CU_TENSOR_MAP_SWIZZLE_64B); }
    { cuuint64_t d[3] = {32, 1536, 20}, s[2] = {1280, 64}; cuuint32_t b1[3] = {32, 32, 5};
      enc(fn, &M.wn, P.Wd, 3, d, s, b1, CU_TENSOR_MAP_SWIZZLE_64B); }
    { cuuint64_t d[2] = {3840, 640}, s[1] = {7680}; cuuint32_t b1[2] = {64, 160};
      enc(fn, &M.wm, d_in[11], 2, d, s, b1, CU_TENSOR_MAP_SWIZZLE_128B); }
    { cuuint64_t d[3] = {160, 4, 2048}, s[2] = {320, 1280}; cuuint32_t b1[3] = {168, 1, 8};
      enc(fn, &M.out, d_out, 3, d, s, b1, CU_TENSOR_MAP_SWIZZLE_NONE); }
    cudaFuncSetAttribute(fused_kernel, cudaFuncAttributeMaxDynamicSharedMemorySize, SMEM_BYTES);
    fused_kernel<<<132, 384, SMEM_BYTES>>>(P, M);
}
```

```cpp
#include <cuda_runtime.h>
#include <cuda_bf16.h>
#include <cuda.h>
#include <stdint.h>
#include <stddef.h>
#include <type_traits>

namespace {

constexpr int D_ = 640;

struct Scratch {
    uint4 kvT[D_ * 256], yT[D_ * 256];
    uint4 z[16 * 10 * 1024];
    uint4 hh[16 * 24 * 1024];
    uint4 st2[2048];
    uint4 abc[320];
    uint2 mod[640];
    uint2 ut[5 * 3072];
    uint32_t cnt[64 * 1024];
};
__device__ __align__(1024) Scratch g_s;
#define SC(f, off) padd(P.scr, (uint32_t)offsetof(Scratch, f) + (off))
constexpr int C_KV = 0  , C_Y = 10  , C_Z = 16  , C_HH = 32  ;

constexpr uint32_t WR = 163840, MISC = 229376, SMEM_BYTES = 232448;
constexpr uint32_t ESLOT = 0x31650;
constexpr uint32_t XP = 4112, XB = 65536 + 18432, ST_SH = XB + 2 * XP;
constexpr uint32_t ST_Q = 131072, ST_Y = ST_Q + 20480, ST_S = ST_Y + 10240  , UST = ST_Q;
__host__ __device__ constexpr uint32_t st_kv(int r) { return r == 2 ? ST_Y : r == 1 || r == 4 ? 65536 + 9216 : 65536; }
__host__ __device__ constexpr uint32_t eslot(int r) { return ((ESLOT >> (4 * r)) & 7) << 15; }
constexpr uint32_t PP = 4352;
constexpr uint32_t BARS = MISC, TAB1 = MISC + 688, TAB2 = TAB1 + 32 * 48, CS_TAB = TAB1  , PRF = -256;
constexpr uint32_t GBT = 0, G2B = 8192, G2A = 131072;
enum { B_H = 0, B_KV = 5, B_Q = 10, B_X = 15  , B_MD = 17  , B_AF = 20, B_AL = 30, B_WF = 40, B_G2F = 44, B_OI = 50, B_RT = 51, B_Y = 52  ,
       B_WE = 54, B_G2E = 58,
       B_UD = 64, B_HD = 65  , B_S0 = 68, B_HS = 69  ,
       B_RD = 72, B_UF = 77, B_TD = 78  , B_T1 = 81, B_YE = 82  , B_GB = 84, NBARS = 85 };
__host__ __device__ constexpr uint32_t bar_count(int i) {
    return i < B_WE ? 1 : i < B_UD ? 16 : i < B_RD ? 8 : i < B_T1 ? 4 : 2;
}
#define GSTAMPIF(c, i) do {} while (0)
#define STAMPIF(c, i) do {} while (0)
#define STAMP(i) do {} while (0)
#define VALIF(c, i, v) do {} while (0)
#define STAMPI STAMPIF
#define STAMPR(i) do {} while (0)
#define TWAIT(i, stmt) stmt
#define STAMPS(k) do {} while (0)
#define QS 4
__host__ __device__ constexpr int epi_slot(int e) { return e * QS / 4; }
#define ER 7
#define MAPM 0
#define RQE 2
#define EI 1
#define SBAR 1
#define FLATE 1
#define E0 1
#define WDP 14
#define ALT 0
#define WI 0
#define MSUB 1
#define Q2 4
#define G2R 5
#define YH 0
#define WP0 2
#define SEQ0 0x14124310224120ull
#define SEQ1 0x1324441123422140ull
#define NFAST 7
#define EARLYH 0
#define ZE 1
#define N_UT 13
#define NST 6
#define TN(i, v) v
#define TUNING 0
#define ORDER hkhhkxhqkxqqkqxqhwwww
#define TIMES 0, 860, 1570, 2100, 2890, 0, 3810, 0, 4520, 0, 0, 0, 6300, 0, 0, 0, 0, 8400, 0, 0, 0
#define STR2(x) #x
#define STR(x) STR2(x)
constexpr int NORD = sizeof(STR(ORDER)) - 1;
__host__ __device__ constexpr char ord_kind(int i) { return STR(ORDER)[i]; }
__host__ __device__ constexpr int ord_index(int i) { int n = ord_kind(i) == 'k'; for (int j = 0; j < i; j++) n += ord_kind(j) == ord_kind(i); return n; }
__host__ __device__ constexpr int ord_slot(int i) { int n = 0; for (int j = 0; j < i; j++) n += ord_kind(j) == 'k' ? 2 : ord_kind(j) != 'x'; return n; }
__host__ __device__ constexpr int ord_find(char c, int n) { for (int i = 0; i < NORD; i++) if (ord_kind(i) == c && ord_index(i) == n) return i; return -1; }
__host__ __device__ constexpr int ord_count(char c) { int n = 0; for (int i = 0; i < NORD; i++) n += ord_kind(i) == c; return n; }
__host__ __device__ constexpr uint32_t ord_mask(char c) { uint32_t m = 0; for (int i = 0; i < NORD; i++) m |= (uint32_t)(ord_kind(i) == c) << i; return m; }
__host__ __device__ constexpr int ord_time(int i) { constexpr int t[] = {TIMES}; return t[i]; }
constexpr int NWP = ord_count('w');
static_assert(NWP % 2 == 0 && ord_kind(0) == 'h' && ord_count('x') >= 2 && ord_count('k') == 4 && ord_count('q') == 5 && ord_count('h') == 5, "order");
#define TV0 500
#define D_1 TN(0, TV0)
#define TV1 420
#define G_U TN(1, TV1)
#define TV2 590
#define G_ST TN(2, TV2)
#define TV4 2000
#define D_SP TN(4, TV4)
#define TV5 0
#define G_F TN(5, TV5)
#define TV6 7500
#define D_M TN(6, TV6)
#define TV7 700
#define D_PK TN(7, TV7)
#define TV8 500
#define D_PY TN(8, TV8)
#define TV9 100
#define D_PZ TN(9, TV9)
#define TV10 400
#define D_H2 TN(10, TV10)
#define TV11 1600
#define D_UT TN(11, TV11)

__device__ __forceinline__ uint32_t smem_u32(const void* p) { return (uint32_t)__cvta_generic_to_shared(p); }
__device__ __forceinline__ void mbar_init(uint32_t bar, uint32_t cnt) { asm volatile("mbarrier.init.shared::cta.b64 [%0], %1;" :: "r"(bar), "r"(cnt) : "memory"); }
__device__ __forceinline__ void mbar_expect(uint32_t bar, uint32_t bytes) { asm volatile("mbarrier.arrive.expect_tx.shared::cta.b64 _, [%0], %1;" :: "r"(bar), "r"(bytes) : "memory"); }
__device__ __forceinline__ void mbar_arrive_if(uint32_t bar, bool p) { asm volatile("{ .reg .pred p; setp.ne.b32 p, %1, 0; @p mbarrier.arrive.shared::cta.b64 _, [%0]; }" :: "r"(bar), "r"((int)p) : "memory"); }
__device__ __forceinline__ void mbar_arrive_remote_if(uint32_t bar, bool p) { asm volatile("{ .reg .pred p; setp.ne.b32 p, %1, 0; @p mbarrier.arrive.shared::cluster.b64 _, [%0]; }" :: "r"(bar), "r"((int)p) : "memory"); }
#define WAIT_LOOP(op) "{\n .reg .pred p, q; .reg .u32 c; mov.u32 c, 0;\n LAB_WAIT:\n " op " p, [%0], %1;\n @p bra LAB_DONE;\n add.u32 c, c, 1; setp.lt.u32 q, c, 16384;\n @q bra LAB_WAIT;\n LAB_DONE:\n }"
__device__ __forceinline__ void mbar_wait(uint32_t bar, uint32_t parity) { asm volatile(WAIT_LOOP("mbarrier.try_wait.parity.shared::cta.b64") :: "r"(bar), "r"(parity) : "memory"); }
__device__ __forceinline__ bool mbar_test(uint32_t bar, uint32_t parity) {
    uint32_t ok; asm volatile("{ .reg .pred p; mbarrier.test_wait.parity.shared::cta.b64 p, [%1], %2; selp.u32 %0, 1, 0, p; }" : "=r"(ok) : "r"(bar), "r"(parity) : "memory"); return ok;
}
__device__ __forceinline__ uint32_t clock32() { uint32_t t; asm volatile("mov.u32 %0, %%clock;" : "=r"(t) :: "memory"); return t; }
__device__ __forceinline__ void wait_clock(uint32_t t0, uint32_t d) {
    asm volatile("{\n .reg .pred p; .reg .u32 t;\n LAB_CLK:\n mov.u32 t, %%clock; sub.u32 t, t, %0; setp.lt.u32 p, t, %1;\n @p bra LAB_CLK;\n }" :: "r"(t0), "r"(d) : "memory");
}
__device__ __forceinline__ bool elect() { uint32_t p; asm volatile("{ .reg .pred p; elect.sync _|p, 0xffffffff; selp.u32 %0, 1, 0, p; }" : "=r"(p)); return p; }
__device__ __forceinline__ void pf_map(const CUtensorMap* m) { asm volatile("prefetch.tensormap [%0];" :: "l"(m) : "memory"); }
__device__ __forceinline__ void bar_sync(int id, int n) { asm volatile("bar.sync %0, %1;" :: "r"(id), "r"(n) : "memory"); }
__device__ __forceinline__ bool bar_or(int id, int n, bool c) {
    uint32_t r; asm volatile("{ .reg .pred p, q; setp.ne.b32 p, %3, 0; bar.red.or.pred q, %1, %2, p; selp.u32 %0, 1, 0, q; }" : "=r"(r) : "r"(id), "r"(n), "r"((int)c) : "memory"); return r;
}
__device__ __forceinline__ void wait_until(uint32_t t1) {
    asm volatile("{\n .reg .pred p; .reg .s32 t;\n LAB_CLK:\n mov.u32 t, %%clock; sub.s32 t, t, %0; setp.lt.s32 p, t, 0;\n @p bra LAB_CLK;\n }" :: "r"(t1) : "memory");
}
__device__ __forceinline__ void pause(uint32_t d) { wait_clock(clock32(), d); }
__device__ __forceinline__ void bar_arrive(int id, int n) { asm volatile("bar.arrive %0, %1;" :: "r"(id), "r"(n) : "memory"); }
__device__ __forceinline__ void fence_async_smem() { asm volatile("fence.proxy.async.shared::cta;" ::: "memory"); }
__device__ __forceinline__ void fence_async_glob() { asm volatile("fence.proxy.async.global;" ::: "memory"); }
__device__ __forceinline__ void fence_acq() { asm volatile("fence.acquire.gpu;" ::: "memory"); }
__device__ __forceinline__ void bulk_g2s(uint32_t dst, const void* src, uint32_t bytes, uint32_t bar) {
    asm volatile("cp.async.bulk.shared::cluster.global.mbarrier::complete_tx::bytes [%0], [%1], %2, [%3];" :: "r"(dst), "l"(src), "r"(bytes), "r"(bar) : "memory");
}
__device__ __forceinline__ void pf_l2(const void* src, uint32_t bytes) { asm volatile("cp.async.bulk.prefetch.L2.global [%0], %1;" :: "l"(src), "r"(bytes) : "memory"); }
__device__ __forceinline__ void tma2d(uint32_t dst, const CUtensorMap* m, int c0, int c1, uint32_t bar) {
    asm volatile("cp.async.bulk.tensor.2d.shared::cluster.global.mbarrier::complete_tx::bytes [%0], [%1, {%3, %4}], [%2];" :: "r"(dst), "l"(m), "r"(bar), "r"(c0), "r"(c1) : "memory");
}
__device__ __forceinline__ void tma3d(uint32_t dst, const CUtensorMap* m, int c1, int c2, uint32_t bar) {
    asm volatile("cp.async.bulk.tensor.3d.shared::cluster.global.mbarrier::complete_tx::bytes [%0], [%1, {%5, %3, %4}], [%2];" :: "r"(dst), "l"(m), "r"(bar), "r"(c1), "r"(c2), "r"(0) : "memory");
}
__device__ __forceinline__ void tma4d(uint32_t dst, const CUtensorMap* m, int c0, int c2, uint32_t bar) {
    asm volatile("cp.async.bulk.tensor.4d.shared::cluster.global.mbarrier::complete_tx::bytes [%0], [%1, {%3, %5, %4, %5}], [%2];" :: "r"(dst), "l"(m), "r"(bar), "r"(c0), "r"(c2), "r"(0) : "memory");
}
__device__ __forceinline__ void tma5d(uint32_t dst, const CUtensorMap* m, int c0, int c4, uint32_t bar) {
    asm volatile("cp.async.bulk.tensor.5d.shared::cluster.global.mbarrier::complete_tx::bytes [%0], [%1, {%3, %5, %5, %5, %4}], [%2];" :: "r"(dst), "l"(m), "r"(bar), "r"(c0), "r"(c4), "r"(0) : "memory");
}
__device__ __forceinline__ void tma5d_mc(uint32_t dst, const CUtensorMap* m, int c2, int c4, uint32_t bar) {
    asm volatile("cp.async.bulk.tensor.5d.shared::cluster.global.mbarrier::complete_tx::bytes.multicast::cluster [%0], [%1, {%5, %5, %3, %5, %4}], [%2], %6;"
                 :: "r"(dst), "l"(m), "r"(bar), "r"(c2), "r"(c4), "r"(0), "h"((uint16_t)3) : "memory");
}
__device__ __forceinline__ void tma3d_mc(uint32_t dst, const CUtensorMap* m, int c1, int c2, uint32_t bar) {
    asm volatile("cp.async.bulk.tensor.3d.shared::cluster.global.mbarrier::complete_tx::bytes.multicast::cluster [%0], [%1, {%5, %3, %4}], [%2], %6;"
                 :: "r"(dst), "l"(m), "r"(bar), "r"(c1), "r"(c2), "r"(0), "h"((uint16_t)3) : "memory");
}
__device__ __forceinline__ void tma2d_mc(uint32_t dst, const CUtensorMap* m, int c0, int c1, uint32_t bar) {
    asm volatile("cp.async.bulk.tensor.2d.shared::cluster.global.mbarrier::complete_tx::bytes.multicast::cluster [%0], [%1, {%3, %4}], [%2], %5;"
                 :: "r"(dst), "l"(m), "r"(bar), "r"(c0), "r"(c1), "h"((uint16_t)3) : "memory");
}
__device__ __forceinline__ void tma3d_red(const CUtensorMap* m, uint32_t src, int c1, int c2) {
    asm volatile("cp.reduce.async.bulk.tensor.3d.global.shared::cta.add.bulk_group [%0, {%4, %2, %3}], [%1];" :: "l"(m), "r"(src), "r"(c1), "r"(c2), "r"(0) : "memory");
}
__device__ __forceinline__ void red_if(const void* c, uint32_t inc, bool p) { asm volatile("{ .reg .pred p; setp.ne.b32 p, %2, 0; @p red.relaxed.gpu.global.add.u32 [%0], %1; }" :: "l"(c), "r"(inc), "r"((int)p) : "memory"); }
__device__ __forceinline__ uint32_t ldg_rlx32(const void* p) { uint32_t v; asm volatile("ld.relaxed.gpu.global.u32 %0, [%1];" : "=r"(v) : "l"(p) : "memory"); return v; }
__device__ __forceinline__ uint32_t ldg_late(const char* p, int lane) { return ldg_rlx32(p + (lane & 1) * 4); }
__device__ __forceinline__ bool reached(uint32_t v, uint32_t target) { return __ballot_sync(~0u, (int)(v - target) >= 0) & 1; }
__device__ __forceinline__ uint2 ldg_rlx64(const void* p) { uint2 v; asm volatile("{ .reg .b64 x; ld.relaxed.gpu.global.b64 x, [%2]; mov.b64 {%0, %1}, x; }" : "=r"(v.x), "=r"(v.y) : "l"(p) : "memory"); return v; }
__device__ __forceinline__ void ldg_rlx128_if(uint4& v, const void* p, bool c) {
    asm volatile("{ .reg .b128 t; .reg .b64 x, y; .reg .pred p; setp.ne.b32 p, %5, 0; mov.b64 x, {%0, %1}; mov.b64 y, {%2, %3}; mov.b128 t, {x, y};\n"
                 " @p ld.relaxed.gpu.global.b128 t, [%4]; mov.b128 {x, y}, t; mov.b64 {%0, %1}, x; mov.b64 {%2, %3}, y; }"
                 : "+r"(v.x), "+r"(v.y), "+r"(v.z), "+r"(v.w) : "l"(p), "r"((int)c) : "memory");
}
__device__ __forceinline__ uint4 ldg_rlx2x64(const void* p) { uint4 v; asm volatile("{ .reg .b64 x, y; ld.relaxed.gpu.global.v2.b64 {x, y}, [%4]; mov.b64 {%0, %1}, x; mov.b64 {%2, %3}, y; }" : "=r"(v.x), "=r"(v.y), "=r"(v.z), "=r"(v.w) : "l"(p) : "memory"); return v; }
__device__ __forceinline__ void stg_rlx128(void* p, uint32_t x, uint32_t y, uint32_t z, uint32_t w) {
    asm volatile("{ .reg .b128 t; .reg .b64 a, b; mov.b64 a, {%1, %2}; mov.b64 b, {%3, %4}; mov.b128 t, {a, b}; st.relaxed.gpu.global.b128 [%0], t; }" :: "l"(p), "r"(x), "r"(y), "r"(z), "r"(w) : "memory");
}
__device__ __forceinline__ void stg_rlx128_if(void* p, const uint32_t* v, bool c) {
    asm volatile("{ .reg .pred p; .reg .b128 t; .reg .b64 a, b; setp.ne.b32 p, %5, 0; mov.b64 a, {%1, %2}; mov.b64 b, {%3, %4}; mov.b128 t, {a, b}; @p st.relaxed.gpu.global.b128 [%0], t; }" :: "l"(p), "r"(v[0]), "r"(v[1]), "r"(v[2]), "r"(v[3]), "r"((int)c) : "memory");
}
__device__ __forceinline__ void stg128(void* p, uint32_t x, uint32_t y, uint32_t z, uint32_t w) { asm volatile("st.global.v4.b32 [%0], {%1,%2,%3,%4};" :: "l"(p), "r"(x), "r"(y), "r"(z), "r"(w) : "memory"); }
template<int W> __device__ __forceinline__ void stg_tag(void* p, const uint32_t* o, uint32_t tm, uint32_t par) {
    const uint32_t t = (o[W] & ~tm) | (par & tm);
    asm volatile("st.relaxed.gpu.global.v4.b32 [%0], {%1,%2,%3,%4};" :: "l"(p), "r"(W ? o[0] : t), "r"(W ? t : o[1]), "r"(o[2]), "r"(o[3]) : "memory");
}
__device__ __forceinline__ void poll_cnt(const void* c, uint32_t target) {
    asm volatile("{\n .reg .pred p, q; .reg .u32 c, v; mov.u32 c, 0;\n LAB_POLL:\n ld.relaxed.gpu.global.u32 v, [%0];\n sub.u32 v, v, %1; setp.ge.s32 p, v, 0;\n @p bra LAB_PDONE;\n"
                 " add.u32 c, c, 1; setp.lt.u32 q, c, 20000;\n @q bra LAB_POLL;\n LAB_PDONE:\n }" :: "l"(c), "r"(target) : "memory");
}
template<int N, typename F> __device__ __forceinline__ void ll_wait(uint2* v, uint32_t tag, F&& addr) {
    #pragma unroll 1
    for (int it = 0; it < 20000; it++) {
        uint32_t bad = 0;
        #pragma unroll
        for (int i = 0; i < N; i++) bad |= v[i].y ^ tag;
        if (!__any_sync(~0u, bad != 0)) break;
        asm volatile("nanosleep.u32 100;");
        #pragma unroll
        for (int i = 0; i < N; i++) v[i] = ldg_rlx64(addr(i));
    }
}
__device__ __forceinline__ uint4 lds128(uint32_t a) { uint4 v; asm volatile("ld.shared.v4.b32 {%0,%1,%2,%3}, [%4];" : "=r"(v.x), "=r"(v.y), "=r"(v.z), "=r"(v.w) : "r"(a) : "memory"); return v; }
__device__ __forceinline__ uint2 lds64(uint32_t a) { uint2 v; asm volatile("ld.shared.v2.b32 {%0,%1}, [%2];" : "=r"(v.x), "=r"(v.y) : "r"(a) : "memory"); return v; }
__device__ __forceinline__ void sts128(uint32_t a, uint32_t x, uint32_t y, uint32_t z, uint32_t w) { asm volatile("st.shared.v4.b32 [%0], {%1,%2,%3,%4};" :: "r"(a), "r"(x), "r"(y), "r"(z), "r"(w) : "memory"); }
__device__ __forceinline__ void sts32(uint32_t a, uint32_t x) { asm volatile("st.shared.b32 [%0], %1;" :: "r"(a), "r"(x) : "memory"); }
__device__ __forceinline__ void ldsm4t(uint32_t* r, uint32_t a) { asm volatile("ldmatrix.sync.aligned.m8n8.x4.trans.shared.b16 {%0,%1,%2,%3}, [%4];" : "=r"(r[0]), "=r"(r[1]), "=r"(r[2]), "=r"(r[3]) : "r"(a) : "memory"); }
__device__ __forceinline__ void ldsm2t(uint32_t& r0, uint32_t& r1, uint32_t a) { asm volatile("ldmatrix.sync.aligned.m8n8.x2.trans.shared.b16 {%0,%1}, [%2];" : "=r"(r0), "=r"(r1) : "r"(a) : "memory"); }
__device__ __forceinline__ void ldsm4t_if(uint32_t* r, uint32_t a, bool c) { asm volatile("{ .reg .pred p; setp.ne.b32 p, %5, 0; @p ldmatrix.sync.aligned.m8n8.x4.trans.shared.b16 {%0,%1,%2,%3}, [%4]; }" : "+r"(r[0]), "+r"(r[1]), "+r"(r[2]), "+r"(r[3]) : "r"(a), "r"((int)c) : "memory"); }
__device__ __forceinline__ void ldsm2t_if(uint32_t* r, uint32_t a, bool c) { asm volatile("{ .reg .pred p; setp.ne.b32 p, %3, 0; @p ldmatrix.sync.aligned.m8n8.x2.trans.shared.b16 {%0,%1}, [%2]; }" : "+r"(r[0]), "+r"(r[1]) : "r"(a), "r"((int)c) : "memory"); }
__device__ __forceinline__ void lds128_if(uint4& v, uint32_t a, bool c) { asm volatile("{ .reg .pred p; setp.ne.b32 p, %5, 0; @p ld.shared.v4.b32 {%0,%1,%2,%3}, [%4]; }" : "+r"(v.x), "+r"(v.y), "+r"(v.z), "+r"(v.w) : "r"(a), "r"((int)c) : "memory"); }
__device__ __forceinline__ void cp16(uint32_t d, const void* s) { asm volatile("cp.async.cg.shared.global [%0], [%1], 16;" :: "r"(d), "l"(s) : "memory"); }
__device__ __forceinline__ char* padd(const void* p, uint32_t off) { char* r; asm("{ .reg .u64 t; cvt.u64.u32 t, %2; add.u64 %0, %1, t; }" : "=l"(r) : "l"(p), "r"(off)); return r; }
__device__ __forceinline__ uint32_t prmt(uint32_t a, uint32_t b, uint32_t s) { uint32_t r; asm("prmt.b32 %0, %1, %2, %3;" : "=r"(r) : "r"(a), "r"(b), "r"(s)); return r; }
__device__ __forceinline__ uint32_t pack2(float lo, float hi) { uint32_t r; asm("cvt.rn.bf16x2.f32 %0, %1, %2;" : "=r"(r) : "f"(hi), "f"(lo)); return r; }
__device__ __forceinline__ uint32_t pack2relu(float lo, float hi) { uint32_t r; asm("cvt.rn.relu.bf16x2.f32 %0, %1, %2;" : "=r"(r) : "f"(hi), "f"(lo)); return r; }
__device__ __forceinline__ float bflo(uint32_t w) { return __uint_as_float(w << 16); }
__device__ __forceinline__ float bfhi(uint32_t w) { return __uint_as_float(w & 0xffff0000u); }
__device__ __forceinline__ float bfround(float x) { return bflo(pack2(x, x)); }
__device__ __forceinline__ uint32_t hmul2(uint32_t a, uint32_t b) { uint32_t r; asm("mul.rn.bf16x2 %0, %1, %2;" : "=r"(r) : "r"(a), "r"(b)); return r; }
__device__ __forceinline__ uint32_t hadd2(uint32_t a, uint32_t b) { uint32_t r; asm("add.rn.bf16x2 %0, %1, %2;" : "=r"(r) : "r"(a), "r"(b)); return r; }
__device__ __forceinline__ uint32_t hfma2(uint32_t a, uint32_t b, uint32_t c) { uint32_t r; asm("fma.rn.bf16x2 %0, %1, %2, %3;" : "=r"(r) : "r"(a), "r"(b), "r"(c)); return r; }
__device__ __forceinline__ void sched_bar() { asm volatile("pmevent 1;" ::: "memory"); }
template<int H> __device__ __forceinline__ uint32_t hfma2s(uint32_t a, uint32_t w, uint32_t c) {
    uint32_t r;
    if (H) asm("{ .reg .b16 l, h; .reg .b32 t; mov.b32 {l, h}, %2; mov.b32 t, {h, h}; fma.rn.bf16x2 %0, %1, t, %3; }" : "=r"(r) : "r"(a), "r"(w), "r"(c));
    else asm("{ .reg .b16 l, h; .reg .b32 t; mov.b32 {l, h}, %2; mov.b32 t, {l, l}; fma.rn.bf16x2 %0, %1, t, %3; }" : "=r"(r) : "r"(a), "r"(w), "r"(c));
    return r;
}
__device__ __forceinline__ void bump(uint32_t& a, uint32_t d) { asm volatile("add.u32 %0, %0, %1;" : "+r"(a) : "r"(d) : "memory"); }
template<int D> __device__ __forceinline__ void bump(char*& p) { asm volatile("add.s64 %0, %0, %1;" : "+l"(p) : "n"(D) : "memory"); }
__device__ __forceinline__ void wg_fence() { asm volatile("wgmma.fence.sync.aligned;" ::: "memory"); }
__device__ __forceinline__ void wg_commit() { asm volatile("wgmma.commit_group.sync.aligned;" ::: "memory"); }
template<int N> __device__ __forceinline__ void wg_wait() { asm volatile("wgmma.wait_group.sync.aligned %0;" :: "n"(N) : "memory"); }
template<int N> __device__ __forceinline__ void pin(float* d) {
    #pragma unroll
    for (int i = 0; i < N; i++) asm volatile("" : "+f"(d[i]) :: "memory");
}
__device__ __forceinline__ uint32_t dlo(uint32_t addr, uint32_t lbo) { return ((addr & 0x3FFFF) >> 4) | ((lbo >> 4) << 16); }
__host__ __device__ constexpr uint32_t dhi(uint32_t sbo, uint32_t sw) { return (sbo >> 4) | (sw << 30); }

template<int N> struct WG;
template<> struct WG<8> { template<int TA, int TB> static __device__ __forceinline__ void ss(float* d, uint32_t alo, uint32_t ahi, uint32_t blo, uint32_t bhi, int sd) {
  asm volatile("{ .reg .pred p; .reg .b64 da, db; mov.b64 da, {%4,%5}; mov.b64 db, {%6,%7}; setp.ne.b32 p, %8, 0;\n"
    "wgmma.mma_async.sync.aligned.m64n8k16.f32.bf16.bf16 {%0,%1,%2,%3}, da, db, p, 1, 1, %9, %10; }"
    : "+f"(d[0]),"+f"(d[1]),"+f"(d[2]),"+f"(d[3])
    : "r"(alo), "r"(ahi), "r"(blo), "r"(bhi), "r"(sd), "n"(TA), "n"(TB)); }
};
template<> struct WG<16> { template<int TA, int TB> static __device__ __forceinline__ void ss(float* d, uint32_t alo, uint32_t ahi, uint32_t blo, uint32_t bhi, int sd) {
  asm volatile("{ .reg .pred p; .reg .b64 da, db; mov.b64 da, {%8,%9}; mov.b64 db, {%10,%11}; setp.ne.b32 p, %12, 0;\n"
    "wgmma.mma_async.sync.aligned.m64n16k16.f32.bf16.bf16 {%0,%1,%2,%3,%4,%5,%6,%7}, da, db, p, 1, 1, %13, %14; }"
    : "+f"(d[0]),"+f"(d[1]),"+f"(d[2]),"+f"(d[3]),"+f"(d[4]),"+f"(d[5]),"+f"(d[6]),"+f"(d[7])
    : "r"(alo), "r"(ahi), "r"(blo), "r"(bhi), "r"(sd), "n"(TA), "n"(TB)); }
};
template<> struct WG<32> { template<int TA, int TB> static __device__ __forceinline__ void ss(float* d, uint32_t alo, uint32_t ahi, uint32_t blo, uint32_t bhi, int sd) {
  asm volatile("{ .reg .pred p; .reg .b64 da, db; mov.b64 da, {%16,%17}; mov.b64 db, {%18,%19}; setp.ne.b32 p, %20, 0;\n"
    "wgmma.mma_async.sync.aligned.m64n32k16.f32.bf16.bf16 {%0,%1,%2,%3,%4,%5,%6,%7,%8,%9,%10,%11,%12,%13,%14,%15}, da, db, p, 1, 1, %21, %22; }"
    : "+f"(d[0]),"+f"(d[1]),"+f"(d[2]),"+f"(d[3]),"+f"(d[4]),"+f"(d[5]),"+f"(d[6]),"+f"(d[7]),"+f"(d[8]),"+f"(d[9]),"+f"(d[10]),"+f"(d[11]),"+f"(d[12]),"+f"(d[13]),"+f"(d[14]),"+f"(d[15])
    : "r"(alo), "r"(ahi), "r"(blo), "r"(bhi), "r"(sd), "n"(TA), "n"(TB)); }
};
template<> struct WG<48> { template<int TA, int TB> static __device__ __forceinline__ void ss(float* d, uint32_t alo, uint32_t ahi, uint32_t blo, uint32_t bhi, int sd) {
  asm volatile("{ .reg .pred p; .reg .b64 da, db; mov.b64 da, {%24,%25}; mov.b64 db, {%26,%27}; setp.ne.b32 p, %28, 0;\n"
    "wgmma.mma_async.sync.aligned.m64n48k16.f32.bf16.bf16 {%0,%1,%2,%3,%4,%5,%6,%7,%8,%9,%10,%11,%12,%13,%14,%15,%16,%17,%18,%19,%20,%21,%22,%23}, da, db, p, 1, 1, %29, %30; }"
    : "+f"(d[0]),"+f"(d[1]),"+f"(d[2]),"+f"(d[3]),"+f"(d[4]),"+f"(d[5]),"+f"(d[6]),"+f"(d[7]),"+f"(d[8]),"+f"(d[9]),"+f"(d[10]),"+f"(d[11]),"+f"(d[12]),"+f"(d[13]),"+f"(d[14]),"+f"(d[15]),"+f"(d[16]),"+f"(d[17]),"+f"(d[18]),"+f"(d[19]),"+f"(d[20]),"+f"(d[21]),"+f"(d[22]),"+f"(d[23])
    : "r"(alo), "r"(ahi), "r"(blo), "r"(bhi), "r"(sd), "n"(TA), "n"(TB)); }
};
template<> struct WG<64> { template<int TA, int TB> static __device__ __forceinline__ void ss(float* d, uint32_t alo, uint32_t ahi, uint32_t blo, uint32_t bhi, int sd) {
  asm volatile("{ .reg .pred p; .reg .b64 da, db; mov.b64 da, {%32,%33}; mov.b64 db, {%34,%35}; setp.ne.b32 p, %36, 0;\n"
    "wgmma.mma_async.sync.aligned.m64n64k16.f32.bf16.bf16 {%0,%1,%2,%3,%4,%5,%6,%7,%8,%9,%10,%11,%12,%13,%14,%15,%16,%17,%18,%19,%20,%21,%22,%23,%24,%25,%26,%27,%28,%29,%30,%31}, da, db, p, 1, 1, %37, %38; }"
    : "+f"(d[0]),"+f"(d[1]),"+f"(d[2]),"+f"(d[3]),"+f"(d[4]),"+f"(d[5]),"+f"(d[6]),"+f"(d[7]),"+f"(d[8]),"+f"(d[9]),"+f"(d[10]),"+f"(d[11]),"+f"(d[12]),"+f"(d[13]),"+f"(d[14]),"+f"(d[15]),"+f"(d[16]),"+f"(d[17]),"+f"(d[18]),"+f"(d[19]),"+f"(d[20]),"+f"(d[21]),"+f"(d[22]),"+f"(d[23]),"+f"(d[24]),"+f"(d[25]),"+f"(d[26]),"+f"(d[27]),"+f"(d[28]),"+f"(d[29]),"+f"(d[30]),"+f"(d[31])
    : "r"(alo), "r"(ahi), "r"(blo), "r"(bhi), "r"(sd), "n"(TA), "n"(TB)); }
};
template<> struct WG<80> { template<int TA, int TB> static __device__ __forceinline__ void ss(float* d, uint32_t alo, uint32_t ahi, uint32_t blo, uint32_t bhi, int sd) {
  asm volatile("{ .reg .pred p; .reg .b64 da, db; mov.b64 da, {%40,%41}; mov.b64 db, {%42,%43}; setp.ne.b32 p, %44, 0;\n"
    "wgmma.mma_async.sync.aligned.m64n80k16.f32.bf16.bf16 {%0,%1,%2,%3,%4,%5,%6,%7,%8,%9,%10,%11,%12,%13,%14,%15,%16,%17,%18,%19,%20,%21,%22,%23,%24,%25,%26,%27,%28,%29,%30,%31,%32,%33,%34,%35,%36,%37,%38,%39}, da, db, p, 1, 1, %45, %46; }"
    : "+f"(d[0]),"+f"(d[1]),"+f"(d[2]),"+f"(d[3]),"+f"(d[4]),"+f"(d[5]),"+f"(d[6]),"+f"(d[7]),"+f"(d[8]),"+f"(d[9]),"+f"(d[10]),"+f"(d[11]),"+f"(d[12]),"+f"(d[13]),"+f"(d[14]),"+f"(d[15]),"+f"(d[16]),"+f"(d[17]),"+f"(d[18]),"+f"(d[19]),"+f"(d[20]),"+f"(d[21]),"+f"(d[22]),"+f"(d[23]),"+f"(d[24]),"+f"(d[25]),"+f"(d[26]),"+f"(d[27]),"+f"(d[28]),"+f"(d[29]),"+f"(d[30]),"+f"(d[31]),"+f"(d[32]),"+f"(d[33]),"+f"(d[34]),"+f"(d[35]),"+f"(d[36]),"+f"(d[37]),"+f"(d[38]),"+f"(d[39])
    : "r"(alo), "r"(ahi), "r"(blo), "r"(bhi), "r"(sd), "n"(TA), "n"(TB)); }
};
template<> struct WG<96> { template<int TA, int TB> static __device__ __forceinline__ void ss(float* d, uint32_t alo, uint32_t ahi, uint32_t blo, uint32_t bhi, int sd) {
  asm volatile("{ .reg .pred p; .reg .b64 da, db; mov.b64 da, {%48,%49}; mov.b64 db, {%50,%51}; setp.ne.b32 p, %52, 0;\n"
    "wgmma.mma_async.sync.aligned.m64n96k16.f32.bf16.bf16 {%0,%1,%2,%3,%4,%5,%6,%7,%8,%9,%10,%11,%12,%13,%14,%15,%16,%17,%18,%19,%20,%21,%22,%23,%24,%25,%26,%27,%28,%29,%30,%31,%32,%33,%34,%35,%36,%37,%38,%39,%40,%41,%42,%43,%44,%45,%46,%47}, da, db, p, 1, 1, %53, %54; }"
    : "+f"(d[0]),"+f"(d[1]),"+f"(d[2]),"+f"(d[3]),"+f"(d[4]),"+f"(d[5]),"+f"(d[6]),"+f"(d[7]),"+f"(d[8]),"+f"(d[9]),"+f"(d[10]),"+f"(d[11]),"+f"(d[12]),"+f"(d[13]),"+f"(d[14]),"+f"(d[15]),"+f"(d[16]),"+f"(d[17]),"+f"(d[18]),"+f"(d[19]),"+f"(d[20]),"+f"(d[21]),"+f"(d[22]),"+f"(d[23]),"+f"(d[24]),"+f"(d[25]),"+f"(d[26]),"+f"(d[27]),"+f"(d[28]),"+f"(d[29]),"+f"(d[30]),"+f"(d[31]),"+f"(d[32]),"+f"(d[33]),"+f"(d[34]),"+f"(d[35]),"+f"(d[36]),"+f"(d[37]),"+f"(d[38]),"+f"(d[39]),"+f"(d[40]),"+f"(d[41]),"+f"(d[42]),"+f"(d[43]),"+f"(d[44]),"+f"(d[45]),"+f"(d[46]),"+f"(d[47])
    : "r"(alo), "r"(ahi), "r"(blo), "r"(bhi), "r"(sd), "n"(TA), "n"(TB)); }
};
template<> struct WG<112> { template<int TA, int TB> static __device__ __forceinline__ void ss(float* d, uint32_t alo, uint32_t ahi, uint32_t blo, uint32_t bhi, int sd) {
  asm volatile("{ .reg .pred p; .reg .b64 da, db; mov.b64 da, {%56,%57}; mov.b64 db, {%58,%59}; setp.ne.b32 p, %60, 0;\n"
    "wgmma.mma_async.sync.aligned.m64n112k16.f32.bf16.bf16 {%0,%1,%2,%3,%4,%5,%6,%7,%8,%9,%10,%11,%12,%13,%14,%15,%16,%17,%18,%19,%20,%21,%22,%23,%24,%25,%26,%27,%28,%29,%30,%31,%32,%33,%34,%35,%36,%37,%38,%39,%40,%41,%42,%43,%44,%45,%46,%47,%48,%49,%50,%51,%52,%53,%54,%55}, da, db, p, 1, 1, %61, %62; }"
    : "+f"(d[0]),"+f"(d[1]),"+f"(d[2]),"+f"(d[3]),"+f"(d[4]),"+f"(d[5]),"+f"(d[6]),"+f"(d[7]),"+f"(d[8]),"+f"(d[9]),"+f"(d[10]),"+f"(d[11]),"+f"(d[12]),"+f"(d[13]),"+f"(d[14]),"+f"(d[15]),"+f"(d[16]),"+f"(d[17]),"+f"(d[18]),"+f"(d[19]),"+f"(d[20]),"+f"(d[21]),"+f"(d[22]),"+f"(d[23]),"+f"(d[24]),"+f"(d[25]),"+f"(d[26]),"+f"(d[27]),"+f"(d[28]),"+f"(d[29]),"+f"(d[30]),"+f"(d[31]),"+f"(d[32]),"+f"(d[33]),"+f"(d[34]),"+f"(d[35]),"+f"(d[36]),"+f"(d[37]),"+f"(d[38]),"+f"(d[39]),"+f"(d[40]),"+f"(d[41]),"+f"(d[42]),"+f"(d[43]),"+f"(d[44]),"+f"(d[45]),"+f"(d[46]),"+f"(d[47]),"+f"(d[48]),"+f"(d[49]),"+f"(d[50]),"+f"(d[51]),"+f"(d[52]),"+f"(d[53]),"+f"(d[54]),"+f"(d[55])
    : "r"(alo), "r"(ahi), "r"(blo), "r"(bhi), "r"(sd), "n"(TA), "n"(TB)); }
};
template<> struct WG<128> { template<int TA, int TB> static __device__ __forceinline__ void ss(float* d, uint32_t alo, uint32_t ahi, uint32_t blo, uint32_t bhi, int sd) {
  asm volatile("{ .reg .pred p; .reg .b64 da, db; mov.b64 da, {%64,%65}; mov.b64 db, {%66,%67}; setp.ne.b32 p, %68, 0;\n"
    "wgmma.mma_async.sync.aligned.m64n128k16.f32.bf16.bf16 {%0,%1,%2,%3,%4,%5,%6,%7,%8,%9,%10,%11,%12,%13,%14,%15,%16,%17,%18,%19,%20,%21,%22,%23,%24,%25,%26,%27,%28,%29,%30,%31,%32,%33,%34,%35,%36,%37,%38,%39,%40,%41,%42,%43,%44,%45,%46,%47,%48,%49,%50,%51,%52,%53,%54,%55,%56,%57,%58,%59,%60,%61,%62,%63}, da, db, p, 1, 1, %69, %70; }"
    : "+f"(d[0]),"+f"(d[1]),"+f"(d[2]),"+f"(d[3]),"+f"(d[4]),"+f"(d[5]),"+f"(d[6]),"+f"(d[7]),"+f"(d[8]),"+f"(d[9]),"+f"(d[10]),"+f"(d[11]),"+f"(d[12]),"+f"(d[13]),"+f"(d[14]),"+f"(d[15]),"+f"(d[16]),"+f"(d[17]),"+f"(d[18]),"+f"(d[19]),"+f"(d[20]),"+f"(d[21]),"+f"(d[22]),"+f"(d[23]),"+f"(d[24]),"+f"(d[25]),"+f"(d[26]),"+f"(d[27]),"+f"(d[28]),"+f"(d[29]),"+f"(d[30]),"+f"(d[31]),"+f"(d[32]),"+f"(d[33]),"+f"(d[34]),"+f"(d[35]),"+f"(d[36]),"+f"(d[37]),"+f"(d[38]),"+f"(d[39]),"+f"(d[40]),"+f"(d[41]),"+f"(d[42]),"+f"(d[43]),"+f"(d[44]),"+f"(d[45]),"+f"(d[46]),"+f"(d[47]),"+f"(d[48]),"+f"(d[49]),"+f"(d[50]),"+f"(d[51]),"+f"(d[52]),"+f"(d[53]),"+f"(d[54]),"+f"(d[55]),"+f"(d[56]),"+f"(d[57]),"+f"(d[58]),"+f"(d[59]),"+f"(d[60]),"+f"(d[61]),"+f"(d[62]),"+f"(d[63])
    : "r"(alo), "r"(ahi), "r"(blo), "r"(bhi), "r"(sd), "n"(TA), "n"(TB)); }
  template<int TB> static __device__ __forceinline__ void rs(float* d, uint32_t a0, uint32_t a1, uint32_t a2, uint32_t a3, uint32_t blo, uint32_t bhi, int sd) {
  asm volatile("{ .reg .pred p; .reg .b64 db; mov.b64 db, {%68,%69}; setp.ne.b32 p, %71, 0;\n"
    "wgmma.mma_async.sync.aligned.m64n128k16.f32.bf16.bf16 {%0,%1,%2,%3,%4,%5,%6,%7,%8,%9,%10,%11,%12,%13,%14,%15,%16,%17,%18,%19,%20,%21,%22,%23,%24,%25,%26,%27,%28,%29,%30,%31,%32,%33,%34,%35,%36,%37,%38,%39,%40,%41,%42,%43,%44,%45,%46,%47,%48,%49,%50,%51,%52,%53,%54,%55,%56,%57,%58,%59,%60,%61,%62,%63}, {%64,%65,%66,%67}, db, p, 1, 1, %70; }"
    : "+f"(d[0]),"+f"(d[1]),"+f"(d[2]),"+f"(d[3]),"+f"(d[4]),"+f"(d[5]),"+f"(d[6]),"+f"(d[7]),"+f"(d[8]),"+f"(d[9]),"+f"(d[10]),"+f"(d[11]),"+f"(d[12]),"+f"(d[13]),"+f"(d[14]),"+f"(d[15]),"+f"(d[16]),"+f"(d[17]),"+f"(d[18]),"+f"(d[19]),"+f"(d[20]),"+f"(d[21]),"+f"(d[22]),"+f"(d[23]),"+f"(d[24]),"+f"(d[25]),"+f"(d[26]),"+f"(d[27]),"+f"(d[28]),"+f"(d[29]),"+f"(d[30]),"+f"(d[31]),"+f"(d[32]),"+f"(d[33]),"+f"(d[34]),"+f"(d[35]),"+f"(d[36]),"+f"(d[37]),"+f"(d[38]),"+f"(d[39]),"+f"(d[40]),"+f"(d[41]),"+f"(d[42]),"+f"(d[43]),"+f"(d[44]),"+f"(d[45]),"+f"(d[46]),"+f"(d[47]),"+f"(d[48]),"+f"(d[49]),"+f"(d[50]),"+f"(d[51]),"+f"(d[52]),"+f"(d[53]),"+f"(d[54]),"+f"(d[55]),"+f"(d[56]),"+f"(d[57]),"+f"(d[58]),"+f"(d[59]),"+f"(d[60]),"+f"(d[61]),"+f"(d[62]),"+f"(d[63])
    : "r"(a0), "r"(a1), "r"(a2), "r"(a3), "r"(blo), "r"(bhi), "n"(TB), "r"(sd)); }
};
template<> struct WG<144> { template<int TA, int TB> static __device__ __forceinline__ void ss(float* d, uint32_t alo, uint32_t ahi, uint32_t blo, uint32_t bhi, int sd) {
  asm volatile("{ .reg .pred p; .reg .b64 da, db; mov.b64 da, {%72,%73}; mov.b64 db, {%74,%75}; setp.ne.b32 p, %76, 0;\n"
    "wgmma.mma_async.sync.aligned.m64n144k16.f32.bf16.bf16 {%0,%1,%2,%3,%4,%5,%6,%7,%8,%9,%10,%11,%12,%13,%14,%15,%16,%17,%18,%19,%20,%21,%22,%23,%24,%25,%26,%27,%28,%29,%30,%31,%32,%33,%34,%35,%36,%37,%38,%39,%40,%41,%42,%43,%44,%45,%46,%47,%48,%49,%50,%51,%52,%53,%54,%55,%56,%57,%58,%59,%60,%61,%62,%63,%64,%65,%66,%67,%68,%69,%70,%71}, da, db, p, 1, 1, %77, %78; }"
    : "+f"(d[0]),"+f"(d[1]),"+f"(d[2]),"+f"(d[3]),"+f"(d[4]),"+f"(d[5]),"+f"(d[6]),"+f"(d[7]),"+f"(d[8]),"+f"(d[9]),"+f"(d[10]),"+f"(d[11]),"+f"(d[12]),"+f"(d[13]),"+f"(d[14]),"+f"(d[15]),"+f"(d[16]),"+f"(d[17]),"+f"(d[18]),"+f"(d[19]),"+f"(d[20]),"+f"(d[21]),"+f"(d[22]),"+f"(d[23]),"+f"(d[24]),"+f"(d[25]),"+f"(d[26]),"+f"(d[27]),"+f"(d[28]),"+f"(d[29]),"+f"(d[30]),"+f"(d[31]),"+f"(d[32]),"+f"(d[33]),"+f"(d[34]),"+f"(d[35]),"+f"(d[36]),"+f"(d[37]),"+f"(d[38]),"+f"(d[39]),"+f"(d[40]),"+f"(d[41]),"+f"(d[42]),"+f"(d[43]),"+f"(d[44]),"+f"(d[45]),"+f"(d[46]),"+f"(d[47]),"+f"(d[48]),"+f"(d[49]),"+f"(d[50]),"+f"(d[51]),"+f"(d[52]),"+f"(d[53]),"+f"(d[54]),"+f"(d[55]),"+f"(d[56]),"+f"(d[57]),"+f"(d[58]),"+f"(d[59]),"+f"(d[60]),"+f"(d[61]),"+f"(d[62]),"+f"(d[63]),"+f"(d[64]),"+f"(d[65]),"+f"(d[66]),"+f"(d[67]),"+f"(d[68]),"+f"(d[69]),"+f"(d[70]),"+f"(d[71])
    : "r"(alo), "r"(ahi), "r"(blo), "r"(bhi), "r"(sd), "n"(TA), "n"(TB)); }
};
template<> struct WG<160> { template<int TA, int TB> static __device__ __forceinline__ void ss(float* d, uint32_t alo, uint32_t ahi, uint32_t blo, uint32_t bhi, int sd) {
  asm volatile("{ .reg .pred p; .reg .b64 da, db; mov.b64 da, {%80,%81}; mov.b64 db, {%82,%83}; setp.ne.b32 p, %84, 0;\n"
    "wgmma.mma_async.sync.aligned.m64n160k16.f32.bf16.bf16 {%0,%1,%2,%3,%4,%5,%6,%7,%8,%9,%10,%11,%12,%13,%14,%15,%16,%17,%18,%19,%20,%21,%22,%23,%24,%25,%26,%27,%28,%29,%30,%31,%32,%33,%34,%35,%36,%37,%38,%39,%40,%41,%42,%43,%44,%45,%46,%47,%48,%49,%50,%51,%52,%53,%54,%55,%56,%57,%58,%59,%60,%61,%62,%63,%64,%65,%66,%67,%68,%69,%70,%71,%72,%73,%74,%75,%76,%77,%78,%79}, da, db, p, 1, 1, %85, %86; }"
    : "+f"(d[0]),"+f"(d[1]),"+f"(d[2]),"+f"(d[3]),"+f"(d[4]),"+f"(d[5]),"+f"(d[6]),"+f"(d[7]),"+f"(d[8]),"+f"(d[9]),"+f"(d[10]),"+f"(d[11]),"+f"(d[12]),"+f"(d[13]),"+f"(d[14]),"+f"(d[15]),"+f"(d[16]),"+f"(d[17]),"+f"(d[18]),"+f"(d[19]),"+f"(d[20]),"+f"(d[21]),"+f"(d[22]),"+f"(d[23]),"+f"(d[24]),"+f"(d[25]),"+f"(d[26]),"+f"(d[27]),"+f"(d[28]),"+f"(d[29]),"+f"(d[30]),"+f"(d[31]),"+f"(d[32]),"+f"(d[33]),"+f"(d[34]),"+f"(d[35]),"+f"(d[36]),"+f"(d[37]),"+f"(d[38]),"+f"(d[39]),"+f"(d[40]),"+f"(d[41]),"+f"(d[42]),"+f"(d[43]),"+f"(d[44]),"+f"(d[45]),"+f"(d[46]),"+f"(d[47]),"+f"(d[48]),"+f"(d[49]),"+f"(d[50]),"+f"(d[51]),"+f"(d[52]),"+f"(d[53]),"+f"(d[54]),"+f"(d[55]),"+f"(d[56]),"+f"(d[57]),"+f"(d[58]),"+f"(d[59]),"+f"(d[60]),"+f"(d[61]),"+f"(d[62]),"+f"(d[63]),"+f"(d[64]),"+f"(d[65]),"+f"(d[66]),"+f"(d[67]),"+f"(d[68]),"+f"(d[69]),"+f"(d[70]),"+f"(d[71]),"+f"(d[72]),"+f"(d[73]),"+f"(d[74]),"+f"(d[75]),"+f"(d[76]),"+f"(d[77]),"+f"(d[78]),"+f"(d[79])
    : "r"(alo), "r"(ahi), "r"(blo), "r"(bhi), "r"(sd), "n"(TA), "n"(TB)); }
  template<int TB> static __device__ __forceinline__ void rs(float* d, uint32_t a0, uint32_t a1, uint32_t a2, uint32_t a3, uint32_t blo, uint32_t bhi, int sd) {
  asm volatile("{ .reg .pred p; .reg .b64 db; mov.b64 db, {%84,%85}; setp.ne.b32 p, %87, 0;\n"
    "wgmma.mma_async.sync.aligned.m64n160k16.f32.bf16.bf16 {%0,%1,%2,%3,%4,%5,%6,%7,%8,%9,%10,%11,%12,%13,%14,%15,%16,%17,%18,%19,%20,%21,%22,%23,%24,%25,%26,%27,%28,%29,%30,%31,%32,%33,%34,%35,%36,%37,%38,%39,%40,%41,%42,%43,%44,%45,%46,%47,%48,%49,%50,%51,%52,%53,%54,%55,%56,%57,%58,%59,%60,%61,%62,%63,%64,%65,%66,%67,%68,%69,%70,%71,%72,%73,%74,%75,%76,%77,%78,%79}, {%80,%81,%82,%83}, db, p, 1, 1, %86; }"
    : "+f"(d[0]),"+f"(d[1]),"+f"(d[2]),"+f"(d[3]),"+f"(d[4]),"+f"(d[5]),"+f"(d[6]),"+f"(d[7]),"+f"(d[8]),"+f"(d[9]),"+f"(d[10]),"+f"(d[11]),"+f"(d[12]),"+f"(d[13]),"+f"(d[14]),"+f"(d[15]),"+f"(d[16]),"+f"(d[17]),"+f"(d[18]),"+f"(d[19]),"+f"(d[20]),"+f"(d[21]),"+f"(d[22]),"+f"(d[23]),"+f"(d[24]),"+f"(d[25]),"+f"(d[26]),"+f"(d[27]),"+f"(d[28]),"+f"(d[29]),"+f"(d[30]),"+f"(d[31]),"+f"(d[32]),"+f"(d[33]),"+f"(d[34]),"+f"(d[35]),"+f"(d[36]),"+f"(d[37]),"+f"(d[38]),"+f"(d[39]),"+f"(d[40]),"+f"(d[41]),"+f"(d[42]),"+f"(d[43]),"+f"(d[44]),"+f"(d[45]),"+f"(d[46]),"+f"(d[47]),"+f"(d[48]),"+f"(d[49]),"+f"(d[50]),"+f"(d[51]),"+f"(d[52]),"+f"(d[53]),"+f"(d[54]),"+f"(d[55]),"+f"(d[56]),"+f"(d[57]),"+f"(d[58]),"+f"(d[59]),"+f"(d[60]),"+f"(d[61]),"+f"(d[62]),"+f"(d[63]),"+f"(d[64]),"+f"(d[65]),"+f"(d[66]),"+f"(d[67]),"+f"(d[68]),"+f"(d[69]),"+f"(d[70]),"+f"(d[71]),"+f"(d[72]),"+f"(d[73]),"+f"(d[74]),"+f"(d[75]),"+f"(d[76]),"+f"(d[77]),"+f"(d[78]),"+f"(d[79])
    : "r"(a0), "r"(a1), "r"(a2), "r"(a3), "r"(blo), "r"(bhi), "n"(TB), "r"(sd)); }
};
template<> struct WG<176> { template<int TA, int TB> static __device__ __forceinline__ void ss(float* d, uint32_t alo, uint32_t ahi, uint32_t blo, uint32_t bhi, int sd) {
  asm volatile("{ .reg .pred p; .reg .b64 da, db; mov.b64 da, {%88,%89}; mov.b64 db, {%90,%91}; setp.ne.b32 p, %92, 0;\n"
    "wgmma.mma_async.sync.aligned.m64n176k16.f32.bf16.bf16 {%0,%1,%2,%3,%4,%5,%6,%7,%8,%9,%10,%11,%12,%13,%14,%15,%16,%17,%18,%19,%20,%21,%22,%23,%24,%25,%26,%27,%28,%29,%30,%31,%32,%33,%34,%35,%36,%37,%38,%39,%40,%41,%42,%43,%44,%45,%46,%47,%48,%49,%50,%51,%52,%53,%54,%55,%56,%57,%58,%59,%60,%61,%62,%63,%64,%65,%66,%67,%68,%69,%70,%71,%72,%73,%74,%75,%76,%77,%78,%79,%80,%81,%82,%83,%84,%85,%86,%87}, da, db, p, 1, 1, %93, %94; }"
    : "+f"(d[0]),"+f"(d[1]),"+f"(d[2]),"+f"(d[3]),"+f"(d[4]),"+f"(d[5]),"+f"(d[6]),"+f"(d[7]),"+f"(d[8]),"+f"(d[9]),"+f"(d[10]),"+f"(d[11]),"+f"(d[12]),"+f"(d[13]),"+f"(d[14]),"+f"(d[15]),"+f"(d[16]),"+f"(d[17]),"+f"(d[18]),"+f"(d[19]),"+f"(d[20]),"+f"(d[21]),"+f"(d[22]),"+f"(d[23]),"+f"(d[24]),"+f"(d[25]),"+f"(d[26]),"+f"(d[27]),"+f"(d[28]),"+f"(d[29]),"+f"(d[30]),"+f"(d[31]),"+f"(d[32]),"+f"(d[33]),"+f"(d[34]),"+f"(d[35]),"+f"(d[36]),"+f"(d[37]),"+f"(d[38]),"+f"(d[39]),"+f"(d[40]),"+f"(d[41]),"+f"(d[42]),"+f"(d[43]),"+f"(d[44]),"+f"(d[45]),"+f"(d[46]),"+f"(d[47]),"+f"(d[48]),"+f"(d[49]),"+f"(d[50]),"+f"(d[51]),"+f"(d[52]),"+f"(d[53]),"+f"(d[54]),"+f"(d[55]),"+f"(d[56]),"+f"(d[57]),"+f"(d[58]),"+f"(d[59]),"+f"(d[60]),"+f"(d[61]),"+f"(d[62]),"+f"(d[63]),"+f"(d[64]),"+f"(d[65]),"+f"(d[66]),"+f"(d[67]),"+f"(d[68]),"+f"(d[69]),"+f"(d[70]),"+f"(d[71]),"+f"(d[72]),"+f"(d[73]),"+f"(d[74]),"+f"(d[75]),"+f"(d[76]),"+f"(d[77]),"+f"(d[78]),"+f"(d[79]),"+f"(d[80]),"+f"(d[81]),"+f"(d[82]),"+f"(d[83]),"+f"(d[84]),"+f"(d[85]),"+f"(d[86]),"+f"(d[87])
    : "r"(alo), "r"(ahi), "r"(blo), "r"(bhi), "r"(sd), "n"(TA), "n"(TB)); }
};
template<> struct WG<192> { template<int TA, int TB> static __device__ __forceinline__ void ss(float* d, uint32_t alo, uint32_t ahi, uint32_t blo, uint32_t bhi, int sd) {
  asm volatile("{ .reg .pred p; .reg .b64 da, db; mov.b64 da, {%96,%97}; mov.b64 db, {%98,%99}; setp.ne.b32 p, %100, 0;\n"
    "wgmma.mma_async.sync.aligned.m64n192k16.f32.bf16.bf16 {%0,%1,%2,%3,%4,%5,%6,%7,%8,%9,%10,%11,%12,%13,%14,%15,%16,%17,%18,%19,%20,%21,%22,%23,%24,%25,%26,%27,%28,%29,%30,%31,%32,%33,%34,%35,%36,%37,%38,%39,%40,%41,%42,%43,%44,%45,%46,%47,%48,%49,%50,%51,%52,%53,%54,%55,%56,%57,%58,%59,%60,%61,%62,%63,%64,%65,%66,%67,%68,%69,%70,%71,%72,%73,%74,%75,%76,%77,%78,%79,%80,%81,%82,%83,%84,%85,%86,%87,%88,%89,%90,%91,%92,%93,%94,%95}, da, db, p, 1, 1, %101, %102; }"
    : "+f"(d[0]),"+f"(d[1]),"+f"(d[2]),"+f"(d[3]),"+f"(d[4]),"+f"(d[5]),"+f"(d[6]),"+f"(d[7]),"+f"(d[8]),"+f"(d[9]),"+f"(d[10]),"+f"(d[11]),"+f"(d[12]),"+f"(d[13]),"+f"(d[14]),"+f"(d[15]),"+f"(d[16]),"+f"(d[17]),"+f"(d[18]),"+f"(d[19]),"+f"(d[20]),"+f"(d[21]),"+f"(d[22]),"+f"(d[23]),"+f"(d[24]),"+f"(d[25]),"+f"(d[26]),"+f"(d[27]),"+f"(d[28]),"+f"(d[29]),"+f"(d[30]),"+f"(d[31]),"+f"(d[32]),"+f"(d[33]),"+f"(d[34]),"+f"(d[35]),"+f"(d[36]),"+f"(d[37]),"+f"(d[38]),"+f"(d[39]),"+f"(d[40]),"+f"(d[41]),"+f"(d[42]),"+f"(d[43]),"+f"(d[44]),"+f"(d[45]),"+f"(d[46]),"+f"(d[47]),"+f"(d[48]),"+f"(d[49]),"+f"(d[50]),"+f"(d[51]),"+f"(d[52]),"+f"(d[53]),"+f"(d[54]),"+f"(d[55]),"+f"(d[56]),"+f"(d[57]),"+f"(d[58]),"+f"(d[59]),"+f"(d[60]),"+f"(d[61]),"+f"(d[62]),"+f"(d[63]),"+f"(d[64]),"+f"(d[65]),"+f"(d[66]),"+f"(d[67]),"+f"(d[68]),"+f"(d[69]),"+f"(d[70]),"+f"(d[71]),"+f"(d[72]),"+f"(d[73]),"+f"(d[74]),"+f"(d[75]),"+f"(d[76]),"+f"(d[77]),"+f"(d[78]),"+f"(d[79]),"+f"(d[80]),"+f"(d[81]),"+f"(d[82]),"+f"(d[83]),"+f"(d[84]),"+f"(d[85]),"+f"(d[86]),"+f"(d[87]),"+f"(d[88]),"+f"(d[89]),"+f"(d[90]),"+f"(d[91]),"+f"(d[92]),"+f"(d[93]),"+f"(d[94]),"+f"(d[95])
    : "r"(alo), "r"(ahi), "r"(blo), "r"(bhi), "r"(sd), "n"(TA), "n"(TB)); }
};
template<> struct WG<208> { template<int TA, int TB> static __device__ __forceinline__ void ss(float* d, uint32_t alo, uint32_t ahi, uint32_t blo, uint32_t bhi, int sd) {
  asm volatile("{ .reg .pred p; .reg .b64 da, db; mov.b64 da, {%104,%105}; mov.b64 db, {%106,%107}; setp.ne.b32 p, %108, 0;\n"
    "wgmma.mma_async.sync.aligned.m64n208k16.f32.bf16.bf16 {%0,%1,%2,%3,%4,%5,%6,%7,%8,%9,%10,%11,%12,%13,%14,%15,%16,%17,%18,%19,%20,%21,%22,%23,%24,%25,%26,%27,%28,%29,%30,%31,%32,%33,%34,%35,%36,%37,%38,%39,%40,%41,%42,%43,%44,%45,%46,%47,%48,%49,%50,%51,%52,%53,%54,%55,%56,%57,%58,%59,%60,%61,%62,%63,%64,%65,%66,%67,%68,%69,%70,%71,%72,%73,%74,%75,%76,%77,%78,%79,%80,%81,%82,%83,%84,%85,%86,%87,%88,%89,%90,%91,%92,%93,%94,%95,%96,%97,%98,%99,%100,%101,%102,%103}, da, db, p, 1, 1, %109, %110; }"
    : "+f"(d[0]),"+f"(d[1]),"+f"(d[2]),"+f"(d[3]),"+f"(d[4]),"+f"(d[5]),"+f"(d[6]),"+f"(d[7]),"+f"(d[8]),"+f"(d[9]),"+f"(d[10]),"+f"(d[11]),"+f"(d[12]),"+f"(d[13]),"+f"(d[14]),"+f"(d[15]),"+f"(d[16]),"+f"(d[17]),"+f"(d[18]),"+f"(d[19]),"+f"(d[20]),"+f"(d[21]),"+f"(d[22]),"+f"(d[23]),"+f"(d[24]),"+f"(d[25]),"+f"(d[26]),"+f"(d[27]),"+f"(d[28]),"+f"(d[29]),"+f"(d[30]),"+f"(d[31]),"+f"(d[32]),"+f"(d[33]),"+f"(d[34]),"+f"(d[35]),"+f"(d[36]),"+f"(d[37]),"+f"(d[38]),"+f"(d[39]),"+f"(d[40]),"+f"(d[41]),"+f"(d[42]),"+f"(d[43]),"+f"(d[44]),"+f"(d[45]),"+f"(d[46]),"+f"(d[47]),"+f"(d[48]),"+f"(d[49]),"+f"(d[50]),"+f"(d[51]),"+f"(d[52]),"+f"(d[53]),"+f"(d[54]),"+f"(d[55]),"+f"(d[56]),"+f"(d[57]),"+f"(d[58]),"+f"(d[59]),"+f"(d[60]),"+f"(d[61]),"+f"(d[62]),"+f"(d[63]),"+f"(d[64]),"+f"(d[65]),"+f"(d[66]),"+f"(d[67]),"+f"(d[68]),"+f"(d[69]),"+f"(d[70]),"+f"(d[71]),"+f"(d[72]),"+f"(d[73]),"+f"(d[74]),"+f"(d[75]),"+f"(d[76]),"+f"(d[77]),"+f"(d[78]),"+f"(d[79]),"+f"(d[80]),"+f"(d[81]),"+f"(d[82]),"+f"(d[83]),"+f"(d[84]),"+f"(d[85]),"+f"(d[86]),"+f"(d[87]),"+f"(d[88]),"+f"(d[89]),"+f"(d[90]),"+f"(d[91]),"+f"(d[92]),"+f"(d[93]),"+f"(d[94]),"+f"(d[95]),"+f"(d[96]),"+f"(d[97]),"+f"(d[98]),"+f"(d[99]),"+f"(d[100]),"+f"(d[101]),"+f"(d[102]),"+f"(d[103])
    : "r"(alo), "r"(ahi), "r"(blo), "r"(bhi), "r"(sd), "n"(TA), "n"(TB)); }
};
template<> struct WG<224> { template<int TA, int TB> static __device__ __forceinline__ void ss(float* d, uint32_t alo, uint32_t ahi, uint32_t blo, uint32_t bhi, int sd) {
  asm volatile("{ .reg .pred p; .reg .b64 da, db; mov.b64 da, {%112,%113}; mov.b64 db, {%114,%115}; setp.ne.b32 p, %116, 0;\n"
    "wgmma.mma_async.sync.aligned.m64n224k16.f32.bf16.bf16 {%0,%1,%2,%3,%4,%5,%6,%7,%8,%9,%10,%11,%12,%13,%14,%15,%16,%17,%18,%19,%20,%21,%22,%23,%24,%25,%26,%27,%28,%29,%30,%31,%32,%33,%34,%35,%36,%37,%38,%39,%40,%41,%42,%43,%44,%45,%46,%47,%48,%49,%50,%51,%52,%53,%54,%55,%56,%57,%58,%59,%60,%61,%62,%63,%64,%65,%66,%67,%68,%69,%70,%71,%72,%73,%74,%75,%76,%77,%78,%79,%80,%81,%82,%83,%84,%85,%86,%87,%88,%89,%90,%91,%92,%93,%94,%95,%96,%97,%98,%99,%100,%101,%102,%103,%104,%105,%106,%107,%108,%109,%110,%111}, da, db, p, 1, 1, %117, %118; }"
    : "+f"(d[0]),"+f"(d[1]),"+f"(d[2]),"+f"(d[3]),"+f"(d[4]),"+f"(d[5]),"+f"(d[6]),"+f"(d[7]),"+f"(d[8]),"+f"(d[9]),"+f"(d[10]),"+f"(d[11]),"+f"(d[12]),"+f"(d[13]),"+f"(d[14]),"+f"(d[15]),"+f"(d[16]),"+f"(d[17]),"+f"(d[18]),"+f"(d[19]),"+f"(d[20]),"+f"(d[21]),"+f"(d[22]),"+f"(d[23]),"+f"(d[24]),"+f"(d[25]),"+f"(d[26]),"+f"(d[27]),"+f"(d[28]),"+f"(d[29]),"+f"(d[30]),"+f"(d[31]),"+f"(d[32]),"+f"(d[33]),"+f"(d[34]),"+f"(d[35]),"+f"(d[36]),"+f"(d[37]),"+f"(d[38]),"+f"(d[39]),"+f"(d[40]),"+f"(d[41]),"+f"(d[42]),"+f"(d[43]),"+f"(d[44]),"+f"(d[45]),"+f"(d[46]),"+f"(d[47]),"+f"(d[48]),"+f"(d[49]),"+f"(d[50]),"+f"(d[51]),"+f"(d[52]),"+f"(d[53]),"+f"(d[54]),"+f"(d[55]),"+f"(d[56]),"+f"(d[57]),"+f"(d[58]),"+f"(d[59]),"+f"(d[60]),"+f"(d[61]),"+f"(d[62]),"+f"(d[63]),"+f"(d[64]),"+f"(d[65]),"+f"(d[66]),"+f"(d[67]),"+f"(d[68]),"+f"(d[69]),"+f"(d[70]),"+f"(d[71]),"+f"(d[72]),"+f"(d[73]),"+f"(d[74]),"+f"(d[75]),"+f"(d[76]),"+f"(d[77]),"+f"(d[78]),"+f"(d[79]),"+f"(d[80]),"+f"(d[81]),"+f"(d[82]),"+f"(d[83]),"+f"(d[84]),"+f"(d[85]),"+f"(d[86]),"+f"(d[87]),"+f"(d[88]),"+f"(d[89]),"+f"(d[90]),"+f"(d[91]),"+f"(d[92]),"+f"(d[93]),"+f"(d[94]),"+f"(d[95]),"+f"(d[96]),"+f"(d[97]),"+f"(d[98]),"+f"(d[99]),"+f"(d[100]),"+f"(d[101]),"+f"(d[102]),"+f"(d[103]),"+f"(d[104]),"+f"(d[105]),"+f"(d[106]),"+f"(d[107]),"+f"(d[108]),"+f"(d[109]),"+f"(d[110]),"+f"(d[111])
    : "r"(alo), "r"(ahi), "r"(blo), "r"(bhi), "r"(sd), "n"(TA), "n"(TB)); }
};
template<> struct WG<240> { template<int TA, int TB> static __device__ __forceinline__ void ss(float* d, uint32_t alo, uint32_t ahi, uint32_t blo, uint32_t bhi, int sd) {
  asm volatile("{ .reg .pred p; .reg .b64 da, db; mov.b64 da, {%120,%121}; mov.b64 db, {%122,%123}; setp.ne.b32 p, %124, 0;\n"
    "wgmma.mma_async.sync.aligned.m64n240k16.f32.bf16.bf16 {%0,%1,%2,%3,%4,%5,%6,%7,%8,%9,%10,%11,%12,%13,%14,%15,%16,%17,%18,%19,%20,%21,%22,%23,%24,%25,%26,%27,%28,%29,%30,%31,%32,%33,%34,%35,%36,%37,%38,%39,%40,%41,%42,%43,%44,%45,%46,%47,%48,%49,%50,%51,%52,%53,%54,%55,%56,%57,%58,%59,%60,%61,%62,%63,%64,%65,%66,%67,%68,%69,%70,%71,%72,%73,%74,%75,%76,%77,%78,%79,%80,%81,%82,%83,%84,%85,%86,%87,%88,%89,%90,%91,%92,%93,%94,%95,%96,%97,%98,%99,%100,%101,%102,%103,%104,%105,%106,%107,%108,%109,%110,%111,%112,%113,%114,%115,%116,%117,%118,%119}, da, db, p, 1, 1, %125, %126; }"
    : "+f"(d[0]),"+f"(d[1]),"+f"(d[2]),"+f"(d[3]),"+f"(d[4]),"+f"(d[5]),"+f"(d[6]),"+f"(d[7]),"+f"(d[8]),"+f"(d[9]),"+f"(d[10]),"+f"(d[11]),"+f"(d[12]),"+f"(d[13]),"+f"(d[14]),"+f"(d[15]),"+f"(d[16]),"+f"(d[17]),"+f"(d[18]),"+f"(d[19]),"+f"(d[20]),"+f"(d[21]),"+f"(d[22]),"+f"(d[23]),"+f"(d[24]),"+f"(d[25]),"+f"(d[26]),"+f"(d[27]),"+f"(d[28]),"+f"(d[29]),"+f"(d[30]),"+f"(d[31]),"+f"(d[32]),"+f"(d[33]),"+f"(d[34]),"+f"(d[35]),"+f"(d[36]),"+f"(d[37]),"+f"(d[38]),"+f"(d[39]),"+f"(d[40]),"+f"(d[41]),"+f"(d[42]),"+f"(d[43]),"+f"(d[44]),"+f"(d[45]),"+f"(d[46]),"+f"(d[47]),"+f"(d[48]),"+f"(d[49]),"+f"(d[50]),"+f"(d[51]),"+f"(d[52]),"+f"(d[53]),"+f"(d[54]),"+f"(d[55]),"+f"(d[56]),"+f"(d[57]),"+f"(d[58]),"+f"(d[59]),"+f"(d[60]),"+f"(d[61]),"+f"(d[62]),"+f"(d[63]),"+f"(d[64]),"+f"(d[65]),"+f"(d[66]),"+f"(d[67]),"+f"(d[68]),"+f"(d[69]),"+f"(d[70]),"+f"(d[71]),"+f"(d[72]),"+f"(d[73]),"+f"(d[74]),"+f"(d[75]),"+f"(d[76]),"+f"(d[77]),"+f"(d[78]),"+f"(d[79]),"+f"(d[80]),"+f"(d[81]),"+f"(d[82]),"+f"(d[83]),"+f"(d[84]),"+f"(d[85]),"+f"(d[86]),"+f"(d[87]),"+f"(d[88]),"+f"(d[89]),"+f"(d[90]),"+f"(d[91]),"+f"(d[92]),"+f"(d[93]),"+f"(d[94]),"+f"(d[95]),"+f"(d[96]),"+f"(d[97]),"+f"(d[98]),"+f"(d[99]),"+f"(d[100]),"+f"(d[101]),"+f"(d[102]),"+f"(d[103]),"+f"(d[104]),"+f"(d[105]),"+f"(d[106]),"+f"(d[107]),"+f"(d[108]),"+f"(d[109]),"+f"(d[110]),"+f"(d[111]),"+f"(d[112]),"+f"(d[113]),"+f"(d[114]),"+f"(d[115]),"+f"(d[116]),"+f"(d[117]),"+f"(d[118]),"+f"(d[119])
    : "r"(alo), "r"(ahi), "r"(blo), "r"(bhi), "r"(sd), "n"(TA), "n"(TB)); }
};
template<> struct WG<256> { template<int TA, int TB> static __device__ __forceinline__ void ss(float* d, uint32_t alo, uint32_t ahi, uint32_t blo, uint32_t bhi, int sd) {
  asm volatile("{ .reg .pred p; .reg .b64 da, db; mov.b64 da, {%128,%129}; mov.b64 db, {%130,%131}; setp.ne.b32 p, %132, 0;\n"
    "wgmma.mma_async.sync.aligned.m64n256k16.f32.bf16.bf16 {%0,%1,%2,%3,%4,%5,%6,%7,%8,%9,%10,%11,%12,%13,%14,%15,%16,%17,%18,%19,%20,%21,%22,%23,%24,%25,%26,%27,%28,%29,%30,%31,%32,%33,%34,%35,%36,%37,%38,%39,%40,%41,%42,%43,%44,%45,%46,%47,%48,%49,%50,%51,%52,%53,%54,%55,%56,%57,%58,%59,%60,%61,%62,%63,%64,%65,%66,%67,%68,%69,%70,%71,%72,%73,%74,%75,%76,%77,%78,%79,%80,%81,%82,%83,%84,%85,%86,%87,%88,%89,%90,%91,%92,%93,%94,%95,%96,%97,%98,%99,%100,%101,%102,%103,%104,%105,%106,%107,%108,%109,%110,%111,%112,%113,%114,%115,%116,%117,%118,%119,%120,%121,%122,%123,%124,%125,%126,%127}, da, db, p, 1, 1, %133, %134; }"
    : "+f"(d[0]),"+f"(d[1]),"+f"(d[2]),"+f"(d[3]),"+f"(d[4]),"+f"(d[5]),"+f"(d[6]),"+f"(d[7]),"+f"(d[8]),"+f"(d[9]),"+f"(d[10]),"+f"(d[11]),"+f"(d[12]),"+f"(d[13]),"+f"(d[14]),"+f"(d[15]),"+f"(d[16]),"+f"(d[17]),"+f"(d[18]),"+f"(d[19]),"+f"(d[20]),"+f"(d[21]),"+f"(d[22]),"+f"(d[23]),"+f"(d[24]),"+f"(d[25]),"+f"(d[26]),"+f"(d[27]),"+f"(d[28]),"+f"(d[29]),"+f"(d[30]),"+f"(d[31]),"+f"(d[32]),"+f"(d[33]),"+f"(d[34]),"+f"(d[35]),"+f"(d[36]),"+f"(d[37]),"+f"(d[38]),"+f"(d[39]),"+f"(d[40]),"+f"(d[41]),"+f"(d[42]),"+f"(d[43]),"+f"(d[44]),"+f"(d[45]),"+f"(d[46]),"+f"(d[47]),"+f"(d[48]),"+f"(d[49]),"+f"(d[50]),"+f"(d[51]),"+f"(d[52]),"+f"(d[53]),"+f"(d[54]),"+f"(d[55]),"+f"(d[56]),"+f"(d[57]),"+f"(d[58]),"+f"(d[59]),"+f"(d[60]),"+f"(d[61]),"+f"(d[62]),"+f"(d[63]),"+f"(d[64]),"+f"(d[65]),"+f"(d[66]),"+f"(d[67]),"+f"(d[68]),"+f"(d[69]),"+f"(d[70]),"+f"(d[71]),"+f"(d[72]),"+f"(d[73]),"+f"(d[74]),"+f"(d[75]),"+f"(d[76]),"+f"(d[77]),"+f"(d[78]),"+f"(d[79]),"+f"(d[80]),"+f"(d[81]),"+f"(d[82]),"+f"(d[83]),"+f"(d[84]),"+f"(d[85]),"+f"(d[86]),"+f"(d[87]),"+f"(d[88]),"+f"(d[89]),"+f"(d[90]),"+f"(d[91]),"+f"(d[92]),"+f"(d[93]),"+f"(d[94]),"+f"(d[95]),"+f"(d[96]),"+f"(d[97]),"+f"(d[98]),"+f"(d[99]),"+f"(d[100]),"+f"(d[101]),"+f"(d[102]),"+f"(d[103]),"+f"(d[104]),"+f"(d[105]),"+f"(d[106]),"+f"(d[107]),"+f"(d[108]),"+f"(d[109]),"+f"(d[110]),"+f"(d[111]),"+f"(d[112]),"+f"(d[113]),"+f"(d[114]),"+f"(d[115]),"+f"(d[116]),"+f"(d[117]),"+f"(d[118]),"+f"(d[119]),"+f"(d[120]),"+f"(d[121]),"+f"(d[122]),"+f"(d[123]),"+f"(d[124]),"+f"(d[125]),"+f"(d[126]),"+f"(d[127])
    : "r"(alo), "r"(ahi), "r"(blo), "r"(bhi), "r"(sd), "n"(TA), "n"(TB)); }
  template<int TB> static __device__ __forceinline__ void rs(float* d, uint32_t a0, uint32_t a1, uint32_t a2, uint32_t a3, uint32_t blo, uint32_t bhi, int sd) {
  asm volatile("{ .reg .pred p; .reg .b64 db; mov.b64 db, {%132,%133}; setp.ne.b32 p, %135, 0;\n"
    "wgmma.mma_async.sync.aligned.m64n256k16.f32.bf16.bf16 {%0,%1,%2,%3,%4,%5,%6,%7,%8,%9,%10,%11,%12,%13,%14,%15,%16,%17,%18,%19,%20,%21,%22,%23,%24,%25,%26,%27,%28,%29,%30,%31,%32,%33,%34,%35,%36,%37,%38,%39,%40,%41,%42,%43,%44,%45,%46,%47,%48,%49,%50,%51,%52,%53,%54,%55,%56,%57,%58,%59,%60,%61,%62,%63,%64,%65,%66,%67,%68,%69,%70,%71,%72,%73,%74,%75,%76,%77,%78,%79,%80,%81,%82,%83,%84,%85,%86,%87,%88,%89,%90,%91,%92,%93,%94,%95,%96,%97,%98,%99,%100,%101,%102,%103,%104,%105,%106,%107,%108,%109,%110,%111,%112,%113,%114,%115,%116,%117,%118,%119,%120,%121,%122,%123,%124,%125,%126,%127}, {%128,%129,%130,%131}, db, p, 1, 1, %134; }"
    : "+f"(d[0]),"+f"(d[1]),"+f"(d[2]),"+f"(d[3]),"+f"(d[4]),"+f"(d[5]),"+f"(d[6]),"+f"(d[7]),"+f"(d[8]),"+f"(d[9]),"+f"(d[10]),"+f"(d[11]),"+f"(d[12]),"+f"(d[13]),"+f"(d[14]),"+f"(d[15]),"+f"(d[16]),"+f"(d[17]),"+f"(d[18]),"+f"(d[19]),"+f"(d[20]),"+f"(d[21]),"+f"(d[22]),"+f"(d[23]),"+f"(d[24]),"+f"(d[25]),"+f"(d[26]),"+f"(d[27]),"+f"(d[28]),"+f"(d[29]),"+f"(d[30]),"+f"(d[31]),"+f"(d[32]),"+f"(d[33]),"+f"(d[34]),"+f"(d[35]),"+f"(d[36]),"+f"(d[37]),"+f"(d[38]),"+f"(d[39]),"+f"(d[40]),"+f"(d[41]),"+f"(d[42]),"+f"(d[43]),"+f"(d[44]),"+f"(d[45]),"+f"(d[46]),"+f"(d[47]),"+f"(d[48]),"+f"(d[49]),"+f"(d[50]),"+f"(d[51]),"+f"(d[52]),"+f"(d[53]),"+f"(d[54]),"+f"(d[55]),"+f"(d[56]),"+f"(d[57]),"+f"(d[58]),"+f"(d[59]),"+f"(d[60]),"+f"(d[61]),"+f"(d[62]),"+f"(d[63]),"+f"(d[64]),"+f"(d[65]),"+f"(d[66]),"+f"(d[67]),"+f"(d[68]),"+f"(d[69]),"+f"(d[70]),"+f"(d[71]),"+f"(d[72]),"+f"(d[73]),"+f"(d[74]),"+f"(d[75]),"+f"(d[76]),"+f"(d[77]),"+f"(d[78]),"+f"(d[79]),"+f"(d[80]),"+f"(d[81]),"+f"(d[82]),"+f"(d[83]),"+f"(d[84]),"+f"(d[85]),"+f"(d[86]),"+f"(d[87]),"+f"(d[88]),"+f"(d[89]),"+f"(d[90]),"+f"(d[91]),"+f"(d[92]),"+f"(d[93]),"+f"(d[94]),"+f"(d[95]),"+f"(d[96]),"+f"(d[97]),"+f"(d[98]),"+f"(d[99]),"+f"(d[100]),"+f"(d[101]),"+f"(d[102]),"+f"(d[103]),"+f"(d[104]),"+f"(d[105]),"+f"(d[106]),"+f"(d[107]),"+f"(d[108]),"+f"(d[109]),"+f"(d[110]),"+f"(d[111]),"+f"(d[112]),"+f"(d[113]),"+f"(d[114]),"+f"(d[115]),"+f"(d[116]),"+f"(d[117]),"+f"(d[118]),"+f"(d[119]),"+f"(d[120]),"+f"(d[121]),"+f"(d[122]),"+f"(d[123]),"+f"(d[124]),"+f"(d[125]),"+f"(d[126]),"+f"(d[127])
    : "r"(a0), "r"(a1), "r"(a2), "r"(a3), "r"(blo), "r"(bhi), "n"(TB), "r"(sd)); }
};

template<int T> struct Conv {
    static __device__ __forceinline__ void run(float* acc, uint32_t da, uint32_t db) {
        WG<256 - 16 * T>::template ss<0, 0>(acc, da + (T >> 2) * 512 + (T & 3) * 2, dhi(1024, 1), db + T * 16, dhi(128, 0), T != 0);
        Conv<T + 1>::run(acc, da, db);
    }
};
template<> struct Conv<16> { static __device__ __forceinline__ void run(float*, uint32_t, uint32_t) {} };

template<int Q> __device__ __forceinline__ void ffn_epi(const float* g, const float* u, uint32_t* hq, char* dst, uint32_t tm, uint32_t par, float rq0, float rq1) {
    constexpr int U = Q >> 2, i = 4 * Q;
    uint32_t* o = hq + 8 * U;
    o[Q & 3] = hmul2(pack2relu(g[i], g[i + 1]), RQE == 1 ? pack2(u[i] * rq0, u[i + 1] * rq0) : pack2(u[i], u[i + 1]));
    o[4 + (Q & 3)] = hmul2(pack2relu(g[i + 2], g[i + 3]), RQE == 1 ? pack2(u[i + 2] * rq1, u[i + 3] * rq1) : pack2(u[i + 2], u[i + 3]));
    asm volatile("" : "+r"(o[Q & 3]), "+r"(o[4 + (Q & 3)]) :: "memory");
    if ((Q & 3) == 0) {
        stg_tag<0>(dst + U * 8192, o, tm, par);
        stg_tag<1>(dst + U * 8192 + 512, o + 4, tm, par);
    }
}
__device__ __forceinline__ uint32_t tagged(float x, uint32_t tag) { return (__float_as_uint(x) & ~7u) | (tag & 7u); }
__device__ __forceinline__ uint32_t split2(float x) { const float h = bfround(x); return pack2(h, x - h); }
__device__ __forceinline__ float rsqrt_(float x) { float r; asm("rsqrt.approx.ftz.f32 %0, %1;" : "=f"(r) : "f"(x)); return r; }
__device__ __forceinline__ void acc_stat(float& s, float& q, uint32_t w) { const float a = bflo(w), c = bfhi(w); s += a; q = fmaf(a, a, q); s += c; q = fmaf(c, c, q); }
template<int I, int N, typename F> __device__ __forceinline__ void static_for(F&& f) {
    if constexpr (I < N) { f(std::integral_constant<int, I>{}); static_for<I + 1, N>(f); }
}

__device__ __forceinline__ int mod_col(int i, int s) {
    const int g = 4 * i + s - 40;
    return i < 10 ? ((s & 1) ? 1280 + 1280 * (i & 1) : 640 * (i & 1)) + (i >> 1) * 128 + (s >> 1) * 64 : (g < 10 ? 1920 : 2560) + g * 64;
}
__device__ __forceinline__ uint32_t silu2(uint32_t w) {
    const float a0 = bflo(w), a1 = bfhi(w);
    return pack2(__fdividef(a0, 1.f + __expf(-a0)), __fdividef(a1, 1.f + __expf(-a1)));
}

struct Maps { CUtensorMap k, v, q, y, g1, u1, g2, u2, wd, wn, wm, out; };
struct Ptrs { const char *k, *v, *shift, *ssm, *ssmD; char *scr, *out; const char *c, *Wg, *Wu, *Wd;
};

__global__ void __cluster_dims__(2, 1, 1) __launch_bounds__(384, 1)
fused_kernel(const __grid_constant__ Ptrs P, const __grid_constant__ Maps M) {
    extern __shared__ __align__(1024) char smraw[];
    const uint32_t clk0 = clock32();
    const uint32_t sb = smem_u32(smraw);
    const int tid = threadIdx.x, b = blockIdx.x;
    #define BAR(i) (sb + BARS + 8 * (i))
    const char* pk = SBAR ? (&P.k)[tid >> 9] : P.k;
    const uint32_t rv = tid >> 3, c = (tid ^ rv) & 7, rk = rv + 2 + 2 * (rv >> 3);
    const uint32_t go = ((b >> 1) * 32 + (rv & 6) * 4 + 2 * (rv >> 3) + (rv & 1)) * 1280 + (b & 1) * 128 + c * 16, d0 = sb + st_kv(0) + rk * 128 + (((c ^ rk) & 7) << 4);
    if (SBAR) asm volatile("pmevent 1;" : "+l"(pk) : "r"(go), "r"(d0));
    if (SBAR && (go ^ d0 ^ (uint32_t)(uintptr_t)pk) == 0x80000001u) return;
    if (tid < 256 && b < 128) {
        cp16(d0, padd(pk, go));
        cp16(sb + st_kv(0) + 5120 + tid * 16, padd(P.v, go));
        sched_bar();
        if ((rv & 22) == 16)
            asm volatile("cp.async.cg.shared.global [%0], [%1], 16, %2;" :: "r"(sb + st_kv(0) + (rk - 2) * 128 + (((c ^ (rk - 2)) & 7) << 4)), "l"(padd(P.k, b < 2 ? go : go - 10240)), "r"(b < 2 ? 0 : 16) : "memory");
        if (tid < 160) cp16(sb + ST_SH + tid * 16, padd(P.shift, (tid >> 5) * 512 + (b & 1) * 512 + tid * 16));
        asm volatile("cp.async.commit_group;" ::: "memory");
    }
    const int warp = __shfl_sync(~0u, tid >> 5, 0), lane = tid & 31;
    const int rank = b & 1, cl = b >> 1;
    #define FFN_ROLE int cl_ = cl; asm volatile("pmevent 1;" : "+r"(cl_)); const int cu = cl_ - 36, cv = (cu * 37) >> 8, \
        gp_ = cl_ < 4 ? 0 : cl_ < 36 ? (cl_ - 4) & 7 : 1 + cu - 7 * cv, gi_ = cl_ < 4 ? 4 + cl_ : cl_ < 36 ? (cl_ - 4) >> 3 : 4 + cv, \
        grp = MAPM == 0 ? gp_ : MAPM == 1 ? (gp_ & 6) + (gi_ >> 2) : MAPM == 2 ? (gp_ & 6) + (gi_ & 1) : MAPM == 3 ? (gp_ & 4) + (gi_ & 3) : gi_, \
        js = MAPM == 0 ? gi_ : MAPM == 1 ? 4 * (gp_ & 1) + (gi_ & 3) : MAPM == 2 ? 4 * (gp_ & 1) + (gi_ >> 1) : MAPM == 3 ? 2 * (gp_ & 3) + (gi_ >> 2) : gp_, tile = 2 * grp + rank, dq = js & 3
    #define CNT(l, w) SC(cnt, (l) * 4096 + (w) * 4)
    uint32_t epoch = 0;

    if (b >= 128) {
        if (warp >= 10) {
            if (elect()) {
                _Pragma("unroll") for (int i = 0; i < 15; i++) mbar_init(BAR(i % 5 + i / 5 * 10) + (warp & 1) * 40, i < 5 || i >= 10 ? 1 : 4);
                asm volatile("fence.mbarrier_init.release.cluster;" ::: "memory");
                fence_async_smem();
                pf_map(&M.wm);
            }
            __syncwarp();
            asm volatile("barrier.cluster.arrive.relaxed.aligned;" ::: "memory");
            bar_arrive(0, 384);
        } else {
            epoch = ldg_late(CNT(C_Z, 6), lane);
            if (tid < 320) sts32(sb + 204800 + tid * 4, silu2(__ldg((const uint32_t*)P.c + tid)));
            fence_async_smem();
            __syncwarp();
            asm volatile("barrier.cluster.arrive.relaxed.aligned;\n barrier.cluster.wait.aligned;" ::: "memory");
            bar_sync(0, 384);
            STAMPIF(warp == 0, 7);
        }
        if (warp >= 10) {
            if (elect()) {
                wait_clock(clk0, D_SP);
                uint32_t fb = BAR(0) + (warp & 1) * 40, dst = sb + (warp & 1) * 102400, s = 0, ph = 1;
                _Pragma("unroll 1") for (int i = warp & 1; i < 15; i += 2) {
                    const int col = mod_col(i, b - 128);
                    _Pragma("unroll 1") for (int j = 0; j < 640; j += 160) {
                        mbar_wait(fb + 80, ph);
                        mbar_expect(fb, 20480);
                        tma2d(dst, &M.wm, col, j, fb);
                        fb += 8; dst += 20480;
                        if (++s == 5) { s = 0; ph ^= 1; fb -= 40; dst -= 102400; }
                    }
                }
            }
        } else if (warp == 9 && !rank) {
            epoch = (__shfl_sync(~0u, epoch, 0) >> 7) + 1;
            _Pragma("unroll 1") for (int r = 0; r < 5; r++) {
                if (lane == 0) mbar_expect(BAR(20 + r), 512);
                mbar_wait(BAR(20 + r), 0);
                uint32_t v[4];
                #pragma unroll
                for (int k = 0; k < 4; k++) asm volatile("ld.shared.b32 %0, [%1];" : "=r"(v[k]) : "r"(sb + 206336 + r * 512 + k * 128 + (lane & 16) * 4 + (lane & 3) * 16 + (lane & 12)) : "memory");
                stg_rlx128(SC(abc, (r * 64 + (b - 128) * 16 + lane) * 16), hmul2(v[2], hadd2(v[1], 0x3f803f80u)), hmul2(v[2], v[0]), hadd2(v[3], 0x3f803f80u), epoch);
                STAMP(1 + r);
            }
        } else if (warp < 8) {
            const int wg = warp >> 2;
            epoch = (__shfl_sync(~0u, epoch, 0) >> 7) + 1;
            int s = 0, ph = 0;
            _Pragma("unroll 1") for (int i = wg; i < 15; i += 2) {
                float ac5[20];
                uint32_t prev = 0;
                _Pragma("unroll 1") for (int j = 0; j < 4; j++) {
                    const int sl = wg * 5 + s;
                    mbar_wait(BAR(sl), ph);
                    wg_fence();
                    const uint32_t da = dlo(sb + sl * 20480, 16), db = dlo(sb + 204800 + j * 320, 16);
                    #pragma unroll
                    for (int ks = 0; ks < 10; ks++) WG<8>::ss<1, 0>(ac5 + 4 * (ks % 5), da + ks * 128, dhi(1024, 1), db + ks * 2, dhi(128, 0), ks >= 5 || j != 0);
                    wg_commit();
                    wg_wait<1>();
                    mbar_arrive_if(prev, lane == 0 && j);
                    prev = BAR(10 + sl);
                    if (++s == 5) { s = 0; ph ^= 1; }
                }
                wg_wait<0>();
                pin<20>(ac5);
                mbar_arrive_if(prev, lane == 0);
                const float acc[3] = {ac5[0] + ac5[4] + ac5[8] + ac5[12] + ac5[16], 0.f, ac5[2] + ac5[6] + ac5[10] + ac5[14] + ac5[18]};
                const uint32_t m0 = pack2(acc[0], __shfl_down_sync(~0u, acc[0], 4)), m1 = pack2(acc[2], __shfl_down_sync(~0u, acc[2], 4));
                if (i < 10) {
                    if ((lane & 7) == 0)
                        asm volatile("{ .reg .u32 a, m; mapa.shared::cluster.u32 a, %0, 0; mapa.shared::cluster.u32 m, %1, 0; \n"
                                     " st.async.shared::cluster.mbarrier::complete_tx::bytes.b32 [a], %2, [m]; st.async.shared::cluster.mbarrier::complete_tx::bytes.b32 [a+16], %3, [m]; }"
                                     :: "r"(sb + 206336 + (i >> 1) * 512 + rank * 256 + warp * 32 + (lane >> 3) * 4), "r"(BAR(20 + (i >> 1))), "r"(m0), "r"(m1) : "memory");
                } else if ((lane & 7) == 0) {
                    char* mp = SC(mod, ((4 * i + b - 168) * 64 + (warp & 3) * 16 + (lane >> 2)) * 4);
                    asm volatile("{ .reg .b64 x; mov.b64 x, {%1, %3}; st.relaxed.gpu.global.b64 [%0], x; mov.b64 x, {%2, %3}; st.relaxed.gpu.global.b64 [%0+32], x; }" :: "l"(mp), "r"(m0), "r"(m1), "r"(epoch) : "memory");
                }
                STAMPIF(warp == 0 && i == 12, 6); STAMPIF(warp == 0 && i == 0, 8);
            }
        }
        return;
    }

    const bool l0 = lane == 0;
    const int q = lane & 3, rr = lane >> 2;

    if (warp < 8) {
        const int wg = warp >> 2, w = warp & 3, t = tid & 127;
        if (t < 5) sts128(wg ? sb + XB + (t & 1) * XP + 4096 : sb + eslot(t), 0, 0, 0, 0);
        bar_sync(0, 384);
        asm volatile("barrier.cluster.arrive.relaxed.aligned;" ::: "memory");
        STAMPIF(warp == 0, 1);
        uint32_t dv = 0;
        if (t < 5) asm volatile("ld.global.nc.u16 %0, [%1];" : "=r"(dv) : "l"(padd(P.ssmD, (b + 128 * t) * 2)));
        FFN_ROLE;
        epoch = ldg_late(CNT(C_Z + tile, 6), lane);
        asm volatile("cp.async.wait_group 0;" ::: "memory");
        bar_sync(2, 256);
        mbar_arrive_if(BAR(B_KV), tid == 0);
        epoch = (__shfl_sync(~0u, epoch, 0) >> 7) + 1;
        asm volatile("barrier.cluster.wait.aligned;" ::: "memory");
        uint32_t g2e;
        asm("mapa.shared::cluster.u32 %0, %1, %2;" : "=r"(g2e) : "r"(BAR(B_G2E)), "r"(rank ^ (lane & 1)));
        const bool l01 = lane < 2;
        const uint32_t wre = g2e - 8 * (B_G2E - B_WE);
        {
            const uint32_t par = epoch & 1, xa = sb + XB + wg * XP, ye = ~lane & 1;
            const char* gp = SC(kvT, (b + 128 * wg) * 4096 + t * 16);
            if (wg) bar_arrive(1, 256);
            auto krow = [&](int o) { const int tk = 39 - 8 * ((lane & 7) >> 1) - o, ro = (tk & 1) + 2 * (tk >> 3) + 10 * ((tk >> 1) & 3); return sb + ro * 128 + (((ro & 7) ^ (2 * w)) << 4); };
            const int o0 = 2 * (lane >> 3) + (lane & 1);
            const int tv = 31 - 8 * ((lane & 7) >> 1) - o0, rv = (tv & 1) + 2 * (tv >> 3) + 8 * ((tv >> 1) & 3);
            uint32_t aE = krow(o0), aH = krow(8 + (o0 & 3)), aV = sb + 5120 + rv * 128 + (((rv & 7) ^ (2 * w)) << 4);
            uint32_t tdo = (rank * 64 + w * 16 + rr) * 4096 + (252 - 4 * cl + q) * 16;
            asm volatile("" : "+r"(aE), "+r"(aH), "+r"(aV), "+r"(tdo));
            const uint32_t kt = q == (((63 - cl) >> 1) & 3);
            _Pragma("unroll 1") for (unsigned long long steps = wg ? SEQ1 : SEQ0; steps; steps >>= 8) {
                const int r = steps & 7;
                STAMPS(0);
                if (steps & 0x40) {
                    const uint32_t so = st_kv(r);
                    const char *dst = SC(kvT, tdo + r * 524288), *hc = CNT(C_KV + 2 * r + rank, t);
                    mbar_wait(BAR(B_KV + r), 0);
                    STAMPIF(w == 1 && (r & 3) == 0, 35 + r); STAMPS(1);
                    red_if(hc, 2, t == 0 && ((EARLYH >> r) & 1));
                    uint2 sw[2]; uint32_t ke[2][6], vv[2][4], o[2][4];
                    #pragma unroll
                    for (int u = 0; u < 2; u++) {
                        sw[u] = lds64(sb + ST_SH + r * 512 + w * 128 + rr * 8 + u * 64);
                        ldsm4t(ke[u], (aE ^ (u << 4)) + so); ldsm2t(ke[u][4], ke[u][5], (aH ^ (u << 4)) + so); ldsm4t(vv[u], (aV ^ (u << 4)) + so);
                    }
                    sched_bar();
                    #pragma unroll
                    for (int u = 0; u < 2; u++) {
                        uint32_t ko[5];
                        #pragma unroll
                        for (int j = 0; j < 5; j++) ko[j] = prmt(ke[u][j], ke[u][j + 1], 0x5432);
                        #pragma unroll
                        for (int j = 0; j < 4; j++) o[u][j] = hmul2(hfma2s<0>(ke[u][j], sw[u].x, hfma2s<1>(ko[j], sw[u].x, hfma2s<0>(ke[u][j + 1], sw[u].y, hfma2s<1>(ko[j + 1], sw[u].y, 0x80008000u)))), vv[u][j]);
                        o[u][0] = (o[u][0] & ~kt) | (par & kt);
                    }
                    asm volatile("{ .reg .pred h; setp.ne.b32 h, %10, 0; pmevent 1;\n @h red.relaxed.gpu.global.add.u32 [%9], 2;\n"
                                 " st.relaxed.gpu.global.v4.b32 [%0], {%1,%2,%3,%4}; st.relaxed.gpu.global.v4.b32 [%0+32768], {%5,%6,%7,%8}; }"
                                 :: "l"(dst), "r"(o[0][0]), "r"(o[0][1]), "r"(o[0][2]), "r"(o[0][3]), "r"(o[1][0]), "r"(o[1][1]), "r"(o[1][2]), "r"(o[1][3]),
                                    "l"(hc), "r"((int)(t == 0 && !((EARLYH >> r) & 1))) : "memory");
                    mbar_arrive_if(BAR(B_TD + r), l0 && r < 3);
                    STAMPIF(w == 1 && (r & 3) == 0, r ? 3 : 45);
                    continue;
                }
                const uint32_t eb = sb + eslot(r);
                if (steps & 0x20) {
                    const int ew = (t >> 1) & 3, et = (ew + (t >> 3)) & 3, eh = (t >> 5) & 1;
                    const uint32_t ha = eb + ((t & 64) + 16 * et + 8 * eh + 2 * ew + (t & 1)) * 16;
                    const uint32_t ea = eb + (t & 64) * 128 + (2 * ew + eh) * 1024 + ((2 * et + (t & 1)) << 4);
                    mbar_wait(BAR(B_H + r), 0);
                    STAMPIF(warp == 1 && r == 0, 2); STAMPS(1);
                    uint4 hv4[4];
                    #pragma unroll
                    for (int i = 0; i < 4; i++) hv4[i] = lds128(ha + (i >> 1) * 2048 + (i & 1) * 16);
                    if (w == 0) { const uint32_t dr = __shfl_sync(~0u, dv, r); if (l0) hv4[1].x = hadd2(hv4[1].x, dr); }
                    bar_sync(5 + wg, 128);
                    #pragma unroll
                    for (int h = 0; h < 2; h++) {
                        const uint32_t* w8 = &hv4[2 * h].x;
                        #pragma unroll
                        for (int row = 0; row < ((WI & 64) ? 2 : 8); row++) {
                            uint32_t o[4];
                            #pragma unroll
                            for (int i = 0; i < 4; i++) o[i] = (row & 1) ? prmt(w8[(7 - row) / 2 + i], w8[(7 - row) / 2 + i + 1], 0x5432) : w8[(8 - row) / 2 + i];
                            sts128((ea ^ (row << 4)) + row * 128 + h * 16384, o[0], o[1], o[2], o[3]);
                        }
                    }
                    if (!(steps & 0x2000)) fence_async_smem();
                    STAMPIF(w == 0, wg ? 30 : 4);
                    continue;
                }
                float acc[128];
                mbar_wait(BAR(B_X + wg), (r >> 1) & 1); STAMPS(1);
                STAMPIF(w == 0, 10 + r);
                bar_sync(1 + wg, 256);
                GSTAMPIF(w == 0 && r == 0, 7); STAMPS(2);
                _Pragma("unroll 1") for (int rep = 0;; rep++) {
                    wg_fence();
                    Conv<0>::run(acc, dlo(eb, 16), dlo(xa, 16));
                    wg_commit();
                    if (r < 4 && !rep) bar_arrive(2 - wg, 256);
                    uint32_t t0;
                    asm volatile("ld.shared.b32 %0, [%1];" : "=r"(t0) : "r"(xa + w * 512 + (lane & 8) * 256 + (lane & 7) * 64 + (lane & 6) * 8) : "memory");
                    wg_wait<0>();
                    pin<128>(acc);
                    STAMPIF(w == 0, 15 + r);
                    if (!bar_or(5 + wg, 128, (t0 ^ par) & 1) || rep) break;
                    VALIF(true, 90, 1);
                    _Pragma("unroll 1") for (int h = 0; h < 2; h++) {
                        uint4 kx = {0, 0, 0, 0};
                        _Pragma("unroll 1") for (int it = 0; it < 20000; it++) {
                            ldg_rlx128_if(kx, gp + h * 2048, true);
                            if (!__any_sync(~0u, q == (lane >> 3) && ((kx.x ^ par) & 1))) break;
                        }
                        sts128(xa + t * 16 + h * 2048, kx.x, kx.y, kx.z, kx.w);
                    }
                    fence_async_smem();
                    bar_sync(5 + wg, 128);
                }
                gp += 2 * 524288;
                mbar_arrive_if(BAR(B_MD + r), t == 0 && r < 3);
                const uint32_t pw = eb + w * PP + lane * 16;
                #pragma unroll
                for (int g = 0; g < 8; g++) {
                    uint32_t o[4];
                    #pragma unroll
                    for (int l = 0; l < 4; l++) { const int i = 4 * g + l;
                        o[l] = i < 31 ? pack2(acc[4 * i] + acc[4 * i + 6], acc[4 * i + 1] + acc[4 * i + 7]) : pack2(acc[4 * i], acc[4 * i + 1]); }
                    asm volatile("stmatrix.sync.aligned.m8n8.x4.trans.shared.b16 [%0], {%1,%2,%3,%4};" :: "r"(pw + g * 512), "r"(o[0]), "r"(o[1]), "r"(o[2]), "r"(o[3]) : "memory");
                    if (g & 1) sched_bar();
                }
                if (lane < 6) sts128(pw + 4096, 0, 0, 0, 0);
                bar_sync(5 + wg, 128);
                if (YH < 0) red_if(CNT(C_Y + r, t), 1, t == 0);
                char* yp = (char*)gp + (offsetof(Scratch, yT) - 2 * 524288);
                #pragma unroll
                for (int h = 0; h < 2; h++) {
                    uint4 p[4];
                    #pragma unroll
                    for (int k = 0; k < 4; k++) p[k] = (WI & 128) && k > 0 ? p[0] : lds128(eb + (t + 128 * h) * 16 + k * (PP + 32));
                    uint32_t y[4];
                    #pragma unroll
                    for (int j = 0; j < 4; j++) y[j] = hadd2((&p[0].x)[j], hadd2((&p[1].x)[j], hadd2((&p[2].x)[j], (&p[3].x)[j])));
                    stg_rlx128(yp + h * 2048, (y[0] & ~ye) | (par & ye), y[1], y[2], y[3]);
                    if (h == YH) red_if(CNT(C_Y + r, t), 1, t == 0);
                }
                __syncwarp();
                mbar_arrive_if(BAR(B_RD + r), l0);
                mbar_arrive_remote_if(wre + 16 * (r - 1) + (lane & 4) * 2, lane < 8 && (r == 1 || r == 2));
                STAMPIF(w == 0, 20 + r);
            }
        }
        float acc1[128];
        uint4 sv[2] = {};
        const char* s2p = SC(st2, (tile * 128 + wg * 64 + w * 16 + rr) * 16);
        auto pass1 = [&](int n0, int n1, auto&& top, auto&& mid) {
            _Pragma("unroll 1") for (int n = n0; n < n1; n++) {
                top();
                const uint32_t da = dlo(sb + wg * 4096, 16) + n * 512, db = dlo(sb + WR, 4096) + (n & 3) * 1024;
                TWAIT((n & 1) ? 91 : 10 + (n >> 1), mbar_wait(BAR(B_AF) + (n >> 1) * 8, 0));
                TWAIT(50 + n, mbar_wait(BAR(B_WF) + (n & 3) * 8, (n >> 2) & 1));
                GSTAMPIF(n == 0 && warp == 0, 8);
                STAMPIF(n == 0 && warp == 4, 9);
                STAMPI(warp == 0 && !(n & 1), 50 + (n >> 1));
                wg_fence();
                WG<256>::ss<0, 1>(acc1, da, dhi(512, 2), db, dhi(1024, 1), n0 ? 1 : n);
                if (ER & 1) {
                    wg_commit();
                    wg_wait<1>();
                    mbar_arrive_remote_if(wre + ((n + 3) & 3) * 8, l01 && n > 0);
                }
                WG<256>::ss<0, 1>(acc1, da + 2, dhi(512, 2), db + 128, dhi(1024, 1), 1);
                wg_commit();
                if (!(ER & 1)) {
                    wg_wait<1>();
                    mbar_arrive_remote_if(wre + ((n + 3) & 3) * 8, l01 && n > 0);
                }
                mid(n);
            }
        };
        pass1(0, N_UT, []() {}, [](int) {});
        {
            float au[8];
            const int un = min(2 * b + wg, 239), cg = (un * 205) >> 10;
            char* up = SC(ut, ((un - 5 * cg) * 3072 + cg * 64 + w * 16 + rr) * 8);
            pass1(N_UT, N_UT + 1, [&]() {
                TWAIT(20, mbar_wait(BAR(B_UF), 0));
                const uint32_t ua = dlo(sb + UST + wg * 16384, 16), ub = dlo(sb + CS_TAB + wg * 512, 32);
                wg_fence();
                #pragma unroll
                for (int ks = 0; ks < 8; ks++) WG<8>::ss<1, 0>(au + 4 * (ks & 1), ua + ks * 128, dhi(1024, 1), ub + ks * 4, dhi(128, 0), ks >= 2);
                wg_commit();
            }, [&](int) {
                pin<8>(au);
                asm volatile("{ .reg .pred p; .reg .b64 x; setp.eq.b32 p, %5, 0; mov.b64 x, {%1, %2}; @p st.relaxed.gpu.global.b64 [%0], x; mov.b64 x, {%3, %4}; @p st.relaxed.gpu.global.b64 [%0+64], x; }"
                             :: "l"(up), "r"(tagged(au[0] + au[4], epoch)), "f"(au[1] + au[5]), "r"(tagged(au[2] + au[6], epoch)), "f"(au[3] + au[7]), "r"(q | (b >= 120)) : "memory");
                mbar_arrive_if(BAR(B_UD), l0);
                STAMPIF(warp == 0, 25);
            });
        }
        pass1(N_UT + 1, 20, []() {}, [&](int n) { ldg_rlx128_if(sv[0], s2p, n == 16); ldg_rlx128_if(sv[1], s2p + 128, n == 16); });
        _Pragma("unroll 1") for (int it = 0; it < 20000 && __any_sync(~0u, sv[0].w != epoch || sv[1].w != epoch); it++) { ldg_rlx128_if(sv[0], s2p, true); ldg_rlx128_if(sv[1], s2p + 128, true); }
        float acc2[64];
        const float rq0 = __uint_as_float(sv[0].z), rq1 = __uint_as_float(sv[1].z);
        {
            uint32_t ax[4];
            const uint32_t zm = q == 0 ? ~0u : q == 1 ? 0xffffu : 0u, sh = q ? 0x5454 : 0x5410, sl = sh + 0x2222;
            uint32_t a0 = prmt(sv[0].x, sv[0].y, sh), a1 = prmt(sv[1].x, sv[1].y, sh), a2 = prmt(sv[0].x, sv[0].y, sl), a3 = prmt(sv[1].x, sv[1].y, sl);
            TWAIT(21, mbar_wait(BAR(B_T1), 0));
            wg_wait<0>();
            mbar_arrive_remote_if(wre + 24, l01);
            asm volatile("setmaxnreg.inc.sync.aligned.u32 232;\n and.b32 %0, %4, %8; and.b32 %1, %5, %8; and.b32 %2, %6, %8; and.b32 %3, %7, %8;"
                         : "=r"(ax[0]), "=r"(ax[1]), "=r"(ax[2]), "=r"(ax[3]) : "r"(a0), "r"(a1), "r"(a2), "r"(a3), "r"(zm) : "memory");
            wg_fence();
            WG<256>::rs<1>(acc1, ax[0], ax[1], ax[2], ax[3], dlo(sb + TAB1, 0), dhi(48, 0), 1);
            WG<128>::rs<1>(acc2, ax[0], ax[1], ax[2], ax[3], dlo(sb + TAB2, 0), dhi(48, 0), 0);
            wg_commit();
        }
        char* hdst = SC(hh, (tile * 24 + js * 3) * 16384 + warp * 1024 + rr * 64 + ((q ^ (rr >> 1)) << 4));
        GSTAMPIF(warp == 0, 26);
        uint32_t hq[48];
        const uint32_t tm = (lane & 7) == (w & 1) * 4;
        auto release2 = [&](int it) {
            mbar_arrive_remote_if(wre + 8 * ((it + 3) & 3), l01 && it < 7);
            mbar_arrive_if(BAR(B_HS - 7) + 8 * it, l0 && it >= 7);
            mbar_arrive_remote_if(g2e + 8 * (it - G2R), l01 && it >= G2R && it < G2R + 6);
        };
        auto pass2 = [&](int it, auto&& epi) {
            TWAIT(70 + it, mbar_wait(BAR(B_WF) + (it & 3) * 8, ((it >> 2) & 1) ^ 1));
            STAMPI(warp == 0, 60 + it);
            const uint32_t da = dlo(sb + wg * 4096, 16) + it * 1024, db = dlo(sb + WR, 8192) + (it & 3) * 1024;
            wg_fence();
            static_for<0, 4>([&](auto KS) {
                WG<128>::ss<0, 1>(acc2, da + (KS.value >> 1) * 512 + (KS.value & 1) * 2, dhi(512, 2), db + KS.value * 128, dhi(1024, 1), 1);
                if constexpr (KS.value == 3) wg_commit();
                if constexpr (KS.value == 0 && (ER & 2)) { wg_commit(); wg_wait<1>(); if (it) release2(it); }
                epi(KS);
            });
            if (!(ER & 2)) { wg_wait<1>(); if (it) release2(it); }
        };
        constexpr int NE = ((epi_slot(15) + E0) >> 2) + 1;
        static_for<0, NE>([&](auto IT) {
            pass2(IT.value, [&](auto KS) {
                if constexpr (IT.value == 0 && KS.value == 0) pin<128>(acc1);
                static_for<0, 16>([&](auto E) {
                    if constexpr (epi_slot(E.value) == 4 * IT.value + KS.value - E0) {
                        sched_bar();
                        ffn_epi<15 - E.value>(acc1, acc1 + 64, hq, hdst, tm, epoch, rq0, rq1);
                        if constexpr ((E.value & 7) == 7) { __syncwarp(); mbar_arrive_if(BAR(B_HD + (E.value >> 3)), l0); }
                        sched_bar();
                    }
                });
            });
        });
        _Pragma("unroll 1") for (int it = NE; it < 10; it++) pass2(it, [](auto) {});
        {
            float acc[80];
            static_for<0, 3>([&](auto IT) {
                constexpr int it = IT.value;
                TWAIT(35 + it, mbar_wait(BAR(B_G2F + it), 0));
                STAMPI(warp == 0 && it == 0, 70);
                const uint32_t db = dlo(sb + G2B + it * 20480, 2048);
                #pragma unroll
                for (int i = 0; i < 16; i++) asm volatile("" : "+r"(hq[16 * it + i]) :: "memory");
                wg_fence();
                static_for<0, 4>([&](auto KS) {
                    constexpr int ks = KS.value, sl = 4 * it + ks;
                    const uint32_t* o = hq + 16 * it + 8 * (ks >> 1) + 2 * (ks & 1);
                    WG<160>::rs<1>(acc, o[0], o[4], o[1], o[5], db + (ks >> 1) * 640 + (ks & 1) * 64, dhi(512, 2), it != 0 || ks != 0);
                    if constexpr (sl == 0 || ks == 3) wg_commit();
                    if constexpr (it > 0 && ks == 0 && (ER & 4)) { wg_commit(); wg_wait<1>(); mbar_arrive_remote_if(g2e + 8 * (it ? it - 1 : 0), l01); }
                    if constexpr (sl == 0) {
                        wg_wait<1>();
                        pin<64>(acc2);
                        mbar_arrive_if(BAR(B_S0), l0);
                        static_for<(G2R > 4 ? 10 - G2R : 6), 6>([&](auto G) { mbar_arrive_remote_if(g2e + 8 * G.value, l01); });
                    }
                    if constexpr (sl < 8 / Q2) {
                        sched_bar();
                        static_for<0, Q2>([&](auto J) { ffn_epi<7 - Q2 * sl - J.value>(acc2, acc2 + 32, hq + 32, hdst + 32768, tm, epoch, rq0, rq1); });
                        if constexpr (sl == 8 / Q2 - 1) { __syncwarp(); mbar_arrive_if(BAR(B_HD + 2), l0); }
                        sched_bar();
                    }
                    if constexpr (sl == 0) wg_fence();
                });
                if (it && !(ER & 4)) {
                    wg_wait<1>();
                    mbar_arrive_remote_if(g2e + 8 * (it ? it - 1 : 0), l01);
                }
            });
            uint4 gw[5];
            mbar_wait(BAR(B_GB), 0);
            #pragma unroll
            for (int i = 0; i < 5; i++) gw[i] = lds128(sb + GBT + q * 80 + i * 16);
            const uint32_t da = dlo(sb + G2A + wg * 4096, 16), db = dlo(sb + G2B, 2048);
            _Pragma("unroll 1") for (int it = 3; it < 12 - NST; it++) {
                const int g = it >= 6 ? it - 6 : it, ga = it >= 5 ? it - 5 : it + 1;
                TWAIT(35 + it, mbar_wait(BAR(B_G2F + g), it >= 6));
                TWAIT(77 + it, mbar_wait(BAR(B_AF - 3 + it), 1));
                STAMPI(warp == 0 && (it == 3 || it == 6), 70 + (it >> 2) + 1);
                wg_fence();
                #pragma unroll
                for (int ks = 0; ks < 4; ks++) {
                    WG<160>::ss<0, 1>(acc, da + ga * 1024 + (ks >> 1) * 512 + (ks & 1) * 2, dhi(512, 2), db + g * 1280 + (ks >> 1) * 640 + (ks & 1) * 64, dhi(512, 2), 1);
                    if (ks == 3 || (ks == 0 && (ER & 4))) wg_commit();
                    if (ks == ((ER & 4) ? 0 : 3)) {
                        wg_wait<1>();
                        mbar_arrive_remote_if(g2e + 8 * (it - 1), l01 && it < 7);
                        mbar_arrive_if(BAR(B_HS - 4) + 8 * it, l0 && it >= 4 && it < 7);
                    }
                }
            }
            mbar_wait(BAR(B_G2F + 6 - NST), 1);
            mbar_wait(BAR(B_AF + 9 - NST), 1);
            auto rel5 = [&](bool p) { mbar_arrive_remote_if(g2e + 40, l01 && p); mbar_arrive_if(BAR(B_HS + 2), l0 && p); };
            if (NST == 6 && wg) { wg_wait<0>(); rel5(true); }
            if (wg) TWAIT(47, bar_sync(7, 256));
            STAMPI(warp == 0, 73);
            float gf[80];
            wg_fence();
            static_for<48 - 4 * NST, 48>([&](auto K) {
                constexpr int it = K.value >> 2, ks = K.value & 3;
                WG<160>::ss<0, 1>(acc, da + (it == 11 ? 0 : it - 5) * 1024 + (ks >> 1) * 512 + (ks & 1) * 2, dhi(512, 2), db + (it - 6) * 1280 + (ks >> 1) * 640 + (ks & 1) * 64, dhi(512, 2), 1);
                if constexpr (K.value == 24) { wg_commit(); wg_wait<1>(); rel5(!wg); }
                if constexpr (it < 11 && ks == 1) TWAIT(36 + it, mbar_wait(BAR(B_G2F + it - 5), 1));
                if constexpr (it < 11 && ks == 2) TWAIT(78 + it, mbar_wait(BAR(B_AF + it - 2), 1));
                if constexpr (RQE == 2 && K.value >= 28 && K.value < 47) {
                    sched_bar();
                    #pragma unroll
                    for (int j = K.value - 28; j < (K.value == 46 ? 20 : K.value - 27); j++) {
                        const float lo = bflo((&gw[j >> 2].x)[j & 3]), hi = bfhi((&gw[j >> 2].x)[j & 3]);
                        gf[4 * j] = lo * rq0; gf[4 * j + 1] = hi * rq0; gf[4 * j + 2] = lo * rq1; gf[4 * j + 3] = hi * rq1;
                        pin<4>(gf + 4 * j);
                    }
                    sched_bar();
                }
                if constexpr (K.value == 45) { mbar_wait(BAR(B_OI), 0); fence_async_glob(); }
                if constexpr (K.value == 39) wg_commit();
                if constexpr (K.value == 46) { if (!wg) bar_arrive(7, 256); }
            });
            wg_commit();
            wg_wait<1>();
            bar_sync(5 + wg, 128);
            uint32_t osts[2];
            const uint32_t orow = (lane & 7) * 336 + (lane >> 3) * 16;
            osts[0] = sb + G2A + (1 + w) * 16384 + wg * 4096; osts[1] = osts[0] + 8192;
            wg_wait<0>();
            pin<80>(acc);
            STAMPIF(w == 0, 27 + wg);
            GSTAMPIF(warp == 4, 29);
            #pragma unroll
            for (int hf = 0; hf < 2; hf++) {
                #pragma unroll
                for (int i = 0; i < 5; i++) {
                    uint32_t o[4];
                    const float rq = hf ? rq1 : rq0;
                    #pragma unroll
                    for (int j = 0; j < 4; j++) { const int n = 16 * i + 4 * j + 2 * hf; o[j] = RQE == 2 ? pack2(acc[n] * gf[n], acc[n + 1] * gf[n + 1]) : hmul2(RQE ? pack2(acc[n], acc[n + 1]) : pack2(acc[n] * rq, acc[n + 1] * rq), (&gw[i].x)[j]); }
                    asm volatile("stmatrix.sync.aligned.m8n8.x4.shared.b16 [%0], {%1,%2,%3,%4};" :: "r"(osts[hf] + orow + i * 64), "r"(o[0]), "r"(o[1]), "r"(o[2]), "r"(o[3]) : "memory");
                    if (EI && i < 4 && (EI == 1 || (i & 1))) sched_bar();
                }
                fence_async_smem();
                __syncwarp();
                if (elect() && !((WI & 8) && hf)) { tma3d_red(&M.out, osts[hf], dq, 128 * tile + 16 * warp + 8 * hf); }
                sched_bar();
            }
            STAMPIF(w == 0, wg ? 31 : 85);
            if (elect()) asm volatile("cp.async.bulk.commit_group;\n cp.async.bulk.wait_group.read 0;" ::: "memory");
            STAMPIF(w == 3, wg ? 33 : 86);
            GSTAMPIF(warp == 4, 34);
        }
    } else {
        const int hw = warp & 3, wv = hw & 1;
        if (elect()) {
            if (warp & 2) {
                if (warp & 1) { _Pragma("unroll") for (int i = B_UD; i < NBARS; i++) mbar_init(BAR(i), bar_count(i)); }
                else { _Pragma("unroll") for (int i = B_WF; i < B_UD; i++) mbar_init(BAR(i), bar_count(i)); }
            } else { _Pragma("unroll") for (int i = 0; i < 20; i++) mbar_init(BAR(i) + wv * 160, 1); }
            asm volatile("fence.mbarrier_init.release.cluster;" ::: "memory");
            fence_async_smem();
        }
        __syncwarp();
        asm volatile("barrier.cluster.arrive.relaxed.aligned;" ::: "memory");
        const uint32_t t1 = clk0 + D_1 + ((((b * 37) & 127) * G_ST) >> 7);
        if (hw == 0) {
            bar_arrive(0, 384);
            if (lane < 15 && lane != B_KV) mbar_expect(BAR(lane), lane >= B_KV && lane < B_Q ? 9216 : 4096);
            __syncwarp();
            if (elect()) { wait_until(t1); bulk_g2s(sb + 16, P.ssm + b * 4096, 4096, BAR(B_H)); }
            __syncwarp();
            bar_sync(3, 128);
        } else { bar_sync(0, 384); bar_arrive(3, 128); }
        FFN_ROLE;
        const int kh = js >> 2, ft = tile * 8 + js;
        const int oz = __shfl_sync(~0u, tid >> 9, lane);
        epoch = ldg_rlx32(CNT(C_Z + tile, 6 + oz));
        if (hw == 0) {
            if (elect()) {
                auto x_fetch = [&](int r) {
                    if (!mbar_test(BAR(B_KV + r), 0)) { mbar_wait(BAR(B_KV + r), 0); pause(D_PK); }
                    poll_cnt(CNT(C_KV + 2 * r + (b >> 6), 0), (epoch | 127) + 1);
                    fence_async_glob();
                    if (r >= 2) mbar_wait(BAR(B_MD - 2 + r), 0);
                    mbar_expect(BAR(B_X + (r & 1)), 4096);
                    bulk_g2s(sb + XB + (r & 1) * XP, SC(kvT, (b + 128 * r) * 4096), 4096, BAR(B_X + (r & 1)));
                    STAMPIF(r < 2, 5 + r);
                };
                static_for<1, NORD>([&](auto I) {
                    constexpr char kind = ord_kind(I.value); constexpr int n = ord_index(I.value);
                    if constexpr (kind == 'k' && n >= 3) mbar_wait(BAR(B_TD + n - 3), 0);
                    if constexpr (kind != '_' && kind != 'x' && (TUNING || ord_time(I.value))) wait_until(t1 + TN(16 + I.value, ord_time(I.value)));
                    if constexpr (kind == 'k') { tma4d(sb + st_kv(n), &M.k, n * 128 + rank * 64, cl * 4 - 1, BAR(B_KV + n)); tma4d(sb + st_kv(n) + 5120, &M.v, n * 128 + rank * 64, cl * 4, BAR(B_KV + n)); }
                    if constexpr (kind == 'q') tma3d(sb + ST_Q + n * 4096, &M.q, ft * 16, n * 4, BAR(B_Q + n));
                    if constexpr (kind == 'h') bulk_g2s(sb + eslot(n) + 16, P.ssm + (b + 128 * n) * 4096, 4096, BAR(B_H + n));
                    if constexpr (kind == 'w') pf_l2(((n & 1) ? P.Wu : P.Wg) + (b + 128 * (n >> 1)) * 3072, 3072);
                    if constexpr (kind == 'x') x_fetch(n);
                });
                _Pragma("unroll 1") for (int r = ord_count('x'); r < 5; r++) x_fetch(r);
            }
        } else if (hw == 2 && elect()) { pf_map(&M.k); pf_map(&M.v); pf_map(&M.q); }
        __syncwarp();
        epoch = (__shfl_sync(~0u, epoch, 0) >> 7) + 1;
        const uint32_t target = epoch << 7, par = epoch & 1;
        const char* pa = lane < 8 ? CNT(C_Y, 0) : SC(abc, (lane & 7) * 128 + 12);
        const uint32_t want = lane < 8 ? target : epoch;
        auto y_poll = [&](int r) {
            if (!mbar_test(BAR(B_RD + r), 0)) { mbar_wait(BAR(B_RD + r), 0); pause(D_PY); }
            _Pragma("unroll 1") for (int it = 0; it < 20000 && __any_sync(~0u, (int)(ldg_rlx32(pa) - want) < 0); it++) {}
        };
        auto y_request = [&](int r) {
            if (elect()) {
                fence_async_glob();
                mbar_expect(BAR(B_Y + (r & 1)), 5120);
                tma5d(sb + ST_Y + (r & 1) * 4096, &M.y, 2032 - 16 * ft, 4 * r, BAR(B_Y + (r & 1)));
                bulk_g2s(sb + ST_Y + 8192 + (r & 1) * 1024, SC(abc, r * 1024), 1024, BAR(B_Y + (r & 1)));
            }
            STAMPIF(r < 2, 48 + r);
            pa += lane < 8 ? 4096 : 1024;
        };
        if (hw == 1) {
            if (elect()) pf_map(&M.y);
            mbar_wait(BAR(B_TD + 2), 0);
            wait_until(clk0 + D_M);
            _Pragma("unroll 1") for (int r = 0; r < 2; r++) {
                y_poll(r); y_request(r);
            }
        }
        if (hw >= 2) {
            pa += lane < 8 ? 8192 : 2048;
            {
                uint32_t aQ = sb + ST_Q + wv * 2048 + (lane & 15) * 64 + (((lane >> 1) + (lane >> 4)) & 3) * 16;
                float sq[4] = {0.f, 0.f, 0.f, 0.f};
                _Pragma("unroll 1") for (int rq = 0; rq < 5; rq++) {
                    mbar_wait(BAR(B_Q + rq), 0);
                    STAMPIF(wv && rq == 4, 44);
                    uint4 v[4];
                    #pragma unroll
                    for (int u = 0; u < 4; u++) v[u] = lds128((aQ ^ ((u & 1) << 5)) + (u >> 1) * 1024);
                    sched_bar();
                    #pragma unroll
                    for (int j = 0; j < ((WI & 256) ? 2 : 16); j++) acc_stat(sq[2 * (j & 1)], sq[2 * (j & 1) + 1], (&v[(j & 1) + (j >> 3) * 2].x)[(j >> 1) & 3]);
                    aQ += 4096;
                }
                asm volatile("st.shared.v2.f32 [%0], {%1,%2};" :: "r"(sb + ST_S + (lane & 15) * 48 + wv * 16 + (lane >> 4) * 8), "f"(sq[0] + sq[2]), "f"(sq[1] + sq[3]) : "memory");
            }
            float sa[4] = {0.f, 0.f, 0.f, 0.f};
            uint32_t yl = sb + ST_Y + wv * 1024 + lane * 32 + (lane & 4) * 4, ca = sb + ST_Y + 8192 + wv * 256 + q * 16;
            const uint32_t ym = rr ? 0u : 0x00010001u;
            char* zp = SC(z, tile * 163840 + wv * 8192 + (16 * js + 15 - rr) * 64 + ((q ^ 3 ^ (rr >> 1)) << 4));
            uint32_t xs = sb + ST_Q + wv * 1024 + (15 - rr) * 64 + q * 16;
            const uint32_t tm = (lane & 7) == (~js & 1) * 4;
            const char* zc = CNT(C_Z + tile, lane & 7);
            bar_sync(4, 64);
            STAMPIF(hw == 3, 46);
            uint32_t rs[2], mr[2];
            #pragma unroll
            for (int h = 0; h < 2; h++) {
                float f[2] = {0.f, 0.f};
                #pragma unroll
                for (int i = 0; i < 2; i++) { const uint4 a = lds128(sb + ST_S + (15 - 8 * h - rr) * 48 + i * 16); f[0] += __uint_as_float(a.x) + __uint_as_float(a.z); f[1] += __uint_as_float(a.y) + __uint_as_float(a.w); }
                const float mu = f[0] * (1.f / D_), r_ = rsqrt_(fmaxf(f[1] * (1.f / D_) - mu * mu, 0.f) + 1e-5f);
                rs[h] = pack2(r_, r_); const float m_ = MSUB ? -mu : -mu * bflo(rs[h]); mr[h] = pack2(m_, m_);
            }
            const int un = min(2 * b + wv, 239), cg = (un * 205) >> 10, ur = un - 5 * cg;
            char* op = padd(P.out, (ft * 16 + 15 - rr) * 1280 + wv * 64 + q * 16) - 256;
            uint4 x1[4] = {};
            const char *cp_ = SC(abc, (ur * 64 + (lane & 16) + q * 4 + (rr & 3)) * 16 + 8), *sp_ = SC(mod, (ur * 64 + lane) * 8);
            auto caddr = [&](int i) { return i < 2 ? sp_ + i * 256 : cp_ + (i & 1) * 512; };
            uint2 mv[4] = {};
            uint32_t pv = 0;
            bool asked = false;
            _Pragma("unroll 1") for (int r = 0;; r++) {
                STAMPR(0);
                uint4 x[4] = {};
                const bool ask = r >= 2 && r < 5 && wv == (ALT & r);
                if (ask) { if (!__any_sync(~0u, (int)(pv - want) < 0)) { y_request(r); asked = true; } else pv = ldg_rlx32(pa); }
                STAMPR(1);
                if (r < 5) {
                    #pragma unroll
                    for (int i = 0; i < 4; i++) x[i] = lds128(xs + (i >> 1) * 2048 - (i & 1) * 512);
                    sched_bar();
                } else {
                    mbar_wait(BAR(B_TD), 1);
                    if (elect()) {
                        mbar_expect(BAR(B_UF), (WI & 1) ? 0 : 16384);
                        #pragma unroll
                        for (int i = 0; i < ((WI & 1) ? 0 : 2); i++) tma2d(sb + UST + wv * 16384 + i * 8192, cg >= 24 ? &M.u2 : &M.g2, (cg >= 24 ? cg - 24 : cg) * 64, ur * 128 + i * 64, BAR(B_UF));
                    }
                    ll_wait<4>(mv, epoch, caddr);
                    #pragma unroll
                    for (int i = 0; i < 4; i++) sts32(sb + CS_TAB + wv * 512 + ((i & 1) * 8 + rr) * 32 + q * 4 + (i < 2 ? 16 : 0), mv[i].x);
                    fence_async_smem(); __syncwarp(); mbar_arrive_if(BAR(B_UF), l0);
                    STAMPIF(wv, 41);
                }
                if (r) {
                    #pragma unroll
                    for (int j = 0; j < ((WI & 16) ? 1 : 16); j++) acc_stat(sa[j & 2], sa[(j & 2) + 1], (&x1[(j >> 1) & 3].x)[(j & 1) + (j >> 3) * 2]);
                    #pragma unroll
                    for (int j = 0; j < 4; j++) asm volatile("" : "+f"(sa[j]) :: "memory");
                    bump<32768>(zp); bump(yl, (r & 1) ? 4096 : -4096); bump(ca, (r & 1) ? 1024 : -1024);
                }
                STAMPR(2);
                uint32_t nx[16];
                #pragma unroll
                for (int j = 0; j < 16; j++) { nx[j] = MSUB ? hmul2(hadd2((&x[j >> 2].x)[j & 3], mr[(j >> 2) & 1]), rs[(j >> 2) & 1]) : hfma2((&x[j >> 2].x)[j & 3], rs[(j >> 2) & 1], mr[(j >> 2) & 1]); asm volatile("" : "+r"(nx[j]) :: "memory"); }
                sched_bar();
                if (r) {
                    #pragma unroll
                    for (int i = 0; i < ((WI & 32) ? 0 : 4); i++) stg128(op + (i >> 1) * 128 - (i & 1) * 10240, x1[i].x, x1[i].y, x1[i].z, x1[i].w);
                }
                if (r == 5) break;
                STAMPR(3);
                if (ask && !asked) { if (__any_sync(~0u, (int)(pv - want) < 0)) y_poll(r); y_request(r); }
                asked = false;
                STAMPR(4);
                mbar_wait(BAR(B_Y + (r & 1)), (r >> 1) & 1);
                if (ALT && r >= 2 && !ask) pa += lane < 8 ? 4096 : 1024;
                if (wv == (ALT & (r + 1)) && r) { mbar_wait(BAR(B_YE + (~r & 1)), (r - 1) >> 1 & 1); pv = ldg_rlx32(pa); }
                if (r == 4) { _Pragma("unroll") for (int i = 0; i < 4; i++) mv[i] = ldg_rlx64(caddr(i)); }
                STAMPIF(wv == 0 && r == 0, 47);
                STAMPR(5);
                uint4 cc[8];
                uint32_t y[4][4];
                _Pragma("unroll 1") for (int it = 0; it < 20000; it++) {
                    uint32_t all = ~0u, any = 0;
                    #pragma unroll
                    for (int i = 0; i < 4; i++) ldsm4t(y[i], (yl ^ ((i & 1) << 4)) + (i >> 1) * 2048);
                    #pragma unroll
                    for (int i = 0; i < 8; i++) cc[i] = lds128(ca + (i >> 2) * 512 + (i & 3) * 64);
                    #pragma unroll
                    for (int j = 0; j < 8; j++) { all &= y[(j >> 2) * 2][j & 3]; any |= y[(j >> 2) * 2][j & 3]; }
                    if (!__any_sync(~0u, ((par ? ~all : any) & ym) != 0)) break;
                    VALIF(true, 89, 1);
                    const char* yp = SC(yT, (r * 128 + wv * 32 + (lane & 6) * 4 + (lane >> 3) * 2 + (lane & 1)) * 4096 + (254 - 2 * ft) * 16);
                    #pragma unroll
                    for (int i = 0; i < 4; i++) cp16((yl ^ ((i & 1) << 4)) + (i >> 1) * 2048, yp + (i & 1) * 16 + (i >> 1) * 262144);
                    asm volatile("cp.async.wait_all;" ::: "memory");
                    __syncwarp();
                }
                STAMPR(6);
                bump<256>(op); bump(xs, 4096);
                if (ZE) red_if(zc, 8, lane == r);
                #pragma unroll
                for (int j = 0; j < 16; j++) {
                    (&x1[j >> 2].x)[j & 3] = hfma2(hfma2(nx[j], cc[(j >> 3) * 4 + (j & 3)].x, cc[(j >> 3) * 4 + (j & 3)].y), y[j >> 2][j & 3], (&x[j >> 2].x)[j & 3]);
                    y[j >> 2][j & 3] = hmul2((&x1[j >> 2].x)[j & 3], cc[(j >> 3) * 4 + (j & 3)].z);
                    if ((j & 3) == (~j >> 2 & 1)) y[j >> 2][j & 3] = (y[j >> 2][j & 3] & ~tm) | (par & tm);
                    asm volatile("" : "+r"(y[j >> 2][j & 3]) :: "memory");
                }
                sched_bar();
                #pragma unroll
                for (int i = 0; i < 4; i++) asm volatile("st.relaxed.gpu.global.v4.b32 [%0], {%1,%2,%3,%4};" :: "l"(zp + (i >> 1) * 16384 - (i & 1) * 512), "r"(y[i][0]), "r"(y[i][1]), "r"(y[i][2]), "r"(y[i][3]) : "memory");
                if (!ZE) red_if(zc, 8, lane == r);
                mbar_arrive_if(r == 4 ? BAR(B_TD) : BAR(B_YE + (r & 1)), lane <= (r == 4));
                mbar_arrive_if(BAR(B_H + r), tid == 352);
                STAMPIF(wv, 75 + r);
                STAMPR(7);
            }
            auto x1_release = [&]() {
                if (l0) asm volatile("fence.release.gpu;\n red.relaxed.gpu.global.add.u32 [%0], 16;" :: "l"(CNT(C_Z + tile, 6)) : "memory");
                __syncwarp();
            };
            const float e0 = ((q & 2) ? sa[2] : sa[0]) + __shfl_xor_sync(~0u, (q & 2) ? sa[0] : sa[2], 2), e1 = ((q & 2) ? sa[3] : sa[1]) + __shfl_xor_sync(~0u, (q & 2) ? sa[1] : sa[3], 2);
            float e = ((q & 1) ? e1 : e0) + __shfl_xor_sync(~0u, (q & 1) ? e0 : e1, 1);
            if (wv) sts32(sb + TAB2 + lane * 4, __float_as_uint(e));
            bar_sync(4, 64);
            if (wv) { if (!FLATE) x1_release(); }
            else {
                uint32_t oth; asm volatile("ld.shared.b32 %0, [%1];" : "=r"(oth) : "r"(sb + TAB2 + lane * 4) : "memory");
                e += __uint_as_float(oth);
                const float mu = e * (1.f / D_), ve = fmaxf(__shfl_down_sync(~0u, e, 1) * (1.f / D_) - mu * mu, 0.f) + 1e-5f, r_ = rsqrt_(ve);
                if (!(q & 1)) stg_rlx128(SC(st2, (ft * 16 + 15 - rr - 4 * q) * 16), split2(-mu), split2(ve * r_), __float_as_uint(r_ * r_), epoch);
            }
            if (WDP == 0 && !wv && elect()) pf_l2(P.Wd + b * 15360, 15360);
            mbar_wait(BAR(B_UD), 0);
            if (!(WI & 2)) pause(D_UT);
            if (WDP == 1 && !wv && elect()) pf_l2(P.Wd + b * 15360, 15360);
            const char* up = SC(ut, (wv * 1536 + js * 192 + 2 * lane) * 8);
            uint4 v[15] = {};
            _Pragma("unroll 1") for (int it = 0; it < ((WI & 2) ? 0 : 20000); it++) {
                uint32_t bad = 0;
                #pragma unroll
                for (int i = 0; i < 15; i++) v[i] = ldg_rlx2x64(up + (i / 3) * 24576 + (i % 3) * 512);
                #pragma unroll
                for (int i = 0; i < 15; i++) bad |= (v[i].x ^ epoch) | (v[i].z ^ epoch);
                if (!__any_sync(~0u, (bad & 7) != 0)) break;
            }
            #pragma unroll
            for (int n = 0; n < 3; n++) {
                float f[4];
                #pragma unroll
                for (int j = 0; j < 4; j++) f[j] = (__uint_as_float((&v[n].x)[j]) + __uint_as_float((&v[3 + n].x)[j])) + (__uint_as_float((&v[6 + n].x)[j]) + __uint_as_float((&v[9 + n].x)[j])) + __uint_as_float((&v[12 + n].x)[j]);
                const uint32_t ta = sb + TAB1 + ((n == 2 ? 32 + wv * 8 : n * 8 + wv * 16) + rr) * 48 + q * 4, th2 = pack2(f[1], f[3]);
                sts32(ta, pack2(f[0], f[2])); sts32(ta + 16, th2); sts32(ta + 32, pack2(f[1] - bflo(th2), f[3] - bfhi(th2)));
            }
            if (lane < 20) sts32(sb + TAB1 + 48 * 48 + lane * 4, 0);
            fence_async_smem();
            __syncwarp();
            mbar_arrive_if(BAR(B_T1), l0);
            STAMPIF(hw == 3, 43);
        }
        asm volatile("setmaxnreg.dec.sync.aligned.u32 40;");
        const uint32_t ep2 = __shfl_sync(~0u, epoch, 0), tg2 = ep2 << 7;
        const char* hfl = CNT(C_HH + tile * 2 + kh, 0);
        auto hh_src = [&](int j) { const int c = (j * 11) >> 5, m = j - 3 * c; return SC(hh, (tile * 24 + (kh * 4 + m + (m >= dq)) * 3 + (c ^ (c < 2))) * 16384); };
        if (hw == 0 || hw == 3) {
            if (hw == 0) {
            if (elect()) {
                const CUtensorMap *m1 = rank ? &M.u1 : &M.g1, *m2 = rank ? &M.u2 : &M.g2;
                const char* pw = P.Wg + (b + 128 * (NWP >> 1)) * 3072;
                const long long dw = P.Wu - P.Wg;
                pf_map(m1);
                _Pragma("unroll 1") for (int n = 0; n < 20; n += 2) {
                    #pragma unroll
                    for (int h = 0; h < 2; h++) {
                        const uint32_t so = (n & 2) + h;
                        mbar_wait(BAR(B_WE) + so * 8, (n >> 2) & 1);
                        mbar_expect(BAR(B_WF) + so * 8, 16384);
                        tma3d_mc(sb + WR + rank * 8192 + so * 16384, m1, (n + h) * 32, js * 3, BAR(B_WF) + so * 8);
                        if (n >= WP0 && n < WP0 + 10 - NWP) pf_l2(pw + h * dw, 3072);
                    }
                    if (n >= WP0) pw += 128 * 3072;
                    if (WDP >= 8 && n >= WDP && n < WDP + 6) pf_l2(P.Wd + b * 15360 + (n - WDP) * 2560, 5120);
                }
                _Pragma("unroll 1") for (int n = 0; n < 10; n++) {
                    const uint32_t so = n & 3;
                    mbar_wait(BAR(B_WE) + so * 8, ((n >> 2) & 1) ^ 1);
                    mbar_expect(BAR(B_WF) + so * 8, 16384);
                    tma2d_mc(sb + WR + rank * 8192 + so * 16384, m2, js * 192 + 128, n * 64, BAR(B_WF) + so * 8);
                }
            }
            } else {
                const char* gp = SC(mod, (320 + dq * 80 + lane) * 8);
                auto gaddr = [&](int i) { return gp + i * 192; };
                uint2 gv[3];
                #pragma unroll
                for (int i = 0; i < 3; i++) gv[i] = ldg_rlx64(gaddr(i));
                ll_wait<3>(gv, ep2, gaddr);
                mbar_wait(BAR(B_HD), 0);
                red_if(hfl + lane * 4, 32, l0);
                STAMP(36);
                #pragma unroll
                for (int n = 0; n < 3; n++) sts32(sb + GBT + q * 80 + (rr + 6 * n) * 4, gv[n].x);
                __syncwarp();
                mbar_arrive_if(BAR(B_GB), lane < 2);
                mbar_wait(BAR(B_HD + 1), 0);
                red_if(hfl + lane * 4, 32, lane == 1);
            }
            if (elect()) {
                _Pragma("unroll 1") for (int j = 3 - hw; j < 6 + hw; j += j == 2 ? 4 : 1) {
                    const int c = (j * 11) >> 5;
                    const char* src = hh_src(j);
                    mbar_expect(BAR(B_AL + j), 16384);
                    if (j == 3 * c) { mbar_wait(BAR(B_HD + c), 0); if (c == 2) { red_if(hfl + 8, 32, true); STAMP(40); pause(D_H2); } poll_cnt(hfl + c * 4, tg2); fence_async_glob(); STAMPIF(c != 1, c ? 32 : 38); }
                    mbar_wait(c == 1 ? BAR(B_S0) : BAR(B_HS + j - 3 * c), c == 2);
                    bulk_g2s(sb + (j < 2 ? j + 12 : j < 8 ? j + 6 : 8) * 16384, src, 16384, BAR(B_AL + j));
                }
                if (hw == 0) { poll_cnt(CNT(C_Z + tile, 6), tg2); fence_acq(); mbar_arrive_if(BAR(B_OI), true); }
            }
        } else if (wv) {
            {
                if (lane < 10) mbar_expect(BAR(B_AL + lane), 16384);
                if (elect()) { pf_map(&M.g2); pf_map(&M.u2); }
                const char *zc = CNT(C_Z + tile, lane & 7), *zp = SC(z, tile * 163840);
                uint32_t rtp = 0, zv = tg2 - 1, al = BAR(B_AL), dst = sb;
                const uint32_t vo = lane * 128 + (lane & 3) * 16 + (lane & 8) * 8 + (lane & 4);
                int zr = 0;
                _Pragma("unroll 1") for (int i = 0; i < 19; i++) {
                    if (zr < 5) {
                        const uint32_t fre = BAR(zr == 4 ? B_UD : zr ? B_RD + 3 + (zr > 1) : B_RD);
                        bool go = (__ballot_sync(~0u, (int)(zv - tg2) >= 0) >> zr) & 1;
                        if (2 * zr <= i) {
                            mbar_wait(fre, 0);
                            if (!go) {
                                if (!mbar_test(BAR(B_H + zr), 1)) { mbar_wait(BAR(B_H + zr), 1); pause(D_PZ); }
                                poll_cnt(CNT(C_Z + tile, zr), tg2);
                            }
                            go = true;
                        } else go = go && mbar_test(fre, 0);
                        if (go) {
                            if (elect()) {
                                fence_async_glob();
                                bulk_g2s(sb + zr * 32768, zp, 16384, BAR(B_AL + 2 * zr));
                                bulk_g2s(sb + zr * 32768 + 16384, zp + 16384, 16384, BAR(B_AL + 2 * zr + 1));
                            }
                            STAMP(80 + zr);
                            zr++; zp += 32768;
                        }
                    }
                    mbar_wait(al, i >= 10);
                    _Pragma("unroll 1") for (int rt = 0; rt < 2000; rt++) {
                        uint32_t v[4];
                        #pragma unroll
                        for (int k = 0; k < 4; k++) asm volatile("ld.shared.b32 %0, [%1];" : "=r"(v[k]) : "r"(dst + vo + k * 4096) : "memory");
                        if (!__any_sync(~0u, ((v[0] ^ ep2) | (v[1] ^ ep2) | (v[2] ^ ep2) | (v[3] ^ ep2)) & 1)) break;
                        int i_ = i; asm volatile("" : "+r"(i_));
                        VALIF(true, 87 + (i >= 10), 1);
                        if (elect()) { mbar_expect(BAR(B_RT), 16384); bulk_g2s(dst, i_ < 10 ? SC(z, (tile * 10 + i_) * 16384) : hh_src(i_ - 10), 16384, BAR(B_RT)); }
                        mbar_wait(BAR(B_RT), rtp);
                        rtp ^= 1;
                    }
                    mbar_arrive_if(al - 8 * (B_AL - B_AF), l0);
                    if (zr < 5) zv = ldg_rlx32(zc);
                    al += i == 9 ? -72 : 8; dst += i == 9 ? 49152 : i == 11 || i == 17 ? -81920 : 16384;
                    STAMPIF(i == 0 || i == 10 || i == 16, i == 10 ? 37 : i ? 74 : 42);
                }
            }
        } else if (elect()) {
            if (WDP == 2) pf_l2(P.Wd + b * 15360, 15360);
            if (FLATE) asm volatile("fence.release.gpu;\n red.relaxed.gpu.global.add.u32 [%0], 16;" :: "l"(CNT(C_Z + tile, 6)) : "memory");
            pf_map(&M.wn); pf_map(&M.wd); pf_map(&M.out);
            int g = 0, c = 0, m = -3;
            _Pragma("unroll 1") for (int n = 0; n < 12; n++) {
                const uint32_t st = sb + G2B + g * 20480 + rank * 10240, f = BAR(B_G2F + g);
                mbar_wait(BAR(B_G2E + g), n >= 6);
                mbar_expect(f, 20480);
                if (m < 0) tma3d_mc(st, &M.wn, (js * 3 + n) * 64 + rank * 32, dq * 5, f);
                else tma5d_mc(st, &M.wd, ((kh * 4 + m + (m >= dq)) * 3 + (c ^ (c < 2))) * 8 + rank * 4, dq * 5, f);
                g = g == 5 ? 0 : g + 1;
                if (++m == 3) { m = 0; c++; }
            }
        }
    }
}

typedef CUresult (*EncodeFn)(CUtensorMap*, CUtensorMapDataType, cuuint32_t, void*, const cuuint64_t*, const cuuint64_t*, const cuuint32_t*, const cuuint32_t*,
                             CUtensorMapInterleave, CUtensorMapSwizzle, CUtensorMapL2promotion, CUtensorMapFloatOOBfill);
void enc(EncodeFn fn, CUtensorMap* m, const void* ptr, int rank, const cuuint64_t* dims, const cuuint64_t* strides, const cuuint32_t* box, CUtensorMapSwizzle sw,
         CUtensorMapL2promotion pr = CU_TENSOR_MAP_L2_PROMOTION_L2_128B) {
    cuuint32_t es[5] = {1, 1, 1, 1, 1};
    fn(m, CU_TENSOR_MAP_DATA_TYPE_BFLOAT16, rank, (void*)ptr, dims, strides, box, es, CU_TENSOR_MAP_INTERLEAVE_NONE, sw,
       pr, CU_TENSOR_MAP_FLOAT_OOB_FILL_NONE);
}
}

extern "C" void kernel_launch(void* const* d_in, const int* in_sizes, int n_in, void* d_out, int out_size) {
    void* fnp = nullptr; cudaDriverEntryPointQueryResult st;
    cudaGetDriverEntryPoint("cuTensorMapEncodeTiled", &fnp, cudaEnableDefault, &st);
    EncodeFn fn = (EncodeFn)fnp;
    void* scr;
    cudaGetSymbolAddress(&scr, g_s);
    Maps M; Ptrs P;
    P.k = (const char*)d_in[1]; P.v = (const char*)d_in[2]; P.shift = (const char*)d_in[3]; P.ssm = (const char*)d_in[4]; P.ssmD = (const char*)d_in[5]; P.Wg = (const char*)d_in[7]; P.Wu = (const char*)d_in[8];
    P.Wd = (const char*)d_in[9]; P.c = (const char*)d_in[10]; P.out = (char*)d_out; P.scr = (char*)scr;
    { cuuint64_t d[4] = {640, 2, 256, 4}, s[3] = {1280, 8 * 1280, 2 * 1280}; cuuint32_t b1[4] = {64, 2, 5, 4}, b2[4] = {64, 2, 4, 4};
      enc(fn, &M.k, d_in[1], 4, d, s, b1, CU_TENSOR_MAP_SWIZZLE_128B); enc(fn, &M.v, d_in[2], 4, d, s, b2, CU_TENSOR_MAP_SWIZZLE_128B); }
    { cuuint64_t d[3] = {32, 2048, 20}, s[2] = {1280, 64}; cuuint32_t b1[3] = {32, 16, 4};
      enc(fn, &M.q, d_in[0], 3, d, s, b1, CU_TENSOR_MAP_SWIZZLE_NONE); }
    { cuuint64_t d[5] = {2048, 2, 4, 4, 20}, s[4] = {4096, 8 * 4096, 2 * 4096, 32 * 4096}; cuuint32_t b1[5] = {16, 2, 4, 4, 4};
      enc(fn, &M.y, (char*)scr + offsetof(Scratch, yT), 5, d, s, b1, CU_TENSOR_MAP_SWIZZLE_32B, CU_TENSOR_MAP_L2_PROMOTION_NONE); }
    { cuuint64_t d[3] = {64, 640, 24}, s[2] = {3072, 128}; cuuint32_t b1[3] = {64, 32, 2};
      enc(fn, &M.g1, P.Wg, 3, d, s, b1, CU_TENSOR_MAP_SWIZZLE_128B); enc(fn, &M.u1, P.Wu, 3, d, s, b1, CU_TENSOR_MAP_SWIZZLE_128B); }
    { cuuint64_t d[2] = {1536, 640}, s[1] = {3072}; cuuint32_t b1[2] = {64, 64};
      enc(fn, &M.g2, P.Wg, 2, d, s, b1, CU_TENSOR_MAP_SWIZZLE_128B); enc(fn, &M.u2, P.Wu, 2, d, s, b1, CU_TENSOR_MAP_SWIZZLE_128B); }
    { cuuint64_t d[5] = {32, 2, 192, 4, 20}, s[4] = {1280, 8 * 1280, 2 * 1280, 64}; cuuint32_t b1[5] = {32, 2, 4, 4, 5};
      enc(fn, &M.wd, P.Wd, 5, d, s, b1, CU_TENSOR_MAP_SWIZZLE_64B); }
    { cuuint64_t d[3] = {32, 1536, 20}, s[2] = {1280, 64}; cuuint32_t b1[3] = {32, 32, 5};
      enc(fn, &M.wn, P.Wd, 3, d, s, b1, CU_TENSOR_MAP_SWIZZLE_64B); }
    { cuuint64_t d[2] = {3840, 640}, s[1] = {7680}; cuuint32_t b1[2] = {64, 160};
      enc(fn, &M.wm, d_in[11], 2, d, s, b1, CU_TENSOR_MAP_SWIZZLE_128B); }
    { cuuint64_t d[3] = {160, 4, 2048}, s[2] = {320, 1280}; cuuint32_t b1[3] = {168, 1, 8};
      enc(fn, &M.out, d_out, 3, d, s, b1, CU_TENSOR_MAP_SWIZZLE_NONE); }
    cudaFuncSetAttribute(fused_kernel, cudaFuncAttributeMaxDynamicSharedMemorySize, SMEM_BYTES);
    fused_kernel<<<132, 384, SMEM_BYTES>>>(P, M);
}
```
